```python
import torch

def _softmax(x, axis=-1):
    return torch.softmax(x, dim=axis)
def _gelu(x):
    return torch.nn.functional.gelu(x, approximate="tanh")
def _silu(x):
    return torch.nn.functional.silu(x)
def _sigmoid(x):
    return torch.sigmoid(x)
def _layernorm(x, axis=-1, eps=1e-5):
    m = x.mean(dim=axis, keepdim=True)
    v = x.var(dim=axis, keepdim=True, unbiased=False)
    return (x - m) / torch.sqrt(v + eps)
def _scatter_add(tgt, idx, src, axis=0):
    return tgt.clone().index_add_(axis, idx, src)
def _segment_sum(src, seg, n):
    out = torch.zeros((n,) + src.shape[1:], dtype=src.dtype)
    return out.index_add_(0, seg, src)
def _pad(x, pw):
    flat = tuple(v for pair in reversed(pw) for v in pair)
    return torch.nn.functional.pad(x, flat)

kernel_name = 'recurrent_scan__grouped_kv_mqa__dense_activation_squared_relu__prompt'

def setup_inputs():

    _w = (lambda a: (lambda t: t.to(torch.bfloat16) if t.is_floating_point() else t)(torch.as_tensor(a)))
    def _A_setup():
        B, S, D, H = 1, 2048, 512, 32
        Dh = D // H
        return {
            "x": _w((lambda *s: torch.randn(*s, dtype=torch.bfloat16) * 0.05)(B, S, D)),
            "wq": _w((lambda *s: torch.randn(*s, dtype=torch.bfloat16) * 0.05)(D, H * Dh)),
            "wk": _w((lambda *s: torch.randn(*s, dtype=torch.bfloat16) * 0.05)(D, Dh)),
            "wv": _w((lambda *s: torch.randn(*s, dtype=torch.bfloat16) * 0.05)(D, Dh)),
            "wo": _w((lambda *s: torch.randn(*s, dtype=torch.bfloat16) * 0.05)(H * Dh, D)),
        }
    _A_in = _A_setup()

    def _B_setup():
        B, S, D, F = 1, 2048, 512, 1792
        return {
            "x": _w((lambda *s: torch.randn(*s, dtype=torch.bfloat16) * 0.05)(B, S, D)),
            "w1": _w((lambda *s: torch.randn(*s, dtype=torch.bfloat16) * 0.05)(D, F)),
            "b1": _w((lambda *s: torch.randn(*s, dtype=torch.bfloat16) * 0.4)(F)),
            "w2": _w((lambda *s: torch.randn(*s, dtype=torch.bfloat16) * 0.05)(F, D)),
            "b2": _w((lambda *s: torch.randn(*s, dtype=torch.bfloat16) * 1.6)(D)),
        }
    _B_in = _B_setup()

    return {
        "A_x": _A_in["x"],
        "A_wq": _A_in["wq"],
        "A_wk": _A_in["wk"],
        "A_wv": _A_in["wv"],
        "A_wo": _A_in["wo"],
        "B_x": _B_in["x"],
        "B_w1": _B_in["w1"],
        "B_b1": _B_in["b1"],
        "B_w2": _B_in["w2"],
        "B_b2": _B_in["b2"],
    }

def reference(A_x, A_wq, A_wk, A_wv, A_wo, B_x, B_w1, B_b1, B_w2, B_b2):
    def _A_ref(x, wq, wk, wv, wo):
        B, S, D = x.shape
        H = 32
        Dh = D // H
        q = (lambda x, *d: x.permute(*d))((x @ wq).reshape(B, S, H, Dh), 0, 2, 1, 3)
        k = x @ wk
        v = x @ wv
        scores = torch.einsum("bhqd,bkd->bhqk", q, k) * (Dh ** -0.5)
        p = _softmax(scores, axis=-1)
        o = torch.einsum("bhqk,bkd->bhqd", p, v)
        return (lambda x, *d: x.permute(*d))(o, 0, 2, 1, 3).reshape(B, S, H * Dh) @ wo

    def _B_ref(x, w1, b1, w2, b2):
        h = torch.einsum("bsd,df->bsf", x, w1) + b1
        zero = torch.zeros_like(h)
        r = torch.where(h > zero, h, zero)
        h = r * r
        out = torch.einsum("bsf,fd->bsd", h, w2) + b2
        return out

    x = A_x
    xn = _layernorm(x, axis=-1)
    s = _A_ref(xn, A_wq, A_wk, A_wv, A_wo)
    g = _silu(_B_ref(xn, B_w1, B_b1, B_w2, B_b2))
    return x + s * g
```

```cpp
#include <cuda_runtime.h>
#include <cuda_bf16.h>
#include <cuda.h>
#include <stdint.h>

namespace {

constexpr int S_LEN = 2048, D_MODEL = 512, F_DIM = 1792;

__device__ __align__(1024) __nv_bfloat16 g_Q[S_LEN * D_MODEL];
__device__ __align__(1024) __nv_bfloat16 g_KV[4 * S_LEN * 8];
__device__ __align__(1024) __nv_bfloat16 g_H[S_LEN * F_DIM];
__device__ __align__(1024) __nv_bfloat16 g_O[S_LEN * D_MODEL];
__device__ __align__(1024) float g_kvmax[256];

__device__ __forceinline__ uint32_t smem_u32(const void* p) { return (uint32_t)__cvta_generic_to_shared(p); }
__device__ __forceinline__ void wg_fence() { asm volatile("wgmma.fence.sync.aligned;" ::: "memory"); }
__device__ __forceinline__ void wg_commit() { asm volatile("wgmma.commit_group.sync.aligned;" ::: "memory"); }
template <int N> __device__ __forceinline__ void wg_wait() { asm volatile("wgmma.wait_group.sync.aligned %0;" ::"n"(N) : "memory"); }
__device__ __forceinline__ void fence_proxy_async() { asm volatile("fence.proxy.async.shared::cta;" ::: "memory"); }
__device__ __forceinline__ void mbar_init(uint32_t bar, int cnt) { asm volatile("mbarrier.init.shared::cta.b64 [%0], %1;" ::"r"(bar), "r"(cnt) : "memory"); }
__device__ __forceinline__ void mbar_init_fence() { asm volatile("fence.mbarrier_init.release.cluster;" ::: "memory"); }
__device__ __forceinline__ void mbar_expect_tx(uint32_t bar, uint32_t bytes) {
    asm volatile("mbarrier.arrive.expect_tx.shared::cta.b64 _, [%0], %1;" ::"r"(bar), "r"(bytes) : "memory");
}
__device__ __forceinline__ void mbar_arrive(uint32_t bar) { asm volatile("mbarrier.arrive.shared::cta.b64 _, [%0];" ::"r"(bar) : "memory"); }
__device__ __forceinline__ bool mbar_try(uint32_t bar, uint32_t parity) {
    uint32_t ok;
    asm volatile("{\n.reg .pred p;\nmbarrier.try_wait.parity.shared::cta.b64 p, [%1], %2;\nselp.u32 %0, 1, 0, p;\n}\n"
                 : "=r"(ok) : "r"(bar), "r"(parity) : "memory");
    return ok != 0;
}
__device__ __forceinline__ void mbar_wait(uint32_t bar, uint32_t parity) {
    if (mbar_try(bar, parity)) return;
    uint32_t n = 0;
    while (!mbar_try(bar, parity)) {
        if (++n > (1u << 24)) __trap();
    }
}
__device__ __forceinline__ void bulk_g2s(uint32_t dst, const void* src, uint32_t bytes, uint32_t bar) {
    asm volatile("cp.async.bulk.shared::cluster.global.mbarrier::complete_tx::bytes [%0], [%1], %2, [%3];"
                 ::"r"(dst), "l"(src), "r"(bytes), "r"(bar) : "memory");
}
__device__ __forceinline__ void tma_load_2d(uint32_t dst, const CUtensorMap* tm, int c0, int c1, uint32_t bar) {
    asm volatile("cp.async.bulk.tensor.2d.shared::cluster.global.mbarrier::complete_tx::bytes [%0], [%1, {%3, %4}], [%2];"
                 ::"r"(dst), "l"((uint64_t)tm), "r"(bar), "r"(c0), "r"(c1) : "memory");
}
__device__ __forceinline__ void tma_store_2d(const CUtensorMap* tm, uint32_t src, int c0, int c1) {
    asm volatile("cp.async.bulk.tensor.2d.global.shared::cta.bulk_group [%0, {%2, %3}], [%1];"
                 ::"l"((uint64_t)tm), "r"(src), "r"(c0), "r"(c1) : "memory");
}
__device__ __forceinline__ void tma_store_commit() { asm volatile("cp.async.bulk.commit_group;" ::: "memory"); }
__device__ __forceinline__ void tma_store_wait() { asm volatile("cp.async.bulk.wait_group 0;" ::: "memory"); }
__device__ __forceinline__ void tma_prefetch_desc(const CUtensorMap* tm) { asm volatile("prefetch.tensormap [%0];" ::"l"((uint64_t)tm) : "memory"); }
__device__ __forceinline__ void named_bar_sync(int id, int n) { asm volatile("bar.sync %0, %1;" ::"r"(id), "r"(n) : "memory"); }
__device__ __forceinline__ void pdl_wait() { asm volatile("griddepcontrol.wait;" ::: "memory"); }
__device__ __forceinline__ void pdl_launch() { asm volatile("griddepcontrol.launch_dependents;" ::: "memory"); }
template <int N> __device__ __forceinline__ void reg_alloc() { asm volatile("setmaxnreg.inc.sync.aligned.u32 %0;" ::"n"(N)); }
template <int N> __device__ __forceinline__ void reg_dealloc() { asm volatile("setmaxnreg.dec.sync.aligned.u32 %0;" ::"n"(N)); }
__device__ __forceinline__ float ex2(float x) { float y; asm("ex2.approx.ftz.f32 %0, %1;" : "=f"(y) : "f"(x)); return y; }
__device__ __forceinline__ uint32_t pack_bf16(float lo, float hi) {
    uint32_t r; asm("cvt.rn.bf16x2.f32 %0, %1, %2;" : "=r"(r) : "f"(hi), "f"(lo)); return r;
}
__device__ __forceinline__ float bf_lo(uint32_t v) { return __uint_as_float(v << 16); }
__device__ __forceinline__ float bf_hi(uint32_t v) { return __uint_as_float(v & 0xFFFF0000u); }
__device__ __forceinline__ void stmatrix_x4(uint32_t addr, uint32_t r0, uint32_t r1, uint32_t r2, uint32_t r3) {
    asm volatile("stmatrix.sync.aligned.m8n8.x4.shared.b16 [%0], {%1,%2,%3,%4};" ::"r"(addr), "r"(r0), "r"(r1), "r"(r2), "r"(r3) : "memory");
}
__device__ __forceinline__ uint64_t make_desc(uint32_t addr, uint32_t lbo, uint32_t sbo, uint32_t swz) {
    return (uint64_t)((addr & 0x3FFFF) >> 4) | ((uint64_t)(lbo >> 4) << 16) | ((uint64_t)(sbo >> 4) << 32) | ((uint64_t)swz << 62);
}

__device__ __forceinline__ void wgmma_ss_n256_tb(float* d, uint64_t descA, uint64_t descB, int scaleD) {
    asm volatile("{\n.reg .pred p;\nsetp.ne.b32 p, %130, 0;\n"
      "wgmma.mma_async.sync.aligned.m64n256k16.f32.bf16.bf16 {%0,%1,%2,%3,%4,%5,%6,%7,%8,%9,%10,%11,%12,%13,%14,%15,%16,%17,%18,%19,%20,%21,%22,%23,%24,%25,%26,%27,%28,%29,%30,%31,%32,%33,%34,%35,%36,%37,%38,%39,%40,%41,%42,%43,%44,%45,%46,%47,%48,%49,%50,%51,%52,%53,%54,%55,%56,%57,%58,%59,%60,%61,%62,%63,%64,%65,%66,%67,%68,%69,%70,%71,%72,%73,%74,%75,%76,%77,%78,%79,%80,%81,%82,%83,%84,%85,%86,%87,%88,%89,%90,%91,%92,%93,%94,%95,%96,%97,%98,%99,%100,%101,%102,%103,%104,%105,%106,%107,%108,%109,%110,%111,%112,%113,%114,%115,%116,%117,%118,%119,%120,%121,%122,%123,%124,%125,%126,%127}, %128, %129, p, 1, 1, 0, 1;\n}\n"
      : "+f"(d[0]), "+f"(d[1]), "+f"(d[2]), "+f"(d[3]), "+f"(d[4]), "+f"(d[5]), "+f"(d[6]), "+f"(d[7]), "+f"(d[8]), "+f"(d[9]), "+f"(d[10]), "+f"(d[11]), "+f"(d[12]), "+f"(d[13]), "+f"(d[14]), "+f"(d[15]), "+f"(d[16]), "+f"(d[17]), "+f"(d[18]), "+f"(d[19]), "+f"(d[20]), "+f"(d[21]), "+f"(d[22]), "+f"(d[23]), "+f"(d[24]), "+f"(d[25]), "+f"(d[26]), "+f"(d[27]), "+f"(d[28]), "+f"(d[29]), "+f"(d[30]), "+f"(d[31]), "+f"(d[32]), "+f"(d[33]), "+f"(d[34]), "+f"(d[35]), "+f"(d[36]), "+f"(d[37]), "+f"(d[38]), "+f"(d[39]), "+f"(d[40]), "+f"(d[41]), "+f"(d[42]), "+f"(d[43]), "+f"(d[44]), "+f"(d[45]), "+f"(d[46]), "+f"(d[47]), "+f"(d[48]), "+f"(d[49]), "+f"(d[50]), "+f"(d[51]), "+f"(d[52]), "+f"(d[53]), "+f"(d[54]), "+f"(d[55]), "+f"(d[56]), "+f"(d[57]), "+f"(d[58]), "+f"(d[59]), "+f"(d[60]), "+f"(d[61]), "+f"(d[62]), "+f"(d[63]), "+f"(d[64]), "+f"(d[65]), "+f"(d[66]), "+f"(d[67]), "+f"(d[68]), "+f"(d[69]), "+f"(d[70]), "+f"(d[71]), "+f"(d[72]), "+f"(d[73]), "+f"(d[74]), "+f"(d[75]), "+f"(d[76]), "+f"(d[77]), "+f"(d[78]), "+f"(d[79]), "+f"(d[80]), "+f"(d[81]), "+f"(d[82]), "+f"(d[83]), "+f"(d[84]), "+f"(d[85]), "+f"(d[86]), "+f"(d[87]), "+f"(d[88]), "+f"(d[89]), "+f"(d[90]), "+f"(d[91]), "+f"(d[92]), "+f"(d[93]), "+f"(d[94]), "+f"(d[95]), "+f"(d[96]), "+f"(d[97]), "+f"(d[98]), "+f"(d[99]), "+f"(d[100]), "+f"(d[101]), "+f"(d[102]), "+f"(d[103]), "+f"(d[104]), "+f"(d[105]), "+f"(d[106]), "+f"(d[107]), "+f"(d[108]), "+f"(d[109]), "+f"(d[110]), "+f"(d[111]), "+f"(d[112]), "+f"(d[113]), "+f"(d[114]), "+f"(d[115]), "+f"(d[116]), "+f"(d[117]), "+f"(d[118]), "+f"(d[119]), "+f"(d[120]), "+f"(d[121]), "+f"(d[122]), "+f"(d[123]), "+f"(d[124]), "+f"(d[125]), "+f"(d[126]), "+f"(d[127])
      : "l"(descA), "l"(descB), "r"(scaleD));
}
__device__ __forceinline__ void wgmma_ss_n128_tb(float* d, uint64_t descA, uint64_t descB, int scaleD) {
    asm volatile("{\n.reg .pred p;\nsetp.ne.b32 p, %66, 0;\n"
      "wgmma.mma_async.sync.aligned.m64n128k16.f32.bf16.bf16 {%0,%1,%2,%3,%4,%5,%6,%7,%8,%9,%10,%11,%12,%13,%14,%15,%16,%17,%18,%19,%20,%21,%22,%23,%24,%25,%26,%27,%28,%29,%30,%31,%32,%33,%34,%35,%36,%37,%38,%39,%40,%41,%42,%43,%44,%45,%46,%47,%48,%49,%50,%51,%52,%53,%54,%55,%56,%57,%58,%59,%60,%61,%62,%63}, %64, %65, p, 1, 1, 0, 1;\n}\n"
      : "+f"(d[0]), "+f"(d[1]), "+f"(d[2]), "+f"(d[3]), "+f"(d[4]), "+f"(d[5]), "+f"(d[6]), "+f"(d[7]), "+f"(d[8]), "+f"(d[9]), "+f"(d[10]), "+f"(d[11]), "+f"(d[12]), "+f"(d[13]), "+f"(d[14]), "+f"(d[15]), "+f"(d[16]), "+f"(d[17]), "+f"(d[18]), "+f"(d[19]), "+f"(d[20]), "+f"(d[21]), "+f"(d[22]), "+f"(d[23]), "+f"(d[24]), "+f"(d[25]), "+f"(d[26]), "+f"(d[27]), "+f"(d[28]), "+f"(d[29]), "+f"(d[30]), "+f"(d[31]), "+f"(d[32]), "+f"(d[33]), "+f"(d[34]), "+f"(d[35]), "+f"(d[36]), "+f"(d[37]), "+f"(d[38]), "+f"(d[39]), "+f"(d[40]), "+f"(d[41]), "+f"(d[42]), "+f"(d[43]), "+f"(d[44]), "+f"(d[45]), "+f"(d[46]), "+f"(d[47]), "+f"(d[48]), "+f"(d[49]), "+f"(d[50]), "+f"(d[51]), "+f"(d[52]), "+f"(d[53]), "+f"(d[54]), "+f"(d[55]), "+f"(d[56]), "+f"(d[57]), "+f"(d[58]), "+f"(d[59]), "+f"(d[60]), "+f"(d[61]), "+f"(d[62]), "+f"(d[63])
      : "l"(descA), "l"(descB), "r"(scaleD));
}
__device__ __forceinline__ void wgmma_ss_n64_tb(float* d, uint64_t descA, uint64_t descB, int scaleD) {
    asm volatile("{\n.reg .pred p;\nsetp.ne.b32 p, %34, 0;\n"
      "wgmma.mma_async.sync.aligned.m64n64k16.f32.bf16.bf16 {%0,%1,%2,%3,%4,%5,%6,%7,%8,%9,%10,%11,%12,%13,%14,%15,%16,%17,%18,%19,%20,%21,%22,%23,%24,%25,%26,%27,%28,%29,%30,%31}, %32, %33, p, 1, 1, 0, 1;\n}\n"
      : "+f"(d[0]), "+f"(d[1]), "+f"(d[2]), "+f"(d[3]), "+f"(d[4]), "+f"(d[5]), "+f"(d[6]), "+f"(d[7]), "+f"(d[8]), "+f"(d[9]), "+f"(d[10]), "+f"(d[11]), "+f"(d[12]), "+f"(d[13]), "+f"(d[14]), "+f"(d[15]), "+f"(d[16]), "+f"(d[17]), "+f"(d[18]), "+f"(d[19]), "+f"(d[20]), "+f"(d[21]), "+f"(d[22]), "+f"(d[23]), "+f"(d[24]), "+f"(d[25]), "+f"(d[26]), "+f"(d[27]), "+f"(d[28]), "+f"(d[29]), "+f"(d[30]), "+f"(d[31])
      : "l"(descA), "l"(descB), "r"(scaleD));
}
__device__ __forceinline__ void wgmma_qk_n64(float* d, const uint32_t* a, uint64_t descB) {
    asm volatile("wgmma.mma_async.sync.aligned.m64n64k16.f32.bf16.bf16 {%0,%1,%2,%3,%4,%5,%6,%7,%8,%9,%10,%11,%12,%13,%14,%15,%16,%17,%18,%19,%20,%21,%22,%23,%24,%25,%26,%27,%28,%29,%30,%31}, {%32,%33,%34,%35}, %36, 0, 1, 1, 0;\n"
      : "=f"(d[0]), "=f"(d[1]), "=f"(d[2]), "=f"(d[3]), "=f"(d[4]), "=f"(d[5]), "=f"(d[6]), "=f"(d[7]), "=f"(d[8]), "=f"(d[9]), "=f"(d[10]), "=f"(d[11]), "=f"(d[12]), "=f"(d[13]), "=f"(d[14]), "=f"(d[15]), "=f"(d[16]), "=f"(d[17]), "=f"(d[18]), "=f"(d[19]), "=f"(d[20]), "=f"(d[21]), "=f"(d[22]), "=f"(d[23]), "=f"(d[24]), "=f"(d[25]), "=f"(d[26]), "=f"(d[27]), "=f"(d[28]), "=f"(d[29]), "=f"(d[30]), "=f"(d[31])
      : "r"(a[0]), "r"(a[1]), "r"(a[2]), "r"(a[3]), "l"(descB));
}
__device__ __forceinline__ void wgmma_qk_n32(float* d, const uint32_t* a, uint64_t descB) {
    asm volatile("wgmma.mma_async.sync.aligned.m64n32k16.f32.bf16.bf16 {%0,%1,%2,%3,%4,%5,%6,%7,%8,%9,%10,%11,%12,%13,%14,%15}, {%16,%17,%18,%19}, %20, 0, 1, 1, 0;\n"
      : "=f"(d[0]), "=f"(d[1]), "=f"(d[2]), "=f"(d[3]), "=f"(d[4]), "=f"(d[5]), "=f"(d[6]), "=f"(d[7]), "=f"(d[8]), "=f"(d[9]), "=f"(d[10]), "=f"(d[11]), "=f"(d[12]), "=f"(d[13]), "=f"(d[14]), "=f"(d[15])
      : "r"(a[0]), "r"(a[1]), "r"(a[2]), "r"(a[3]), "l"(descB));
}


__device__ __forceinline__ void wgmma_pv(float* d, uint32_t a0, uint32_t a1, uint32_t a2, uint32_t a3, uint64_t descB) {
    asm volatile("wgmma.mma_async.sync.aligned.m64n24k16.f32.bf16.bf16 {%0,%1,%2,%3,%4,%5,%6,%7,%8,%9,%10,%11}, {%12,%13,%14,%15}, %16, 1, 1, 1, 1;\n"
                 : "+f"(d[0]), "+f"(d[1]), "+f"(d[2]), "+f"(d[3]), "+f"(d[4]), "+f"(d[5]), "+f"(d[6]), "+f"(d[7]), "+f"(d[8]), "+f"(d[9]), "+f"(d[10]), "+f"(d[11])
                 : "r"(a0), "r"(a1), "r"(a2), "r"(a3), "l"(descB));
}

constexpr int K1_STAGES = 4;
constexpr int K1_BK = 32;
constexpr int K1_PANEL_BYTES = K1_BK * 128;
constexpr int K1_STAGE_BYTES = 5 * K1_PANEL_BYTES;
constexpr int K1_A_BYTES = 128 * 512 * 2;
constexpr int K1_SMEM = K1_A_BYTES + K1_STAGES * K1_STAGE_BYTES + 256 + 1024;
constexpr float Q_SCALE = 0.25f * 1.4426950408889634f;

__device__ __forceinline__ void k1_panel(int g, int i, int& type, int& col) {
    if (g < 6) {
        int p = g * 5 + i;
        if (p < 8) { type = 0; col = p * 64; } else { type = 1; col = (p - 8) * 64; }
    } else {
        if (i < 3) { type = 1; col = (22 + (g - 6) * 3 + i) * 64; } else { type = 2 + (g - 6); col = 0; }
    }
}

__global__ void __launch_bounds__(384, 1)
k1_proj(const __grid_constant__ CUtensorMap tm_wq, const __grid_constant__ CUtensorMap tm_wk,
        const __grid_constant__ CUtensorMap tm_wv, const __grid_constant__ CUtensorMap tm_w1,
        const __grid_constant__ CUtensorMap tm_qo, const __grid_constant__ CUtensorMap tm_ho,
        const __nv_bfloat16* __restrict__ x, const __nv_bfloat16* __restrict__ b1,
        __nv_bfloat16* __restrict__ kv, float* __restrict__ kvmax) {
    extern __shared__ uint8_t smem_raw[];
    const uint32_t sbase = (smem_u32(smem_raw) + 1023) & ~1023u;
    const uint32_t sA = sbase, sB = sbase + K1_A_BYTES;
    const uint32_t bar_full = sB + K1_STAGES * K1_STAGE_BYTES, bar_empty = bar_full + 8 * K1_STAGES;
    const int tid = threadIdx.x, warp = tid >> 5, lane = tid & 31;
    const int rb = blockIdx.x >> 3, grp = blockIdx.x & 7;
    const int npanels = grp < 6 ? 5 : 4;

    if (tid == 256) {
        for (int s = 0; s < K1_STAGES; s++) { mbar_init(bar_full + 8 * s, 1); mbar_init(bar_empty + 8 * s, 8); }
        mbar_init_fence();
    }
    __syncthreads();
    pdl_launch();

    if (warp >= 8) {
        reg_dealloc<40>();
        if (tid == 256) {
            const CUtensorMap* tms[5]; int cols[5];
#pragma unroll
            for (int i = 0; i < 5; i++) {
                int type, col; k1_panel(grp, i, type, col);
                tms[i] = type == 0 ? &tm_wq : type == 1 ? &tm_w1 : type == 2 ? &tm_wk : &tm_wv;
                cols[i] = col;
            }
            for (int ks = 0; ks < 512 / K1_BK; ks++) {
                const int s = ks % K1_STAGES;
                mbar_wait(bar_empty + 8 * s, ((ks / K1_STAGES) & 1) ^ 1);
                mbar_expect_tx(bar_full + 8 * s, npanels * K1_PANEL_BYTES);
#pragma unroll
                for (int i = 0; i < 5; i++)
                    if (i < npanels)
                        tma_load_2d(sB + s * K1_STAGE_BYTES + i * K1_PANEL_BYTES, tms[i], cols[i], ks * K1_BK, bar_full + 8 * s);
            }
        }
    } else {
        reg_alloc<232>();
        const int wg = warp >> 2;
        {
            const uint4* xp = reinterpret_cast<const uint4*>(x + (size_t)(rb * 128 + warp * 16) * D_MODEL);
            uint4 v[16][2];
#pragma unroll
            for (int r = 0; r < 16; r++) { v[r][0] = __ldg(xp + r * 64 + lane); v[r][1] = __ldg(xp + r * 64 + 32 + lane); }
#pragma unroll
            for (int r = 0; r < 16; r++) {
                float f[16];
                const uint32_t w[8] = {v[r][0].x, v[r][0].y, v[r][0].z, v[r][0].w, v[r][1].x, v[r][1].y, v[r][1].z, v[r][1].w};
#pragma unroll
                for (int i = 0; i < 8; i++) { f[2 * i] = bf_lo(w[i]); f[2 * i + 1] = bf_hi(w[i]); }
                float sum = 0.f;
#pragma unroll
                for (int i = 0; i < 16; i++) sum += f[i];
#pragma unroll
                for (int o = 16; o > 0; o >>= 1) sum += __shfl_xor_sync(0xffffffffu, sum, o);
                const float mean = sum * (1.0f / D_MODEL);
                float sq = 0.f;
#pragma unroll
                for (int i = 0; i < 16; i++) { f[i] -= mean; sq += f[i] * f[i]; }
#pragma unroll
                for (int o = 16; o > 0; o >>= 1) sq += __shfl_xor_sync(0xffffffffu, sq, o);
                const float rstd = rsqrtf(sq * (1.0f / D_MODEL) + 1e-5f);
                uint32_t o[8];
#pragma unroll
                for (int i = 0; i < 8; i++) o[i] = pack_bf16(f[2 * i] * rstd, f[2 * i + 1] * rstd);
                const int row = warp * 16 + r;
                const uint32_t a = sA + (lane >> 3) * 16384 + row * 128 + (((lane & 7) ^ (row & 7)) << 4);
                asm volatile("st.shared.v4.b32 [%0], {%1,%2,%3,%4};" ::"r"(a), "r"(o[0]), "r"(o[1]), "r"(o[2]), "r"(o[3]) : "memory");
                asm volatile("st.shared.v4.b32 [%0], {%1,%2,%3,%4};" ::"r"(a + 4 * 16384), "r"(o[4]), "r"(o[5]), "r"(o[6]), "r"(o[7]) : "memory");
            }
            fence_proxy_async();
            named_bar_sync(1 + wg, 128);
        }
        float acc[160];
#pragma unroll
        for (int i = 0; i < 160; i++) acc[i] = 0.f;
        const uint64_t dA0 = make_desc(sA + wg * 8192, 16, 1024, 1);
        const uint64_t dB0 = make_desc(sB, K1_PANEL_BYTES, 1024, 1);
#define K1_MAINLOOP(FIVE)                                                                                          \
        for (int ks = 0; ks < 512 / K1_BK; ks++) {                                                                 \
            const int s = ks % K1_STAGES;                                                                          \
            mbar_wait(bar_full + 8 * s, (ks / K1_STAGES) & 1);                                                     \
            wg_fence();                                                                                            \
            _Pragma("unroll") for (int kk = 0; kk < 2; kk++) {                                                     \
                const uint64_t dA = dA0 + (uint64_t)(((ks >> 1) * 16384 + ((ks & 1) * 2 + kk) * 32) >> 4);         \
                const uint64_t dB = dB0 + (uint64_t)((s * K1_STAGE_BYTES + kk * 2048) >> 4);                       \
                wgmma_ss_n256_tb(acc, dA, dB, (ks | kk) != 0);                                                     \
                if (FIVE) wgmma_ss_n64_tb(acc + 128, dA, dB + (uint64_t)((4 * K1_PANEL_BYTES) >> 4), (ks | kk) != 0); \
            }                                                                                                      \
            wg_commit();                                                                                           \
            if (ks > 0) {                                                                                          \
                wg_wait<1>();                                                                                      \
                if (lane == 0) mbar_arrive(bar_empty + 8 * ((ks - 1) % K1_STAGES));                                \
            }                                                                                                      \
        }                                                                                                          \
        wg_wait<0>();
        if (npanels == 5) { K1_MAINLOOP(true) } else { K1_MAINLOOP(false) }
        named_bar_sync(1 + wg, 128);
        const int g = lane >> 2, t = lane & 3;
        const int wrow = (warp & 3) * 16;
        const int srow = wrow + (lane & 7) + ((lane >> 3) & 1) * 8;
#pragma unroll
        for (int p = 0; p < 5; p++) {
            if (p < npanels) {
                int type, col; k1_panel(grp, p, type, col);
                float* a = acc + p * 32;
                if (type <= 1) {
                    const uint32_t stg = sA + p * 16384 + wg * 8192;
                    uint32_t pk[16];
                    if (type == 0) {
#pragma unroll
                        for (int j = 0; j < 8; j++) {
                            pk[2 * j] = pack_bf16(a[4 * j] * Q_SCALE, a[4 * j + 1] * Q_SCALE);
                            pk[2 * j + 1] = pack_bf16(a[4 * j + 2] * Q_SCALE, a[4 * j + 3] * Q_SCALE);
                        }
                    } else {
#pragma unroll
                        for (int j = 0; j < 8; j++) {
                            const uint32_t bb = __ldg(reinterpret_cast<const uint32_t*>(b1 + col + j * 8 + 2 * t));
                            const float b0 = bf_lo(bb), bb1 = bf_hi(bb);
                            float h0 = fmaxf(a[4 * j] + b0, 0.f), h1 = fmaxf(a[4 * j + 1] + bb1, 0.f);
                            float h2 = fmaxf(a[4 * j + 2] + b0, 0.f), h3 = fmaxf(a[4 * j + 3] + bb1, 0.f);
                            pk[2 * j] = pack_bf16(h0 * h0, h1 * h1);
                            pk[2 * j + 1] = pack_bf16(h2 * h2, h3 * h3);
                        }
                    }
#pragma unroll
                    for (int j = 0; j < 8; j += 2) {
                        const int c16 = j + (lane >> 4);
                        stmatrix_x4(stg + srow * 128 + ((c16 ^ (srow & 7)) << 4), pk[2 * j], pk[2 * j + 1], pk[2 * j + 2], pk[2 * j + 3]);
                    }
                } else {
                    const int key = rb * 128 + wg * 64 + wrow + g;
                    uint32_t* dst = reinterpret_cast<uint32_t*>(kv + (type - 2) * 2 * (S_LEN * 8));
                    uint32_t r00 = pack_bf16(a[0], a[1]), r01 = pack_bf16(a[4], a[5]);
                    uint32_t r10 = pack_bf16(a[2], a[3]), r11 = pack_bf16(a[6], a[7]);
                    dst[key * 4 + t] = r00;
                    dst[S_LEN * 4 + key * 4 + t] = r01;
                    dst[(key + 8) * 4 + t] = r10;
                    dst[S_LEN * 4 + (key + 8) * 4 + t] = r11;
                    float m;
                    if (type == 2) {
                        float n0 = bf_lo(r00) * bf_lo(r00) + bf_hi(r00) * bf_hi(r00) + bf_lo(r01) * bf_lo(r01) + bf_hi(r01) * bf_hi(r01);
                        float n1 = bf_lo(r10) * bf_lo(r10) + bf_hi(r10) * bf_hi(r10) + bf_lo(r11) * bf_lo(r11) + bf_hi(r11) * bf_hi(r11);
                        n0 += __shfl_xor_sync(0xffffffffu, n0, 1); n0 += __shfl_xor_sync(0xffffffffu, n0, 2);
                        n1 += __shfl_xor_sync(0xffffffffu, n1, 1); n1 += __shfl_xor_sync(0xffffffffu, n1, 2);
                        m = fmaxf(n0, n1);
                        if (!(n0 == n0) || !(n1 == n1)) m = __int_as_float(0x7f800000);
                    } else {
                        m = fmaxf(fmaxf(fmaxf(fabsf(bf_lo(r00)), fabsf(bf_hi(r00))), fmaxf(fabsf(bf_lo(r01)), fabsf(bf_hi(r01)))),
                                  fmaxf(fmaxf(fabsf(bf_lo(r10)), fabsf(bf_hi(r10))), fmaxf(fabsf(bf_lo(r11)), fabsf(bf_hi(r11)))));
                    }
#pragma unroll
                    for (int o = 16; o > 0; o >>= 1) m = fmaxf(m, __shfl_xor_sync(0xffffffffu, m, o));
                    if (lane == 0) kvmax[(type - 2) * 128 + rb * 8 + warp] = m;
                }
            }
        }
        fence_proxy_async();
        named_bar_sync(1 + wg, 128);
        if ((tid & 127) == 0) {
#pragma unroll
            for (int p = 0; p < 5; p++) {
                if (p < npanels) {
                    int type, col; k1_panel(grp, p, type, col);
                    if (type <= 1) tma_store_2d(type == 0 ? &tm_qo : &tm_ho, sA + p * 16384 + wg * 8192, col, rb * 128 + wg * 64);
                }
            }
            tma_store_commit();
            tma_store_wait();
        }
    }
}

constexpr int AT_KT = 64;
constexpr int AT_NCHUNK = 8;
constexpr int AT_NSTEP = S_LEN / AT_KT;
constexpr int AT_SPC = AT_NSTEP / AT_NCHUNK;
constexpr int AT_SMEM = 5 * 32768 + 256 + 1024;
constexpr uint32_t AT_SWMASK = 0xF8F8;

#define AT_MAGIC (383.0f + 0.00390625f - 0.5849625f)
__device__ __forceinline__ uint32_t exp2_pair_alu(float x0, float x1) {
    const float t0 = x0 + AT_MAGIC, t1 = x1 + AT_MAGIC;
    const uint32_t y = __byte_perm(__float_as_uint(t0), __float_as_uint(t1), 0x6521);
    const uint32_t e = y & 0x7F807F80u;
    uint32_t uh, p;
    asm("lop3.b32 %0, %1, %2, 0x3F003F00, 0xBE;" : "=r"(uh) : "r"(y), "r"(e));
    asm("fma.rn.bf16x2 %0, %1, %2, %3;" : "=r"(p) : "r"(uh), "r"(y), "r"(e));
    return p;
}

__global__ void __launch_bounds__(512, 1)
k2_attn(const __nv_bfloat16* __restrict__ Q, const __nv_bfloat16* __restrict__ KV, const float* __restrict__ kvmax,
        __nv_bfloat16* __restrict__ O) {
    extern __shared__ uint8_t smem_raw[];
    const uint32_t sbase = (smem_u32(smem_raw) + 1023) & ~1023u;
    const uint32_t bar0 = sbase + 5 * 32768;
    const int tid = threadIdx.x;
    if (tid == 0) {
        for (int i = 0; i < AT_NCHUNK; i++) mbar_init(bar0 + 8 * i, 1);
        mbar_init_fence();
    }
    for (int i = tid; i < S_LEN; i += 512)
        asm volatile("st.shared.v4.b32 [%0], {%1,%2,%2,%2};" ::"r"(sbase + 4 * 32768 + i * 16), "r"(0x00003F80u), "r"(0u) : "memory");
    fence_proxy_async();
    pdl_wait();
    pdl_launch();
    if (tid == 0) {
        constexpr uint32_t cb = (S_LEN / AT_NCHUNK) * 16;
#pragma unroll 1
        for (int c = 0; c < AT_NCHUNK; c++) {
            mbar_expect_tx(bar0 + 8 * c, 4 * cb);
#pragma unroll
            for (int r = 0; r < 4; r++)
                bulk_g2s(sbase + r * 32768 + c * cb, (const uint8_t*)KV + r * 32768 + c * cb, cb, bar0 + 8 * c);
        }
    }
    const int wg = tid >> 7, warp = (tid >> 5) & 3, lane = tid & 31;
    const int g = lane >> 2, t = lane & 3;
    const int rowA = blockIdx.x * 512 + wg * 128 + warp * 16;
    uint32_t qa[4], qb[4];
    {
        const uint32_t* qp = reinterpret_cast<const uint32_t*>(Q + (size_t)(rowA + g) * 16);
        qa[0] = qp[t]; qa[2] = qp[t + 4]; qa[1] = qp[64 + t]; qa[3] = qp[64 + t + 4];
        qb[0] = qp[512 + t]; qb[2] = qp[512 + t + 4]; qb[1] = qp[512 + 64 + t]; qb[3] = qp[512 + 64 + t + 4];
    }
    bool unsafe;
    {
        float km = fmaxf(fmaxf(kvmax[lane], kvmax[lane + 32]), fmaxf(kvmax[lane + 64], kvmax[lane + 96]));
        float vm = fmaxf(fmaxf(kvmax[128 + lane], kvmax[160 + lane]), fmaxf(kvmax[192 + lane], kvmax[224 + lane]));
        float n[4];
        n[0] = bf_lo(qa[0]) * bf_lo(qa[0]) + bf_hi(qa[0]) * bf_hi(qa[0]) + bf_lo(qa[2]) * bf_lo(qa[2]) + bf_hi(qa[2]) * bf_hi(qa[2]);
        n[1] = bf_lo(qa[1]) * bf_lo(qa[1]) + bf_hi(qa[1]) * bf_hi(qa[1]) + bf_lo(qa[3]) * bf_lo(qa[3]) + bf_hi(qa[3]) * bf_hi(qa[3]);
        n[2] = bf_lo(qb[0]) * bf_lo(qb[0]) + bf_hi(qb[0]) * bf_hi(qb[0]) + bf_lo(qb[2]) * bf_lo(qb[2]) + bf_hi(qb[2]) * bf_hi(qb[2]);
        n[3] = bf_lo(qb[1]) * bf_lo(qb[1]) + bf_hi(qb[1]) * bf_hi(qb[1]) + bf_lo(qb[3]) * bf_lo(qb[3]) + bf_hi(qb[3]) * bf_hi(qb[3]);
#pragma unroll
        for (int i = 0; i < 4; i++) { n[i] += __shfl_xor_sync(0xffffffffu, n[i], 1); n[i] += __shfl_xor_sync(0xffffffffu, n[i], 2); }
#pragma unroll
        for (int o = 16; o > 0; o >>= 1) { km = fmaxf(km, __shfl_xor_sync(0xffffffffu, km, o)); vm = fmaxf(vm, __shfl_xor_sync(0xffffffffu, vm, o)); }
        const float lim = 3600.0f;
        const bool ok = (n[0] * km <= lim) && (n[1] * km <= lim) && (n[2] * km <= lim) && (n[3] * km <= lim) && (vm <= 1.0e12f);
        unsafe = __syncthreads_or(!ok) != 0;
    }
    const uint64_t descK0 = make_desc(sbase, 32768, 128, 0);
    const uint64_t descV0 = make_desc(sbase + 65536, 128, 32768, 0);

#pragma unroll 1
    for (int mt = 0; mt < 2; mt++) {
        uint32_t q[4];
#pragma unroll
        for (int i = 0; i < 4; i++) q[i] = mt ? qb[i] : qa[i];
        float o[12];
#pragma unroll
        for (int i = 0; i < 12; i++) asm volatile("mov.f32 %0, 0f00000000;" : "=f"(o[i]));
        float s[AT_KT / 2];
        if (!unsafe) {
            uint32_t p0[AT_KT / 4], p1[AT_KT / 4];
#define AT_EXP(P) _Pragma("unroll") for (int i = 0; i < AT_KT / 4; i++) {                       \
                if ((AT_SWMASK >> (i & 15)) & 1) P[i] = exp2_pair_alu(s[2 * i], s[2 * i + 1]);  \
                else P[i] = pack_bf16(ex2(s[2 * i]), ex2(s[2 * i + 1])); }
#define AT_PV(P, dv) _Pragma("unroll") for (int j = 0; j < AT_KT / 16; j++)                     \
                wgmma_pv(o, P[4 * j], P[4 * j + 1], P[4 * j + 2], P[4 * j + 3], (dv) + (uint64_t)(j * 16));
#define AT_STEP(PC, PN, st) {                                                                   \
                if (st == AT_SPC - 1 && mt == 0) mbar_wait(bar0 + 8 * (c + 1), 0);              \
                wg_fence();                                                                     \
                wgmma_qk_n64(s, q, dK + (uint64_t)(st * AT_KT));                                \
                wg_commit();                                                                    \
                AT_PV(PC, dV + (uint64_t)(st * AT_KT));                                         \
                wg_commit();                                                                    \
                wg_wait<1>();                                                                   \
                AT_EXP(PN);                                                                     \
                wg_wait<0>(); }
            if (mt == 0) mbar_wait(bar0, 0);
            wg_fence();
            wgmma_qk_n64(s, q, descK0);
            wg_commit();
            wg_wait<0>();
            AT_EXP(p0);
            uint64_t dK = descK0 + AT_KT, dV = descV0;
#pragma unroll 1
            for (int c = 0; c < AT_NCHUNK - 1; c++) {
                AT_STEP(p0, p1, 0); AT_STEP(p1, p0, 1); AT_STEP(p0, p1, 2); AT_STEP(p1, p0, 3);
                dK += AT_SPC * AT_KT; dV += AT_SPC * AT_KT;
            }
            {
                const int c = 0; (void)c;
                AT_STEP(p0, p1, 0); AT_STEP(p1, p0, 1); AT_STEP(p0, p1, 2);
                wg_fence();
                AT_PV(p1, dV + (uint64_t)(3 * AT_KT));
                wg_commit();
                wg_wait<0>();
            }
        } else {
            float m0 = -INFINITY, m1 = -INFINITY;
            uint32_t p[AT_KT / 4];
#pragma unroll 1
            for (int st = 0; st < AT_NSTEP; st++) {
                if (mt == 0 && (st % AT_SPC) == 0) mbar_wait(bar0 + 8 * (st / AT_SPC), 0);
                wg_fence();
                wgmma_qk_n64(s, q, descK0 + (uint64_t)(st * AT_KT));
                wg_commit();
                wg_wait<0>();
                float x0 = m0, x1 = m1;
#pragma unroll
                for (int j = 0; j < AT_KT / 8; j++) {
                    x0 = fmaxf(x0, fmaxf(s[4 * j], s[4 * j + 1]));
                    x1 = fmaxf(x1, fmaxf(s[4 * j + 2], s[4 * j + 3]));
                }
                x0 = fmaxf(x0, __shfl_xor_sync(0xffffffffu, x0, 1)); x0 = fmaxf(x0, __shfl_xor_sync(0xffffffffu, x0, 2));
                x1 = fmaxf(x1, __shfl_xor_sync(0xffffffffu, x1, 1)); x1 = fmaxf(x1, __shfl_xor_sync(0xffffffffu, x1, 2));
                const float f0 = ex2(m0 - x0), f1 = ex2(m1 - x1);
                m0 = x0; m1 = x1;
#pragma unroll
                for (int j = 0; j < 3; j++) { o[4 * j] *= f0; o[4 * j + 1] *= f0; o[4 * j + 2] *= f1; o[4 * j + 3] *= f1; }
#pragma unroll
                for (int j = 0; j < AT_KT / 8; j++) {
                    p[2 * j] = pack_bf16(ex2(s[4 * j] - m0), ex2(s[4 * j + 1] - m0));
                    p[2 * j + 1] = pack_bf16(ex2(s[4 * j + 2] - m1), ex2(s[4 * j + 3] - m1));
                }
                wg_fence();
                AT_PV(p, descV0 + (uint64_t)(st * AT_KT));
                wg_commit();
                wg_wait<0>();
            }
        }
        const float l0 = __shfl_sync(0xffffffffu, o[8], lane & ~3);
        const float l1 = __shfl_sync(0xffffffffu, o[10], lane & ~3);
        const float r0 = 1.0f / l0, r1 = 1.0f / l1;
        uint32_t* op = reinterpret_cast<uint32_t*>(O + (size_t)(rowA + mt * 64 + g) * 16);
        op[t] = pack_bf16(o[0] * r0, o[1] * r0);
        op[t + 4] = pack_bf16(o[4] * r0, o[5] * r0);
        op[64 + t] = pack_bf16(o[2] * r1, o[3] * r1);
        op[64 + t + 4] = pack_bf16(o[6] * r1, o[7] * r1);
    }
}

constexpr int K3_STAGES = 8;
constexpr int K3_STAGE_BYTES = 16384 + 8192;
constexpr int K3_NKH = F_DIM / 64, K3_NKO = D_MODEL / 64, K3_NK = K3_NKH + K3_NKO;
constexpr int K3_SMEM = K3_STAGES * K3_STAGE_BYTES + 16384 + 256 + 1024;

__global__ void __launch_bounds__(288, 1)
k3_out(const __grid_constant__ CUtensorMap tm_h, const __grid_constant__ CUtensorMap tm_o,
       const __grid_constant__ CUtensorMap tm_w2, const __grid_constant__ CUtensorMap tm_wo,
       const __grid_constant__ CUtensorMap tm_x, const __grid_constant__ CUtensorMap tm_out,
       const __nv_bfloat16* __restrict__ b2) {
    extern __shared__ uint8_t smem_raw[];
    const uint32_t sbase = (smem_u32(smem_raw) + 1023) & ~1023u;
    const uint32_t sX = sbase + K3_STAGES * K3_STAGE_BYTES;
    const uint32_t bar_full = sX + 16384, bar_empty = bar_full + 8 * K3_STAGES, bar_x = bar_empty + 8 * K3_STAGES;
    const int tid = threadIdx.x, warp = tid >> 5, lane = tid & 31;
    const int rb = blockIdx.x >> 3, cb = blockIdx.x & 7;
    if (tid == 256) {
        for (int s = 0; s < K3_STAGES; s++) { mbar_init(bar_full + 8 * s, 1); mbar_init(bar_empty + 8 * s, 8); }
        mbar_init(bar_x, 1);
        mbar_init_fence();
    }
    __syncthreads();
    if (warp == 8) {
        if (lane == 0) {
            for (int ks = 0; ks < K3_NK; ks++) {
                const int s = ks % K3_STAGES;
                const uint32_t st = sbase + s * K3_STAGE_BYTES;
                if (ks == K3_NKH) pdl_wait();
                mbar_wait(bar_empty + 8 * s, ((ks / K3_STAGES) & 1) ^ 1);
                mbar_expect_tx(bar_full + 8 * s, K3_STAGE_BYTES);
                if (ks < K3_NKH) {
                    tma_load_2d(st, &tm_h, ks * 64, rb * 128, bar_full + 8 * s);
                    tma_load_2d(st + 16384, &tm_w2, cb * 64, ks * 64, bar_full + 8 * s);
                } else {
                    tma_load_2d(st, &tm_o, (ks - K3_NKH) * 64, rb * 128, bar_full + 8 * s);
                    tma_load_2d(st + 16384, &tm_wo, cb * 64, (ks - K3_NKH) * 64, bar_full + 8 * s);
                }
                if (ks == K3_STAGES - 1) {
                    mbar_expect_tx(bar_x, 16384);
                    tma_load_2d(sX, &tm_x, cb * 64, rb * 128, bar_x);
                }
            }
        }
    } else {
        const int wg = warp >> 2;
        float accY[32], accS[32];
#pragma unroll
        for (int i = 0; i < 32; i++) { accY[i] = 0.f; accS[i] = 0.f; }
        const uint64_t dA0 = make_desc(sbase + wg * 8192, 16, 1024, 1);
        const uint64_t dB0 = make_desc(sbase + 16384, 8192, 1024, 1);
        for (int ks = 0; ks < K3_NKH; ks++) {
            const int s = ks % K3_STAGES;
            mbar_wait(bar_full + 8 * s, (ks / K3_STAGES) & 1);
            wg_fence();
#pragma unroll
            for (int kk = 0; kk < 4; kk++)
                wgmma_ss_n64_tb(accY, dA0 + (uint64_t)((s * K3_STAGE_BYTES + kk * 32) >> 4),
                                dB0 + (uint64_t)((s * K3_STAGE_BYTES + kk * 2048) >> 4), (ks | kk) != 0);
            wg_commit();
            if (ks > 0) {
                wg_wait<1>();
                if (lane == 0) mbar_arrive(bar_empty + 8 * ((ks - 1) % K3_STAGES));
            }
        }
        for (int ks = K3_NKH; ks < K3_NK; ks++) {
            const int s = ks % K3_STAGES;
            mbar_wait(bar_full + 8 * s, (ks / K3_STAGES) & 1);
            wg_fence();
#pragma unroll
            for (int kk = 0; kk < 4; kk++)
                wgmma_ss_n64_tb(accS, dA0 + (uint64_t)((s * K3_STAGE_BYTES + kk * 32) >> 4),
                                dB0 + (uint64_t)((s * K3_STAGE_BYTES + kk * 2048) >> 4), ((ks - K3_NKH) | kk) != 0);
            wg_commit();
            wg_wait<1>();
            if (lane == 0) mbar_arrive(bar_empty + 8 * ((ks - 1) % K3_STAGES));
        }
        wg_wait<0>();
        mbar_wait(bar_x, 0);
        const int g = lane >> 2, t = lane & 3;
        const int row0 = warp * 16 + g;
#pragma unroll
        for (int j = 0; j < 8; j++) {
            const uint32_t bb = __ldg(reinterpret_cast<const uint32_t*>(b2 + cb * 64 + j * 8 + 2 * t));
            const float b0 = bf_lo(bb), b1v = bf_hi(bb);
#pragma unroll
            for (int h = 0; h < 2; h++) {
                const int row = row0 + h * 8;
                const uint32_t a = sX + row * 128 + ((j ^ (row & 7)) << 4) + t * 4;
                uint32_t xv;
                asm volatile("ld.shared.b32 %0, [%1];" : "=r"(xv) : "r"(a) : "memory");
                const float z0 = accY[4 * j + 2 * h] + b0, z1 = accY[4 * j + 2 * h + 1] + b1v;
                const float g0 = __fdividef(z0, 1.0f + __expf(-z0)), g1 = __fdividef(z1, 1.0f + __expf(-z1));
                const uint32_t ov = pack_bf16(bf_lo(xv) + accS[4 * j + 2 * h] * g0, bf_hi(xv) + accS[4 * j + 2 * h + 1] * g1);
                asm volatile("st.shared.b32 [%0], %1;" ::"r"(a), "r"(ov) : "memory");
            }
        }
        fence_proxy_async();
        named_bar_sync(1 + wg, 128);
        if ((tid & 127) == 0) {
            tma_store_2d(&tm_out, sX + wg * 8192, cb * 64, rb * 128 + wg * 64);
            tma_store_commit();
            tma_store_wait();
        }
    }
}

typedef CUresult (*EncodeFn)(CUtensorMap*, CUtensorMapDataType, cuuint32_t, void*, const cuuint64_t*, const cuuint64_t*,
                             const cuuint32_t*, const cuuint32_t*, CUtensorMapInterleave, CUtensorMapSwizzle,
                             CUtensorMapL2promotion, CUtensorMapFloatOOBfill);

struct HostState {
    bool ready;
    const void* key[11];
    CUtensorMap wq, wk, wv, w1, qo, ho, hi, oi, w2, wo, xi, out;
    void *pQ, *pKV, *pH, *pO, *pMax;
};
HostState g_hs;

void make_map(EncodeFn fn, CUtensorMap* m, const void* ptr, uint64_t inner, uint64_t outer, uint32_t box_in, uint32_t box_out) {
    cuuint64_t dims[2] = {inner, outer};
    cuuint64_t strides[1] = {inner * 2};
    cuuint32_t box[2] = {box_in, box_out};
    cuuint32_t es[2] = {1, 1};
    fn(m, CU_TENSOR_MAP_DATA_TYPE_BFLOAT16, 2, const_cast<void*>(ptr), dims, strides, box, es, CU_TENSOR_MAP_INTERLEAVE_NONE,
       CU_TENSOR_MAP_SWIZZLE_128B, CU_TENSOR_MAP_L2_PROMOTION_L2_256B, CU_TENSOR_MAP_FLOAT_OOB_FILL_NONE);
}

template <typename... KArgs, typename... Args>
void launch(void (*kern)(KArgs...), int grid, int block, int smem, bool pdl, Args... args) {
    cudaLaunchConfig_t cfg = {};
    cfg.gridDim = dim3(grid); cfg.blockDim = dim3(block); cfg.dynamicSmemBytes = smem; cfg.stream = cudaStreamPerThread;
    cudaLaunchAttribute at[1];
    at[0].id = cudaLaunchAttributeProgrammaticStreamSerialization;
    at[0].val.programmaticStreamSerializationAllowed = 1;
    cfg.attrs = at; cfg.numAttrs = pdl ? 1 : 0;
    cudaLaunchKernelEx(&cfg, kern, KArgs(args)...);
}

}

extern "C" void kernel_launch(void* const* d_in, const int* in_sizes, int n_in, void* d_out, int out_size) {
    (void)in_sizes; (void)n_in; (void)out_size;
    HostState& hs = g_hs;
    bool same = hs.ready;
    for (int i = 0; i < 10 && same; i++) same = hs.key[i] == d_in[i];
    same = same && hs.key[10] == d_out;
    if (!same) {
        void* fp = nullptr;
        cudaDriverEntryPointQueryResult qr;
        cudaGetDriverEntryPoint("cuTensorMapEncodeTiled", &fp, cudaEnableDefault, &qr);
        EncodeFn fn = (EncodeFn)fp;
        cudaGetSymbolAddress(&hs.pQ, g_Q); cudaGetSymbolAddress(&hs.pKV, g_KV); cudaGetSymbolAddress(&hs.pH, g_H);
        cudaGetSymbolAddress(&hs.pO, g_O); cudaGetSymbolAddress(&hs.pMax, g_kvmax);
        make_map(fn, &hs.wq, d_in[1], 512, 512, 64, K1_BK);
        make_map(fn, &hs.wk, d_in[2], 16, 512, 64, K1_BK);
        make_map(fn, &hs.wv, d_in[3], 16, 512, 64, K1_BK);
        make_map(fn, &hs.w1, d_in[6], F_DIM, 512, 64, K1_BK);
        make_map(fn, &hs.qo, hs.pQ, 512, S_LEN, 64, 64);
        make_map(fn, &hs.ho, hs.pH, F_DIM, S_LEN, 64, 64);
        make_map(fn, &hs.hi, hs.pH, F_DIM, S_LEN, 64, 128);
        make_map(fn, &hs.oi, hs.pO, 512, S_LEN, 64, 128);
        make_map(fn, &hs.w2, d_in[8], 512, F_DIM, 64, 64);
        make_map(fn, &hs.wo, d_in[4], 512, 512, 64, 64);
        make_map(fn, &hs.xi, d_in[0], 512, S_LEN, 64, 128);
        make_map(fn, &hs.out, d_out, 512, S_LEN, 64, 64);
        cudaFuncSetAttribute(k1_proj, cudaFuncAttributeMaxDynamicSharedMemorySize, K1_SMEM);
        cudaFuncSetAttribute(k2_attn, cudaFuncAttributeMaxDynamicSharedMemorySize, AT_SMEM);
        cudaFuncSetAttribute(k3_out, cudaFuncAttributeMaxDynamicSharedMemorySize, K3_SMEM);
        for (int i = 0; i < 10; i++) hs.key[i] = d_in[i];
        hs.key[10] = d_out;
        hs.ready = true;
    }
    launch(k1_proj, 128, 384, K1_SMEM, false, hs.wq, hs.wk, hs.wv, hs.w1, hs.qo, hs.ho,
           (const __nv_bfloat16*)d_in[0], (const __nv_bfloat16*)d_in[7], (__nv_bfloat16*)hs.pKV, (float*)hs.pMax);
    launch(k2_attn, 128, 512, AT_SMEM, true, (const __nv_bfloat16*)hs.pQ, (const __nv_bfloat16*)hs.pKV, (const float*)hs.pMax,
           (__nv_bfloat16*)hs.pO);
    launch(k3_out, 128, 288, K3_SMEM, true, hs.hi, hs.oi, hs.w2, hs.wo, hs.xi, hs.out, (const __nv_bfloat16*)d_in[9]);
}
```

```cpp
#include <cuda_runtime.h>
#include <cuda_bf16.h>
#include <cuda.h>
#include <stdint.h>

namespace {

constexpr int S_LEN = 2048, D_MODEL = 512, F_DIM = 1792;

__device__ __align__(1024) __nv_bfloat16 g_Q[S_LEN * D_MODEL];
__device__ __align__(1024) __nv_bfloat16 g_KV[6 * S_LEN * 8];
__device__ __align__(1024) __nv_bfloat16 g_H[S_LEN * F_DIM];
__device__ __align__(1024) __nv_bfloat16 g_O[S_LEN * D_MODEL];
__device__ __align__(1024) float g_kvmax[256];
__device__ __align__(1024) float2 g_rowstat[S_LEN];
__device__ __align__(1024) float g_colsum[40 * 64];

#define DEV_STAMP(k, e) do {} while (0)
__device__ __forceinline__ uint32_t smem_u32(const void* p) { return (uint32_t)__cvta_generic_to_shared(p); }
__device__ __forceinline__ void wg_fence() { asm volatile("wgmma.fence.sync.aligned;" ::: "memory"); }
__device__ __forceinline__ void wg_commit() { asm volatile("wgmma.commit_group.sync.aligned;" ::: "memory"); }
template <int N> __device__ __forceinline__ void wg_wait() { asm volatile("wgmma.wait_group.sync.aligned %0;" ::"n"(N) : "memory"); }
__device__ __forceinline__ void fence_proxy_async() { asm volatile("fence.proxy.async.shared::cta;" ::: "memory"); }
__device__ __forceinline__ void mbar_init(uint32_t bar, int cnt) { asm volatile("mbarrier.init.shared::cta.b64 [%0], %1;" ::"r"(bar), "r"(cnt) : "memory"); }
__device__ __forceinline__ void mbar_init_fence() { asm volatile("fence.mbarrier_init.release.cluster;" ::: "memory"); }
__device__ __forceinline__ void mbar_expect_tx(uint32_t bar, uint32_t bytes) {
    asm volatile("mbarrier.arrive.expect_tx.shared::cta.b64 _, [%0], %1;" ::"r"(bar), "r"(bytes) : "memory");
}
__device__ __forceinline__ void mbar_arrive(uint32_t bar) { asm volatile("mbarrier.arrive.shared::cta.b64 _, [%0];" ::"r"(bar) : "memory"); }
__device__ __forceinline__ bool mbar_try(uint32_t bar, uint32_t parity) {
    uint32_t ok;
    asm volatile("{\n.reg .pred p;\nmbarrier.try_wait.parity.shared::cta.b64 p, [%1], %2;\nselp.u32 %0, 1, 0, p;\n}\n"
                 : "=r"(ok) : "r"(bar), "r"(parity) : "memory");
    return ok != 0;
}
__device__ __forceinline__ void mbar_wait(uint32_t bar, uint32_t parity) {
    if (mbar_try(bar, parity)) return;
    uint32_t n = 0;
    while (!mbar_try(bar, parity)) {
        if (++n > (1u << 24)) __trap();
    }
}
__device__ __forceinline__ void bulk_g2s(uint32_t dst, const void* src, uint32_t bytes, uint32_t bar) {
    asm volatile("cp.async.bulk.shared::cluster.global.mbarrier::complete_tx::bytes [%0], [%1], %2, [%3];"
                 ::"r"(dst), "l"(src), "r"(bytes), "r"(bar) : "memory");
}
__device__ __forceinline__ void tma_load_2d(uint32_t dst, const CUtensorMap* tm, int c0, int c1, uint32_t bar) {
    asm volatile("cp.async.bulk.tensor.2d.shared::cluster.global.mbarrier::complete_tx::bytes [%0], [%1, {%3, %4}], [%2];"
                 ::"r"(dst), "l"((uint64_t)tm), "r"(bar), "r"(c0), "r"(c1) : "memory");
}
__device__ __forceinline__ void tma_store_2d(const CUtensorMap* tm, uint32_t src, int c0, int c1) {
    asm volatile("cp.async.bulk.tensor.2d.global.shared::cta.bulk_group [%0, {%2, %3}], [%1];"
                 ::"l"((uint64_t)tm), "r"(src), "r"(c0), "r"(c1) : "memory");
}
__device__ __forceinline__ void tma_store_commit() { asm volatile("cp.async.bulk.commit_group;" ::: "memory"); }
__device__ __forceinline__ void tma_store_wait() { asm volatile("cp.async.bulk.wait_group 0;" ::: "memory"); }
__device__ __forceinline__ void tma_prefetch_desc(const CUtensorMap* tm) { asm volatile("prefetch.tensormap [%0];" ::"l"((uint64_t)tm) : "memory"); }
__device__ __forceinline__ void named_bar_sync(int id, int n) { asm volatile("bar.sync %0, %1;" ::"r"(id), "r"(n) : "memory"); }
__device__ __forceinline__ void pdl_wait() { asm volatile("griddepcontrol.wait;" ::: "memory"); }
__device__ __forceinline__ void pdl_launch() { asm volatile("griddepcontrol.launch_dependents;" ::: "memory"); }
template <int N> __device__ __forceinline__ void reg_alloc() { asm volatile("setmaxnreg.inc.sync.aligned.u32 %0;" ::"n"(N)); }
template <int N> __device__ __forceinline__ void reg_dealloc() { asm volatile("setmaxnreg.dec.sync.aligned.u32 %0;" ::"n"(N)); }
__device__ __forceinline__ float ex2(float x) { float y; asm("ex2.approx.ftz.f32 %0, %1;" : "=f"(y) : "f"(x)); return y; }
__device__ __forceinline__ uint32_t pack_bf16(float lo, float hi) {
    uint32_t r; asm("cvt.rn.bf16x2.f32 %0, %1, %2;" : "=r"(r) : "f"(hi), "f"(lo)); return r;
}
__device__ __forceinline__ float bf_lo(uint32_t v) { return __uint_as_float(v << 16); }
__device__ __forceinline__ float bf_hi(uint32_t v) { return __uint_as_float(v & 0xFFFF0000u); }
__device__ __forceinline__ void stmatrix_x4(uint32_t addr, uint32_t r0, uint32_t r1, uint32_t r2, uint32_t r3) {
    asm volatile("stmatrix.sync.aligned.m8n8.x4.shared.b16 [%0], {%1,%2,%3,%4};" ::"r"(addr), "r"(r0), "r"(r1), "r"(r2), "r"(r3) : "memory");
}
__device__ __forceinline__ uint64_t make_desc(uint32_t addr, uint32_t lbo, uint32_t sbo, uint32_t swz) {
    return (uint64_t)((addr & 0x3FFFF) >> 4) | ((uint64_t)(lbo >> 4) << 16) | ((uint64_t)(sbo >> 4) << 32) | ((uint64_t)swz << 62);
}

__device__ __forceinline__ void wgmma_ss_n256_tb(float* d, uint64_t descA, uint64_t descB, int scaleD) {
    asm volatile("{\n.reg .pred p;\nsetp.ne.b32 p, %130, 0;\n"
      "wgmma.mma_async.sync.aligned.m64n256k16.f32.bf16.bf16 {%0,%1,%2,%3,%4,%5,%6,%7,%8,%9,%10,%11,%12,%13,%14,%15,%16,%17,%18,%19,%20,%21,%22,%23,%24,%25,%26,%27,%28,%29,%30,%31,%32,%33,%34,%35,%36,%37,%38,%39,%40,%41,%42,%43,%44,%45,%46,%47,%48,%49,%50,%51,%52,%53,%54,%55,%56,%57,%58,%59,%60,%61,%62,%63,%64,%65,%66,%67,%68,%69,%70,%71,%72,%73,%74,%75,%76,%77,%78,%79,%80,%81,%82,%83,%84,%85,%86,%87,%88,%89,%90,%91,%92,%93,%94,%95,%96,%97,%98,%99,%100,%101,%102,%103,%104,%105,%106,%107,%108,%109,%110,%111,%112,%113,%114,%115,%116,%117,%118,%119,%120,%121,%122,%123,%124,%125,%126,%127}, %128, %129, p, 1, 1, 0, 1;\n}\n"
      : "+f"(d[0]), "+f"(d[1]), "+f"(d[2]), "+f"(d[3]), "+f"(d[4]), "+f"(d[5]), "+f"(d[6]), "+f"(d[7]), "+f"(d[8]), "+f"(d[9]), "+f"(d[10]), "+f"(d[11]), "+f"(d[12]), "+f"(d[13]), "+f"(d[14]), "+f"(d[15]), "+f"(d[16]), "+f"(d[17]), "+f"(d[18]), "+f"(d[19]), "+f"(d[20]), "+f"(d[21]), "+f"(d[22]), "+f"(d[23]), "+f"(d[24]), "+f"(d[25]), "+f"(d[26]), "+f"(d[27]), "+f"(d[28]), "+f"(d[29]), "+f"(d[30]), "+f"(d[31]), "+f"(d[32]), "+f"(d[33]), "+f"(d[34]), "+f"(d[35]), "+f"(d[36]), "+f"(d[37]), "+f"(d[38]), "+f"(d[39]), "+f"(d[40]), "+f"(d[41]), "+f"(d[42]), "+f"(d[43]), "+f"(d[44]), "+f"(d[45]), "+f"(d[46]), "+f"(d[47]), "+f"(d[48]), "+f"(d[49]), "+f"(d[50]), "+f"(d[51]), "+f"(d[52]), "+f"(d[53]), "+f"(d[54]), "+f"(d[55]), "+f"(d[56]), "+f"(d[57]), "+f"(d[58]), "+f"(d[59]), "+f"(d[60]), "+f"(d[61]), "+f"(d[62]), "+f"(d[63]), "+f"(d[64]), "+f"(d[65]), "+f"(d[66]), "+f"(d[67]), "+f"(d[68]), "+f"(d[69]), "+f"(d[70]), "+f"(d[71]), "+f"(d[72]), "+f"(d[73]), "+f"(d[74]), "+f"(d[75]), "+f"(d[76]), "+f"(d[77]), "+f"(d[78]), "+f"(d[79]), "+f"(d[80]), "+f"(d[81]), "+f"(d[82]), "+f"(d[83]), "+f"(d[84]), "+f"(d[85]), "+f"(d[86]), "+f"(d[87]), "+f"(d[88]), "+f"(d[89]), "+f"(d[90]), "+f"(d[91]), "+f"(d[92]), "+f"(d[93]), "+f"(d[94]), "+f"(d[95]), "+f"(d[96]), "+f"(d[97]), "+f"(d[98]), "+f"(d[99]), "+f"(d[100]), "+f"(d[101]), "+f"(d[102]), "+f"(d[103]), "+f"(d[104]), "+f"(d[105]), "+f"(d[106]), "+f"(d[107]), "+f"(d[108]), "+f"(d[109]), "+f"(d[110]), "+f"(d[111]), "+f"(d[112]), "+f"(d[113]), "+f"(d[114]), "+f"(d[115]), "+f"(d[116]), "+f"(d[117]), "+f"(d[118]), "+f"(d[119]), "+f"(d[120]), "+f"(d[121]), "+f"(d[122]), "+f"(d[123]), "+f"(d[124]), "+f"(d[125]), "+f"(d[126]), "+f"(d[127])
      : "l"(descA), "l"(descB), "r"(scaleD));
}
__device__ __forceinline__ void wgmma_ss_n64_tb(float* d, uint64_t descA, uint64_t descB, int scaleD) {
    asm volatile("{\n.reg .pred p;\nsetp.ne.b32 p, %34, 0;\n"
      "wgmma.mma_async.sync.aligned.m64n64k16.f32.bf16.bf16 {%0,%1,%2,%3,%4,%5,%6,%7,%8,%9,%10,%11,%12,%13,%14,%15,%16,%17,%18,%19,%20,%21,%22,%23,%24,%25,%26,%27,%28,%29,%30,%31}, %32, %33, p, 1, 1, 0, 1;\n}\n"
      : "+f"(d[0]), "+f"(d[1]), "+f"(d[2]), "+f"(d[3]), "+f"(d[4]), "+f"(d[5]), "+f"(d[6]), "+f"(d[7]), "+f"(d[8]), "+f"(d[9]), "+f"(d[10]), "+f"(d[11]), "+f"(d[12]), "+f"(d[13]), "+f"(d[14]), "+f"(d[15]), "+f"(d[16]), "+f"(d[17]), "+f"(d[18]), "+f"(d[19]), "+f"(d[20]), "+f"(d[21]), "+f"(d[22]), "+f"(d[23]), "+f"(d[24]), "+f"(d[25]), "+f"(d[26]), "+f"(d[27]), "+f"(d[28]), "+f"(d[29]), "+f"(d[30]), "+f"(d[31])
      : "l"(descA), "l"(descB), "r"(scaleD));
}
__device__ __forceinline__ void wgmma_qk_n64(float* d, const uint32_t* a, uint64_t descB) {
    asm volatile("wgmma.mma_async.sync.aligned.m64n64k16.f32.bf16.bf16 {%0,%1,%2,%3,%4,%5,%6,%7,%8,%9,%10,%11,%12,%13,%14,%15,%16,%17,%18,%19,%20,%21,%22,%23,%24,%25,%26,%27,%28,%29,%30,%31}, {%32,%33,%34,%35}, %36, 0, 1, 1, 0;\n"
      : "=f"(d[0]), "=f"(d[1]), "=f"(d[2]), "=f"(d[3]), "=f"(d[4]), "=f"(d[5]), "=f"(d[6]), "=f"(d[7]), "=f"(d[8]), "=f"(d[9]), "=f"(d[10]), "=f"(d[11]), "=f"(d[12]), "=f"(d[13]), "=f"(d[14]), "=f"(d[15]), "=f"(d[16]), "=f"(d[17]), "=f"(d[18]), "=f"(d[19]), "=f"(d[20]), "=f"(d[21]), "=f"(d[22]), "=f"(d[23]), "=f"(d[24]), "=f"(d[25]), "=f"(d[26]), "=f"(d[27]), "=f"(d[28]), "=f"(d[29]), "=f"(d[30]), "=f"(d[31])
      : "r"(a[0]), "r"(a[1]), "r"(a[2]), "r"(a[3]), "l"(descB));
}
__device__ __forceinline__ void wgmma_qk_acc_n64(float* d, const uint32_t* a, uint64_t descB) {
    asm volatile("wgmma.mma_async.sync.aligned.m64n64k16.f32.bf16.bf16 {%0,%1,%2,%3,%4,%5,%6,%7,%8,%9,%10,%11,%12,%13,%14,%15,%16,%17,%18,%19,%20,%21,%22,%23,%24,%25,%26,%27,%28,%29,%30,%31}, {%32,%33,%34,%35}, %36, 1, 1, 1, 0;\n"
      : "+f"(d[0]), "+f"(d[1]), "+f"(d[2]), "+f"(d[3]), "+f"(d[4]), "+f"(d[5]), "+f"(d[6]), "+f"(d[7]), "+f"(d[8]), "+f"(d[9]), "+f"(d[10]), "+f"(d[11]), "+f"(d[12]), "+f"(d[13]), "+f"(d[14]), "+f"(d[15]), "+f"(d[16]), "+f"(d[17]), "+f"(d[18]), "+f"(d[19]), "+f"(d[20]), "+f"(d[21]), "+f"(d[22]), "+f"(d[23]), "+f"(d[24]), "+f"(d[25]), "+f"(d[26]), "+f"(d[27]), "+f"(d[28]), "+f"(d[29]), "+f"(d[30]), "+f"(d[31])
      : "r"(a[0]), "r"(a[1]), "r"(a[2]), "r"(a[3]), "l"(descB));
}

__device__ __forceinline__ void wgmma_pv(float* d, uint32_t a0, uint32_t a1, uint32_t a2, uint32_t a3, uint64_t descB) {
    asm volatile("wgmma.mma_async.sync.aligned.m64n24k16.f32.bf16.bf16 {%0,%1,%2,%3,%4,%5,%6,%7,%8,%9,%10,%11}, {%12,%13,%14,%15}, %16, 1, 1, 1, 1;\n"
                 : "+f"(d[0]), "+f"(d[1]), "+f"(d[2]), "+f"(d[3]), "+f"(d[4]), "+f"(d[5]), "+f"(d[6]), "+f"(d[7]), "+f"(d[8]), "+f"(d[9]), "+f"(d[10]), "+f"(d[11])
                 : "r"(a0), "r"(a1), "r"(a2), "r"(a3), "l"(descB));
}

__device__ __forceinline__ void k1_panel(int g, int i, int& type, int& col) {
    if (g < 6) {
        int p = g * 5 + i;
        if (p < 8) { type = 0; col = p * 64; } else { type = 1; col = (p - 8) * 64; }
    } else {
        if (i < 3) { type = 1; col = (22 + (g - 6) * 3 + i) * 64; } else { type = 2 + (g - 6); col = 0; }
    }
}

constexpr int K0_ROW_BLOCKS = 128;
__global__ void __launch_bounds__(256)
k0_stats(const __nv_bfloat16* __restrict__ x, const __nv_bfloat16* __restrict__ wq, const __nv_bfloat16* __restrict__ wk,
         const __nv_bfloat16* __restrict__ wv, const __nv_bfloat16* __restrict__ w1,
         float2* __restrict__ rowstat, float* __restrict__ colsum) {
    pdl_launch();
    const int tid = threadIdx.x, warp = tid >> 5, lane = tid & 31;
    if (tid == 0) DEV_STAMP(3, 0);
    if (blockIdx.x < K0_ROW_BLOCKS) {
        const int row0 = blockIdx.x * 16 + warp * 2;
        const uint4* xp = reinterpret_cast<const uint4*>(x + (size_t)row0 * D_MODEL);
        uint4 v[2][2];
#pragma unroll
        for (int r = 0; r < 2; r++) { v[r][0] = __ldg(xp + r * 64 + lane); v[r][1] = __ldg(xp + r * 64 + 32 + lane); }
#pragma unroll
        for (int r = 0; r < 2; r++) {
            float f[16];
            const uint32_t w[8] = {v[r][0].x, v[r][0].y, v[r][0].z, v[r][0].w, v[r][1].x, v[r][1].y, v[r][1].z, v[r][1].w};
#pragma unroll
            for (int i = 0; i < 8; i++) { f[2 * i] = bf_lo(w[i]); f[2 * i + 1] = bf_hi(w[i]); }
            float sum = 0.f;
#pragma unroll
            for (int i = 0; i < 16; i++) sum += f[i];
#pragma unroll
            for (int o = 16; o > 0; o >>= 1) sum += __shfl_xor_sync(0xffffffffu, sum, o);
            const float mean = sum * (1.0f / D_MODEL);
            float sq = 0.f;
#pragma unroll
            for (int i = 0; i < 16; i++) { const float d = f[i] - mean; sq += d * d; }
#pragma unroll
            for (int o = 16; o > 0; o >>= 1) sq += __shfl_xor_sync(0xffffffffu, sq, o);
            const float rstd = rsqrtf(sq * (1.0f / D_MODEL) + 1e-5f);
            if (lane == 0) rowstat[row0 + r] = make_float2(rstd, mean * rstd);
        }
    } else {
        __shared__ float2 red[8][32];
        const int pb = blockIdx.x - K0_ROW_BLOCKS;
        const int g = pb / 5, i = pb % 5;
        if (g >= 6 && i == 4) return;
        int type, col; k1_panel(g, i, type, col);
        const __nv_bfloat16* w = type == 0 ? wq : type == 1 ? w1 : type == 2 ? wk : wv;
        const int ld = type == 0 ? D_MODEL : type == 1 ? F_DIM : 16;
        const bool valid = type <= 1 || lane < 8;
        float s0 = 0.f, s1 = 0.f;
        if (valid) {
            const uint32_t* wp = reinterpret_cast<const uint32_t*>(w + (size_t)(warp * 64) * ld + col) + lane;
#pragma unroll 4
            for (int k0 = 0; k0 < 64; k0 += 16) {
                uint32_t u[16];
#pragma unroll
                for (int k = 0; k < 16; k++) u[k] = __ldg(wp + (size_t)(k0 + k) * (ld / 2));
#pragma unroll
                for (int k = 0; k < 16; k++) { s0 += bf_lo(u[k]); s1 += bf_hi(u[k]); }
            }
        }
        red[warp][lane] = make_float2(s0, s1);
        __syncthreads();
        if (warp == 0) {
            float a0 = 0.f, a1 = 0.f;
#pragma unroll
            for (int w8 = 0; w8 < 8; w8++) { a0 += red[w8][lane].x; a1 += red[w8][lane].y; }
            reinterpret_cast<float2*>(colsum + pb * 64)[lane] = make_float2(a0, a1);
        }
    }
    if (tid == 0) DEV_STAMP(3, 1);
}

constexpr int K1_STAGES = 4;
constexpr int K1_PANEL_BYTES = 64 * 128;
constexpr int K1_STAGE_BYTES = 16384 + 5 * K1_PANEL_BYTES;
constexpr int K1_SMEM = K1_STAGES * K1_STAGE_BYTES + 128 + 320 * 8;
constexpr float Q_SCALE = 0.25f * 1.4426950408889634f;

__global__ void __launch_bounds__(384, 1)
k1_proj(const __grid_constant__ CUtensorMap tm_x, const __grid_constant__ CUtensorMap tm_wq,
        const __grid_constant__ CUtensorMap tm_wk, const __grid_constant__ CUtensorMap tm_wv,
        const __grid_constant__ CUtensorMap tm_w1, const __grid_constant__ CUtensorMap tm_qo,
        const __grid_constant__ CUtensorMap tm_ho, const __nv_bfloat16* __restrict__ b1,
        const float2* __restrict__ rowstat, const float* __restrict__ colsum,
        __nv_bfloat16* __restrict__ kv, float* __restrict__ kvmax) {
    extern __shared__ __align__(1024) uint8_t smem_raw[];
    const uint32_t sbase = smem_u32(smem_raw);
    const uint32_t bar_full = sbase + K1_STAGES * K1_STAGE_BYTES, bar_empty = bar_full + 8 * K1_STAGES, bar_col = bar_empty + 8 * K1_STAGES;
    const uint32_t sCol = bar_full + 128;
    const int tid = threadIdx.x, warp = tid >> 5, lane = tid & 31;
    const int rb = blockIdx.x >> 3, grp = blockIdx.x & 7;
    const int npanels = grp < 6 ? 5 : 4;
    if (tid == 0) DEV_STAMP(0, 0);

    if (tid == 256) {
        for (int s = 0; s < K1_STAGES; s++) { mbar_init(bar_full + 8 * s, 1); mbar_init(bar_empty + 8 * s, 8); }
        mbar_init(bar_col, 32);
        mbar_init_fence();
    }
    __syncthreads();
    pdl_launch();

    if (warp >= 8) {
        reg_dealloc<40>();
        if (warp == 8) {
            if (lane == 0) {
                const CUtensorMap* tms[5]; int cols[5];
#pragma unroll
                for (int i = 0; i < 5; i++) {
                    int type, col; k1_panel(grp, i, type, col);
                    tms[i] = type == 0 ? &tm_wq : type == 1 ? &tm_w1 : type == 2 ? &tm_wk : &tm_wv;
                    cols[i] = col;
                }
                for (int ks = 0; ks < 8; ks++) {
                    const int s = ks % K1_STAGES;
                    const uint32_t st = sbase + s * K1_STAGE_BYTES;
                    mbar_wait(bar_empty + 8 * s, ((ks / K1_STAGES) & 1) ^ 1);
                    mbar_expect_tx(bar_full + 8 * s, 16384 + npanels * K1_PANEL_BYTES);
                    tma_load_2d(st, &tm_x, ks * 64, rb * 128, bar_full + 8 * s);
#pragma unroll
                    for (int i = 0; i < 5; i++)
                        if (i < npanels) tma_load_2d(st + 16384 + i * K1_PANEL_BYTES, tms[i], cols[i], ks * 64, bar_full + 8 * s);
                }
            }
        } else if (warp == 9) {
            pdl_wait();
#pragma unroll
            for (int p = 0; p < 5; p++) {
                if (p < npanels) {
                    int type, col; k1_panel(grp, p, type, col);
                    const float2 cs = reinterpret_cast<const float2*>(colsum + (grp * 5 + p) * 64)[lane];
                    uint32_t bb = 0;
                    if (type == 1) bb = __ldg(reinterpret_cast<const uint32_t*>(b1 + col) + lane);
                    asm volatile("st.shared.v4.f32 [%0], {%1,%2,%3,%4};" ::"r"(sCol + (p * 64 + lane * 2) * 8),
                                 "f"(cs.x), "f"(bf_lo(bb)), "f"(cs.y), "f"(bf_hi(bb)) : "memory");
                }
            }
            mbar_arrive(bar_col);
        }
    } else {
        reg_alloc<232>();
        const int wg = warp >> 2;
        const int g = lane >> 2, t = lane & 3;
        const int wrow = (warp & 3) * 16;
        float acc[160];
#pragma unroll
        for (int i = 0; i < 160; i++) acc[i] = 0.f;
        float2 rs0, rs1;
        const uint64_t dA0 = make_desc(sbase + wg * 8192, 16, 1024, 1);
        const uint64_t dB0 = make_desc(sbase + 16384, K1_PANEL_BYTES, 1024, 1);
#define K1_MAINLOOP(FIVE)                                                                                          \
        for (int ks = 0; ks < 8; ks++) {                                                                           \
            const int s = ks % K1_STAGES;                                                                          \
            mbar_wait(bar_full + 8 * s, (ks / K1_STAGES) & 1);                                                     \
            if (ks == 0 && tid == 0) DEV_STAMP(0, 1);                                                              \
            wg_fence();                                                                                            \
            _Pragma("unroll") for (int kk = 0; kk < 4; kk++) {                                                     \
                const uint64_t dA = dA0 + (uint64_t)((s * K1_STAGE_BYTES + kk * 32) >> 4);                         \
                const uint64_t dB = dB0 + (uint64_t)((s * K1_STAGE_BYTES + kk * 2048) >> 4);                       \
                wgmma_ss_n256_tb(acc, dA, dB, (ks | kk) != 0);                                                     \
                if (FIVE) wgmma_ss_n64_tb(acc + 128, dA, dB + (uint64_t)((4 * K1_PANEL_BYTES) >> 4), (ks | kk) != 0); \
            }                                                                                                      \
            wg_commit();                                                                                           \
            if (ks == 7) {                                                                                         \
                pdl_wait();                                                                                        \
                rs0 = rowstat[rb * 128 + wg * 64 + wrow + g];                                                      \
                rs1 = rowstat[rb * 128 + wg * 64 + wrow + g + 8];                                                  \
            }                                                                                                      \
            if (ks > 0 && ks <= 4) {                                                                               \
                wg_wait<1>();                                                                                      \
                if (lane == 0) mbar_arrive(bar_empty + 8 * ((ks - 1) % K1_STAGES));                                \
            }                                                                                                      \
        }                                                                                                          \
        wg_wait<0>();
        if (npanels == 5) { K1_MAINLOOP(true) } else { K1_MAINLOOP(false) }
        if (tid == 0) DEV_STAMP(0, 2);
        mbar_wait(bar_col, 0);
        named_bar_sync(1, 256);
        const int srow = wrow + (lane & 7) + ((lane >> 3) & 1) * 8;
#pragma unroll
        for (int p = 0; p < 5; p++) {
            if (p < npanels) {
                int type, col; k1_panel(grp, p, type, col);
                float* a = acc + p * 32;
                const int nj = type <= 1 ? 8 : 2;
#pragma unroll
                for (int j = 0; j < 8; j++) {
                    if (j < nj) {
                        float4 c;
                        asm volatile("ld.shared.v4.f32 {%0,%1,%2,%3}, [%4];" : "=f"(c.x), "=f"(c.y), "=f"(c.z), "=f"(c.w)
                                     : "r"(sCol + (p * 64 + j * 8 + 2 * t) * 8));
                        a[4 * j] = fmaf(a[4 * j], rs0.x, fmaf(-rs0.y, c.x, c.y));
                        a[4 * j + 1] = fmaf(a[4 * j + 1], rs0.x, fmaf(-rs0.y, c.z, c.w));
                        a[4 * j + 2] = fmaf(a[4 * j + 2], rs1.x, fmaf(-rs1.y, c.x, c.y));
                        a[4 * j + 3] = fmaf(a[4 * j + 3], rs1.x, fmaf(-rs1.y, c.z, c.w));
                    }
                }
                if (type <= 1) {
                    const uint32_t stg = sbase + (p * 2 + wg) * 8192;
                    uint32_t pk[16];
                    if (type == 0) {
#pragma unroll
                        for (int j = 0; j < 8; j++) {
                            pk[2 * j] = pack_bf16(a[4 * j] * Q_SCALE, a[4 * j + 1] * Q_SCALE);
                            pk[2 * j + 1] = pack_bf16(a[4 * j + 2] * Q_SCALE, a[4 * j + 3] * Q_SCALE);
                        }
                    } else {
#pragma unroll
                        for (int j = 0; j < 8; j++) {
                            const float h0 = fmaxf(a[4 * j], 0.f), h1 = fmaxf(a[4 * j + 1], 0.f);
                            const float h2 = fmaxf(a[4 * j + 2], 0.f), h3 = fmaxf(a[4 * j + 3], 0.f);
                            pk[2 * j] = pack_bf16(h0 * h0, h1 * h1);
                            pk[2 * j + 1] = pack_bf16(h2 * h2, h3 * h3);
                        }
                    }
#pragma unroll
                    for (int j = 0; j < 8; j += 2) {
                        const int c16 = j + (lane >> 4);
                        stmatrix_x4(stg + srow * 128 + ((c16 ^ (srow & 7)) << 4), pk[2 * j], pk[2 * j + 1], pk[2 * j + 2], pk[2 * j + 3]);
                    }
                    fence_proxy_async();
                    named_bar_sync(2 + wg, 128);
                    if ((tid & 127) == 0) {
                        tma_store_2d(type == 0 ? &tm_qo : &tm_ho, stg, col, rb * 128 + wg * 64);
                        tma_store_commit();
                    }
                } else if (type == 3) {
                    const int r = wg * 64 + wrow + g;
                    const int pos0 = (r >> 2) * 64 + rb * 4 + (r & 3), pos1 = pos0 + 128;
                    uint32_t* dst = reinterpret_cast<uint32_t*>(kv + 2 * (S_LEN * 8));
                    const uint32_t r00 = pack_bf16(a[0], a[1]), r01 = pack_bf16(a[4], a[5]);
                    const uint32_t r10 = pack_bf16(a[2], a[3]), r11 = pack_bf16(a[6], a[7]);
                    dst[pos0 * 4 + t] = r00;
                    dst[S_LEN * 4 + pos0 * 4 + t] = r01;
                    dst[pos1 * 4 + t] = r10;
                    dst[S_LEN * 4 + pos1 * 4 + t] = r11;
                    float m = fmaxf(fmaxf(fmaxf(fabsf(bf_lo(r00)), fabsf(bf_hi(r00))), fmaxf(fabsf(bf_lo(r01)), fabsf(bf_hi(r01)))),
                                    fmaxf(fmaxf(fabsf(bf_lo(r10)), fabsf(bf_hi(r10))), fmaxf(fabsf(bf_lo(r11)), fabsf(bf_hi(r11)))));
#pragma unroll
                    for (int o = 16; o > 0; o >>= 1) m = fmaxf(m, __shfl_xor_sync(0xffffffffu, m, o));
                    if (lane == 0) kvmax[128 + rb * 8 + warp] = m;
                } else {
                    float* kf = reinterpret_cast<float*>(smem_raw + 96 * 1024);
                    const int r = wg * 64 + wrow + g;
                    const int pos0 = (r >> 2) * 64 + rb * 4 + (r & 3), pos1 = pos0 + 128;
                    uint32_t* dst = reinterpret_cast<uint32_t*>(kv + 4 * (S_LEN * 8));
                    dst[pos0 * 4 + t] = pack_bf16(a[0], a[1]);
                    dst[S_LEN * 4 + pos0 * 4 + t] = pack_bf16(a[4], a[5]);
                    dst[pos1 * 4 + t] = pack_bf16(a[2], a[3]);
                    dst[S_LEN * 4 + pos1 * 4 + t] = pack_bf16(a[6], a[7]);
                    kf[r * 17 + 2 * t] = a[0]; kf[r * 17 + 2 * t + 1] = a[1];
                    kf[r * 17 + 8 + 2 * t] = a[4]; kf[r * 17 + 8 + 2 * t + 1] = a[5];
                    kf[(r + 8) * 17 + 2 * t] = a[2]; kf[(r + 8) * 17 + 2 * t + 1] = a[3];
                    kf[(r + 8) * 17 + 8 + 2 * t] = a[6]; kf[(r + 8) * 17 + 8 + 2 * t + 1] = a[7];
                    named_bar_sync(1, 256);
                    if (tid < 64) {
                        const int i = tid >> 4, dim = tid & 15;
                        __nv_bfloat16* dd = kv + (dim >> 3) * (S_LEN * 8) + (rb * 4 + i) * 8 + (dim & 7);
                        float kt = 0.f;
#pragma unroll 8
                        for (int j = 0; j < 32; j++) {
                            const __nv_bfloat16 d = __float2bfloat16_rn(kf[(j * 4 + i) * 17 + dim] - kt);
                            kt += __bfloat162float(d);
                            kf[(j * 4 + i) * 17 + dim] = kt;
                            dd[j * 512] = d;
                        }
                    }
                    named_bar_sync(1, 256);
                    if (tid < 128) {
                        float n = 0.f;
#pragma unroll
                        for (int d = 0; d < 16; d++) { const float v = kf[tid * 17 + d]; n += v * v; }
                        if (!(n == n)) n = __int_as_float(0x7f800000);
#pragma unroll
                        for (int o = 8; o > 0; o >>= 1) n = fmaxf(n, __shfl_xor_sync(0xffffffffu, n, o));
                        if ((lane & 15) == 0) kvmax[rb * 8 + (tid >> 4)] = n;
                    }
                }
            }
        }
        if (tid == 0) DEV_STAMP(0, 3);
        if ((tid & 127) == 0) tma_store_wait();
        if (tid == 0) DEV_STAMP(0, 4);
    }
}

constexpr int AT_KT = 64;
constexpr int AT_NCHUNK = 8;
constexpr int AT_NSTEP = S_LEN / AT_KT;
constexpr int AT_SPC = AT_NSTEP / AT_NCHUNK;
constexpr int AT_SMEM = 5 * 32768 + 256 + 1024;
constexpr uint32_t AT_SWMASK = 0xF8F8;

#define AT_MAGIC (383.0f + 0.00390625f - 0.5849625f)
__device__ __forceinline__ uint32_t exp2_pair_alu(float t0, float t1) {
    const uint32_t y = __byte_perm(__float_as_uint(t0), __float_as_uint(t1), 0x6521);
    const uint32_t e = y & 0x7F807F80u;
    uint32_t uh, p;
    asm("lop3.b32 %0, %1, %2, 0x3F003F00, 0xBE;" : "=r"(uh) : "r"(y), "r"(e));
    asm("fma.rn.bf16x2 %0, %1, %2, %3;" : "=r"(p) : "r"(uh), "r"(y), "r"(e));
    return p;
}

__global__ void __launch_bounds__(512, 1)
k2_attn(const __nv_bfloat16* __restrict__ Q, const __nv_bfloat16* __restrict__ KV, const float* __restrict__ kvmax,
        __nv_bfloat16* __restrict__ O) {
    extern __shared__ uint8_t smem_raw[];
    const uint32_t sbase = (smem_u32(smem_raw) + 1023) & ~1023u;
    const uint32_t bar0 = sbase + 5 * 32768;
    const int tid = threadIdx.x;
    if (tid == 0) DEV_STAMP(1, 0);
    if (tid == 0) {
        for (int i = 0; i < AT_NCHUNK; i++) mbar_init(bar0 + 8 * i, 1);
        mbar_init_fence();
    }
    for (int i = tid; i < S_LEN; i += 512)
        asm volatile("st.shared.v4.b32 [%0], {%1,%2,%2,%2};" ::"r"(sbase + 4 * 32768 + i * 16), "r"(0x00003F80u), "r"(0u) : "memory");
    fence_proxy_async();
    pdl_wait();
    pdl_launch();
    if (tid == 0) DEV_STAMP(1, 1);
    if (tid == 0) {
        constexpr uint32_t cb = (S_LEN / AT_NCHUNK) * 16;
#pragma unroll 1
        for (int c = 0; c < AT_NCHUNK; c++) {
            mbar_expect_tx(bar0 + 8 * c, 4 * cb);
#pragma unroll
            for (int r = 0; r < 4; r++)
                bulk_g2s(sbase + r * 32768 + c * cb, (const uint8_t*)KV + r * 32768 + c * cb, cb, bar0 + 8 * c);
        }
    }
    const int wg = tid >> 7, warp = (tid >> 5) & 3, lane = tid & 31;
    const int g = lane >> 2, t = lane & 3;
    const int rowA = blockIdx.x * 512 + wg * 128 + warp * 16;
    uint32_t qa[4], qb[4];
    {
        const uint32_t* qp = reinterpret_cast<const uint32_t*>(Q + (size_t)(rowA + g) * 16);
        qa[0] = qp[t]; qa[2] = qp[t + 4]; qa[1] = qp[64 + t]; qa[3] = qp[64 + t + 4];
        qb[0] = qp[512 + t]; qb[2] = qp[512 + t + 4]; qb[1] = qp[512 + 64 + t]; qb[3] = qp[512 + 64 + t + 4];
    }
    bool unsafe;
    {
        float km = fmaxf(fmaxf(kvmax[lane], kvmax[lane + 32]), fmaxf(kvmax[lane + 64], kvmax[lane + 96]));
        float vm = fmaxf(fmaxf(kvmax[128 + lane], kvmax[160 + lane]), fmaxf(kvmax[192 + lane], kvmax[224 + lane]));
        float n[4];
        n[0] = bf_lo(qa[0]) * bf_lo(qa[0]) + bf_hi(qa[0]) * bf_hi(qa[0]) + bf_lo(qa[2]) * bf_lo(qa[2]) + bf_hi(qa[2]) * bf_hi(qa[2]);
        n[1] = bf_lo(qa[1]) * bf_lo(qa[1]) + bf_hi(qa[1]) * bf_hi(qa[1]) + bf_lo(qa[3]) * bf_lo(qa[3]) + bf_hi(qa[3]) * bf_hi(qa[3]);
        n[2] = bf_lo(qb[0]) * bf_lo(qb[0]) + bf_hi(qb[0]) * bf_hi(qb[0]) + bf_lo(qb[2]) * bf_lo(qb[2]) + bf_hi(qb[2]) * bf_hi(qb[2]);
        n[3] = bf_lo(qb[1]) * bf_lo(qb[1]) + bf_hi(qb[1]) * bf_hi(qb[1]) + bf_lo(qb[3]) * bf_lo(qb[3]) + bf_hi(qb[3]) * bf_hi(qb[3]);
#pragma unroll
        for (int i = 0; i < 4; i++) { n[i] += __shfl_xor_sync(0xffffffffu, n[i], 1); n[i] += __shfl_xor_sync(0xffffffffu, n[i], 2); }
#pragma unroll
        for (int o = 16; o > 0; o >>= 1) { km = fmaxf(km, __shfl_xor_sync(0xffffffffu, km, o)); vm = fmaxf(vm, __shfl_xor_sync(0xffffffffu, vm, o)); }
        const float lim = 3600.0f;
        const bool ok = (n[0] * km <= lim) && (n[1] * km <= lim) && (n[2] * km <= lim) && (n[3] * km <= lim) && (vm <= 1.0e12f);
        unsafe = __syncthreads_or(!ok) != 0;
    }
    if (unsafe) {
        for (int c = 0; c < AT_NCHUNK; c++) mbar_wait(bar0 + 8 * c, 0);
        __syncthreads();
        if (tid == 0) {
            mbar_expect_tx(bar0, 65536);
            bulk_g2s(sbase, (const uint8_t*)KV + 4 * 32768, 32768, bar0);
            bulk_g2s(sbase + 32768, (const uint8_t*)KV + 5 * 32768, 32768, bar0);
        }
        mbar_wait(bar0, 1);
    }
    const uint64_t descK0 = make_desc(sbase, 32768, 128, 0);
    const uint64_t descV0 = make_desc(sbase + 65536, 128, 32768, 0);

#pragma unroll 1
    for (int mt = 0; mt < 2; mt++) {
        uint32_t q[4];
#pragma unroll
        for (int i = 0; i < 4; i++) q[i] = mt ? qb[i] : qa[i];
        float o[12];
#pragma unroll
        for (int i = 0; i < 12; i++) asm volatile("mov.f32 %0, 0f00000000;" : "=f"(o[i]));
        float s[AT_KT / 2];
        if (!unsafe) {
            uint32_t p0[AT_KT / 4], p1[AT_KT / 4];
#define AT_EXP(P) _Pragma("unroll") for (int i = 0; i < AT_KT / 4; i++) {                       \
                if ((AT_SWMASK >> (i & 15)) & 1) P[i] = exp2_pair_alu(s[2 * i], s[2 * i + 1]);  \
                else P[i] = pack_bf16(ex2(s[2 * i]), ex2(s[2 * i + 1])); }
#define AT_PV(P, dv) _Pragma("unroll") for (int j = 0; j < AT_KT / 16; j++)                     \
                wgmma_pv(o, P[4 * j], P[4 * j + 1], P[4 * j + 2], P[4 * j + 3], (dv) + (uint64_t)(j * 16));
#define AT_STEP(PC, PN, st) {                                                                   \
                if (st == AT_SPC - 1 && mt == 0) mbar_wait(bar0 + 8 * (c + 1), 0);              \
                wg_fence();                                                                     \
                wgmma_qk_acc_n64(s, q, dK + (uint64_t)(st * AT_KT));                            \
                wg_commit();                                                                    \
                AT_PV(PC, dV + (uint64_t)(st * AT_KT));                                         \
                wg_commit();                                                                    \
                wg_wait<1>();                                                                   \
                AT_EXP(PN);                                                                     \
                wg_wait<0>(); }
            if (mt == 0) mbar_wait(bar0, 0);
            if (tid == 0) DEV_STAMP(1, 2 + mt);
#pragma unroll
            for (int i = 0; i < AT_KT / 2; i++) {
                if ((AT_SWMASK >> ((i >> 1) & 15)) & 1) asm volatile("mov.f32 %0, %1;" : "=f"(s[i]) : "f"(AT_MAGIC));
                else asm volatile("mov.f32 %0, 0f00000000;" : "=f"(s[i]));
            }
            wg_fence();
            wgmma_qk_acc_n64(s, q, descK0);
            wg_commit();
            wg_wait<0>();
            AT_EXP(p0);
            uint64_t dK = descK0 + AT_KT, dV = descV0;
#pragma unroll 1
            for (int c = 0; c < AT_NCHUNK - 1; c++) {
                AT_STEP(p0, p1, 0); AT_STEP(p1, p0, 1); AT_STEP(p0, p1, 2); AT_STEP(p1, p0, 3);
                dK += AT_SPC * AT_KT; dV += AT_SPC * AT_KT;
            }
            {
                const int c = 0; (void)c;
                AT_STEP(p0, p1, 0); AT_STEP(p1, p0, 1); AT_STEP(p0, p1, 2);
                wg_fence();
                AT_PV(p1, dV + (uint64_t)(3 * AT_KT));
                wg_commit();
                wg_wait<0>();
            }
        } else {
            float m0 = -INFINITY, m1 = -INFINITY;
            uint32_t p[AT_KT / 4];
#pragma unroll 1
            for (int st = 0; st < AT_NSTEP; st++) {
                wg_fence();
                wgmma_qk_n64(s, q, descK0 + (uint64_t)(st * AT_KT));
                wg_commit();
                wg_wait<0>();
                float x0 = m0, x1 = m1;
#pragma unroll
                for (int j = 0; j < AT_KT / 8; j++) {
                    x0 = fmaxf(x0, fmaxf(s[4 * j], s[4 * j + 1]));
                    x1 = fmaxf(x1, fmaxf(s[4 * j + 2], s[4 * j + 3]));
                }
                x0 = fmaxf(x0, __shfl_xor_sync(0xffffffffu, x0, 1)); x0 = fmaxf(x0, __shfl_xor_sync(0xffffffffu, x0, 2));
                x1 = fmaxf(x1, __shfl_xor_sync(0xffffffffu, x1, 1)); x1 = fmaxf(x1, __shfl_xor_sync(0xffffffffu, x1, 2));
                const float f0 = ex2(m0 - x0), f1 = ex2(m1 - x1);
                m0 = x0; m1 = x1;
#pragma unroll
                for (int j = 0; j < 3; j++) { o[4 * j] *= f0; o[4 * j + 1] *= f0; o[4 * j + 2] *= f1; o[4 * j + 3] *= f1; }
#pragma unroll
                for (int j = 0; j < AT_KT / 8; j++) {
                    p[2 * j] = pack_bf16(ex2(s[4 * j] - m0), ex2(s[4 * j + 1] - m0));
                    p[2 * j + 1] = pack_bf16(ex2(s[4 * j + 2] - m1), ex2(s[4 * j + 3] - m1));
                }
                wg_fence();
                AT_PV(p, descV0 + (uint64_t)(st * AT_KT));
                wg_commit();
                wg_wait<0>();
            }
        }
        const float l0 = __shfl_sync(0xffffffffu, o[8], lane & ~3);
        const float l1 = __shfl_sync(0xffffffffu, o[10], lane & ~3);
        const float r0 = 1.0f / l0, r1 = 1.0f / l1;
        uint32_t* op = reinterpret_cast<uint32_t*>(O + (size_t)(rowA + mt * 64 + g) * 16);
        op[t] = pack_bf16(o[0] * r0, o[1] * r0);
        op[t + 4] = pack_bf16(o[4] * r0, o[5] * r0);
        op[64 + t] = pack_bf16(o[2] * r1, o[3] * r1);
        op[64 + t + 4] = pack_bf16(o[6] * r1, o[7] * r1);
    }
    if (tid == 0) DEV_STAMP(1, 4);
}

constexpr int K3_STAGES = 8;
constexpr int K3_STAGE_BYTES = 16384 + 8192;
constexpr int K3_NKH = F_DIM / 64, K3_NKO = D_MODEL / 64, K3_NK = K3_NKH + K3_NKO;
constexpr int K3_SMEM = K3_STAGES * K3_STAGE_BYTES + 16384 + 256 + 1024;

__global__ void __launch_bounds__(288, 1)
k3_out(const __grid_constant__ CUtensorMap tm_h, const __grid_constant__ CUtensorMap tm_o,
       const __grid_constant__ CUtensorMap tm_w2, const __grid_constant__ CUtensorMap tm_wo,
       const __grid_constant__ CUtensorMap tm_x, const __grid_constant__ CUtensorMap tm_out,
       const __nv_bfloat16* __restrict__ b2) {
    extern __shared__ uint8_t smem_raw[];
    const uint32_t sbase = (smem_u32(smem_raw) + 1023) & ~1023u;
    const uint32_t sX = sbase + K3_STAGES * K3_STAGE_BYTES;
    const uint32_t bar_full = sX + 16384, bar_empty = bar_full + 8 * K3_STAGES, bar_x = bar_empty + 8 * K3_STAGES;
    const int tid = threadIdx.x, warp = tid >> 5, lane = tid & 31;
    const int rb = blockIdx.x >> 3, cb = blockIdx.x & 7;
    if (tid == 0) DEV_STAMP(2, 0);
    if (tid == 256) {
        for (int s = 0; s < K3_STAGES; s++) { mbar_init(bar_full + 8 * s, 1); mbar_init(bar_empty + 8 * s, 8); }
        mbar_init(bar_x, 1);
        mbar_init_fence();
    }
    __syncthreads();
    if (warp == 8) {
        if (lane == 0) {
            for (int ks = 0; ks < K3_NK; ks++) {
                const int s = ks % K3_STAGES;
                const uint32_t st = sbase + s * K3_STAGE_BYTES;
                if (ks == K3_NKH) pdl_wait();
                mbar_wait(bar_empty + 8 * s, ((ks / K3_STAGES) & 1) ^ 1);
                mbar_expect_tx(bar_full + 8 * s, K3_STAGE_BYTES);
                if (ks < K3_NKH) {
                    tma_load_2d(st, &tm_h, ks * 64, rb * 128, bar_full + 8 * s);
                    tma_load_2d(st + 16384, &tm_w2, cb * 64, ks * 64, bar_full + 8 * s);
                } else {
                    tma_load_2d(st, &tm_o, (ks - K3_NKH) * 64, rb * 128, bar_full + 8 * s);
                    tma_load_2d(st + 16384, &tm_wo, cb * 64, (ks - K3_NKH) * 64, bar_full + 8 * s);
                }
                if (ks == K3_STAGES - 1) {
                    mbar_expect_tx(bar_x, 16384);
                    tma_load_2d(sX, &tm_x, cb * 64, rb * 128, bar_x);
                }
            }
        }
    } else {
        const int wg = warp >> 2;
        float accY[32], accS[32];
#pragma unroll
        for (int i = 0; i < 32; i++) { accY[i] = 0.f; accS[i] = 0.f; }
        const uint64_t dA0 = make_desc(sbase + wg * 8192, 16, 1024, 1);
        const uint64_t dB0 = make_desc(sbase + 16384, 8192, 1024, 1);
        for (int ks = 0; ks < K3_NKH; ks++) {
            const int s = ks % K3_STAGES;
            mbar_wait(bar_full + 8 * s, (ks / K3_STAGES) & 1);
            wg_fence();
#pragma unroll
            for (int kk = 0; kk < 4; kk++)
                wgmma_ss_n64_tb(accY, dA0 + (uint64_t)((s * K3_STAGE_BYTES + kk * 32) >> 4),
                                dB0 + (uint64_t)((s * K3_STAGE_BYTES + kk * 2048) >> 4), (ks | kk) != 0);
            wg_commit();
            if (ks > 0) {
                wg_wait<1>();
                if (lane == 0) mbar_arrive(bar_empty + 8 * ((ks - 1) % K3_STAGES));
            }
        }
        if (tid == 0) DEV_STAMP(2, 1);
        for (int ks = K3_NKH; ks < K3_NK; ks++) {
            const int s = ks % K3_STAGES;
            mbar_wait(bar_full + 8 * s, (ks / K3_STAGES) & 1);
            wg_fence();
#pragma unroll
            for (int kk = 0; kk < 4; kk++)
                wgmma_ss_n64_tb(accS, dA0 + (uint64_t)((s * K3_STAGE_BYTES + kk * 32) >> 4),
                                dB0 + (uint64_t)((s * K3_STAGE_BYTES + kk * 2048) >> 4), ((ks - K3_NKH) | kk) != 0);
            wg_commit();
            wg_wait<1>();
            if (lane == 0) mbar_arrive(bar_empty + 8 * ((ks - 1) % K3_STAGES));
        }
        wg_wait<0>();
        if (tid == 0) DEV_STAMP(2, 2);
        mbar_wait(bar_x, 0);
        const int g = lane >> 2, t = lane & 3;
        const int row0 = warp * 16 + g;
#pragma unroll
        for (int j = 0; j < 8; j++) {
            const uint32_t bb = __ldg(reinterpret_cast<const uint32_t*>(b2 + cb * 64 + j * 8 + 2 * t));
            const float b0 = bf_lo(bb), b1v = bf_hi(bb);
#pragma unroll
            for (int h = 0; h < 2; h++) {
                const int row = row0 + h * 8;
                const uint32_t a = sX + row * 128 + ((j ^ (row & 7)) << 4) + t * 4;
                uint32_t xv;
                asm volatile("ld.shared.b32 %0, [%1];" : "=r"(xv) : "r"(a) : "memory");
                const float z0 = accY[4 * j + 2 * h] + b0, z1 = accY[4 * j + 2 * h + 1] + b1v;
                const float g0 = __fdividef(z0, 1.0f + __expf(-z0)), g1 = __fdividef(z1, 1.0f + __expf(-z1));
                const uint32_t ov = pack_bf16(bf_lo(xv) + accS[4 * j + 2 * h] * g0, bf_hi(xv) + accS[4 * j + 2 * h + 1] * g1);
                asm volatile("st.shared.b32 [%0], %1;" ::"r"(a), "r"(ov) : "memory");
            }
        }
        fence_proxy_async();
        named_bar_sync(1 + wg, 128);
        if ((tid & 127) == 0) {
            tma_store_2d(&tm_out, sX + wg * 8192, cb * 64, rb * 128 + wg * 64);
            tma_store_commit();
            if (tid == 0) DEV_STAMP(2, 3);
            tma_store_wait();
            if (tid == 0) DEV_STAMP(2, 4);
        }
    }
}

typedef CUresult (*EncodeFn)(CUtensorMap*, CUtensorMapDataType, cuuint32_t, void*, const cuuint64_t*, const cuuint64_t*,
                             const cuuint32_t*, const cuuint32_t*, CUtensorMapInterleave, CUtensorMapSwizzle,
                             CUtensorMapL2promotion, CUtensorMapFloatOOBfill);

struct HostState {
    bool ready;
    const void* key[11];
    CUtensorMap wq, wk, wv, w1, qo, ho, hi, oi, w2, wo, xi, out;
    void *pQ, *pKV, *pH, *pO, *pMax, *pRow, *pCol;
};
HostState g_hs;

void make_map(EncodeFn fn, CUtensorMap* m, const void* ptr, uint64_t inner, uint64_t outer, uint32_t box_in, uint32_t box_out) {
    cuuint64_t dims[2] = {inner, outer};
    cuuint64_t strides[1] = {inner * 2};
    cuuint32_t box[2] = {box_in, box_out};
    cuuint32_t es[2] = {1, 1};
    fn(m, CU_TENSOR_MAP_DATA_TYPE_BFLOAT16, 2, const_cast<void*>(ptr), dims, strides, box, es, CU_TENSOR_MAP_INTERLEAVE_NONE,
       CU_TENSOR_MAP_SWIZZLE_128B, CU_TENSOR_MAP_L2_PROMOTION_L2_256B, CU_TENSOR_MAP_FLOAT_OOB_FILL_NONE);
}

template <typename... KArgs, typename... Args>
void launch(void (*kern)(KArgs...), int grid, int block, int smem, bool pdl, Args... args) {
    cudaLaunchConfig_t cfg = {};
    cfg.gridDim = dim3(grid); cfg.blockDim = dim3(block); cfg.dynamicSmemBytes = smem; cfg.stream = cudaStreamPerThread;
    cudaLaunchAttribute at[1];
    at[0].id = cudaLaunchAttributeProgrammaticStreamSerialization;
    at[0].val.programmaticStreamSerializationAllowed = 1;
    cfg.attrs = at; cfg.numAttrs = pdl ? 1 : 0;
    cudaLaunchKernelEx(&cfg, kern, KArgs(args)...);
}

}

extern "C" void kernel_launch(void* const* d_in, const int* in_sizes, int n_in, void* d_out, int out_size) {
    (void)in_sizes; (void)n_in; (void)out_size;
    HostState& hs = g_hs;
    bool same = hs.ready;
    for (int i = 0; i < 10 && same; i++) same = hs.key[i] == d_in[i];
    same = same && hs.key[10] == d_out;
    if (!same) {
        void* fp = nullptr;
        cudaDriverEntryPointQueryResult qr;
        cudaGetDriverEntryPoint("cuTensorMapEncodeTiled", &fp, cudaEnableDefault, &qr);
        EncodeFn fn = (EncodeFn)fp;
        cudaGetSymbolAddress(&hs.pQ, g_Q); cudaGetSymbolAddress(&hs.pKV, g_KV); cudaGetSymbolAddress(&hs.pH, g_H);
        cudaGetSymbolAddress(&hs.pO, g_O); cudaGetSymbolAddress(&hs.pMax, g_kvmax);
        cudaGetSymbolAddress(&hs.pRow, g_rowstat); cudaGetSymbolAddress(&hs.pCol, g_colsum);
        make_map(fn, &hs.wq, d_in[1], 512, 512, 64, 64);
        make_map(fn, &hs.wk, d_in[2], 16, 512, 64, 64);
        make_map(fn, &hs.wv, d_in[3], 16, 512, 64, 64);
        make_map(fn, &hs.w1, d_in[6], F_DIM, 512, 64, 64);
        make_map(fn, &hs.qo, hs.pQ, 512, S_LEN, 64, 64);
        make_map(fn, &hs.ho, hs.pH, F_DIM, S_LEN, 64, 64);
        make_map(fn, &hs.hi, hs.pH, F_DIM, S_LEN, 64, 128);
        make_map(fn, &hs.oi, hs.pO, 512, S_LEN, 64, 128);
        make_map(fn, &hs.w2, d_in[8], 512, F_DIM, 64, 64);
        make_map(fn, &hs.wo, d_in[4], 512, 512, 64, 64);
        make_map(fn, &hs.xi, d_in[0], 512, S_LEN, 64, 128);
        make_map(fn, &hs.out, d_out, 512, S_LEN, 64, 64);
        cudaFuncSetAttribute(k1_proj, cudaFuncAttributeMaxDynamicSharedMemorySize, K1_SMEM);
        cudaFuncSetAttribute(k2_attn, cudaFuncAttributeMaxDynamicSharedMemorySize, AT_SMEM);
        cudaFuncSetAttribute(k3_out, cudaFuncAttributeMaxDynamicSharedMemorySize, K3_SMEM);
        for (int i = 0; i < 10; i++) hs.key[i] = d_in[i];
        hs.key[10] = d_out;
        hs.ready = true;
    }
    launch(k0_stats, K0_ROW_BLOCKS + 40, 256, 0, false, (const __nv_bfloat16*)d_in[0], (const __nv_bfloat16*)d_in[1],
           (const __nv_bfloat16*)d_in[2], (const __nv_bfloat16*)d_in[3], (const __nv_bfloat16*)d_in[6], (float2*)hs.pRow, (float*)hs.pCol);
    launch(k1_proj, 128, 384, K1_SMEM, true, hs.xi, hs.wq, hs.wk, hs.wv, hs.w1, hs.qo, hs.ho, (const __nv_bfloat16*)d_in[7],
           (const float2*)hs.pRow, (const float*)hs.pCol, (__nv_bfloat16*)hs.pKV, (float*)hs.pMax);
    launch(k2_attn, 128, 512, AT_SMEM, true, (const __nv_bfloat16*)hs.pQ, (const __nv_bfloat16*)hs.pKV, (const float*)hs.pMax,
           (__nv_bfloat16*)hs.pO);
    launch(k3_out, 128, 288, K3_SMEM, true, hs.hi, hs.oi, hs.w2, hs.wo, hs.xi, hs.out, (const __nv_bfloat16*)d_in[9]);
}
```

```cpp
#include <cuda_runtime.h>
#include <cuda_bf16.h>
#include <cuda.h>
#include <stdint.h>

namespace {

constexpr int S_LEN = 2048, D_MODEL = 512, F_DIM = 1792;

__device__ __align__(1024) __nv_bfloat16 g_Q[S_LEN * D_MODEL];
__device__ __align__(1024) __nv_bfloat16 g_KV[6 * S_LEN * 8];
__device__ __align__(1024) __nv_bfloat16 g_H[S_LEN * F_DIM];
__device__ __align__(1024) __nv_bfloat16 g_O[S_LEN * D_MODEL];
__device__ __align__(1024) float g_kvmax[256];
__device__ __align__(1024) float2 g_rowstat[S_LEN];
__device__ __align__(1024) float g_colsum[40 * 64];

#define DEV_STAMP(k, e) do {} while (0)
__device__ __forceinline__ uint32_t smem_u32(const void* p) { return (uint32_t)__cvta_generic_to_shared(p); }
__device__ __forceinline__ void wg_fence() { asm volatile("wgmma.fence.sync.aligned;" ::: "memory"); }
__device__ __forceinline__ void wg_commit() { asm volatile("wgmma.commit_group.sync.aligned;" ::: "memory"); }
template <int N> __device__ __forceinline__ void wg_wait() { asm volatile("wgmma.wait_group.sync.aligned %0;" ::"n"(N) : "memory"); }
__device__ __forceinline__ void fence_proxy_async() { asm volatile("fence.proxy.async.shared::cta;" ::: "memory"); }
__device__ __forceinline__ void mbar_init(uint32_t bar, int cnt) { asm volatile("mbarrier.init.shared::cta.b64 [%0], %1;" ::"r"(bar), "r"(cnt) : "memory"); }
__device__ __forceinline__ void mbar_init_fence() { asm volatile("fence.mbarrier_init.release.cluster;" ::: "memory"); }
__device__ __forceinline__ void mbar_expect_tx(uint32_t bar, uint32_t bytes) {
    asm volatile("mbarrier.arrive.expect_tx.shared::cta.b64 _, [%0], %1;" ::"r"(bar), "r"(bytes) : "memory");
}
__device__ __forceinline__ void mbar_arrive(uint32_t bar) { asm volatile("mbarrier.arrive.shared::cta.b64 _, [%0];" ::"r"(bar) : "memory"); }
__device__ __forceinline__ bool mbar_try(uint32_t bar, uint32_t parity) {
    uint32_t ok;
    asm volatile("{\n.reg .pred p;\nmbarrier.try_wait.parity.shared::cta.b64 p, [%1], %2;\nselp.u32 %0, 1, 0, p;\n}\n"
                 : "=r"(ok) : "r"(bar), "r"(parity) : "memory");
    return ok != 0;
}
__device__ __forceinline__ void mbar_wait(uint32_t bar, uint32_t parity) {
    if (mbar_try(bar, parity)) return;
    uint32_t n = 0;
#pragma unroll 1
    while (!mbar_try(bar, parity)) {
        if (++n > (1u << 24)) __trap();
    }
}
__device__ __forceinline__ void bulk_g2s(uint32_t dst, const void* src, uint32_t bytes, uint32_t bar) {
    asm volatile("cp.async.bulk.shared::cluster.global.mbarrier::complete_tx::bytes [%0], [%1], %2, [%3];"
                 ::"r"(dst), "l"(src), "r"(bytes), "r"(bar) : "memory");
}
__device__ __forceinline__ void tma_load_2d(uint32_t dst, const CUtensorMap* tm, int c0, int c1, uint32_t bar) {
    asm volatile("cp.async.bulk.tensor.2d.shared::cluster.global.mbarrier::complete_tx::bytes [%0], [%1, {%3, %4}], [%2];"
                 ::"r"(dst), "l"((uint64_t)tm), "r"(bar), "r"(c0), "r"(c1) : "memory");
}
__device__ __forceinline__ void tma_load_2d_mc(uint32_t dst, const CUtensorMap* tm, int c0, int c1, uint32_t bar, uint16_t mask) {
    asm volatile("cp.async.bulk.tensor.2d.shared::cluster.global.mbarrier::complete_tx::bytes.multicast::cluster [%0], [%1, {%3, %4}], [%2], %5;"
                 ::"r"(dst), "l"((uint64_t)tm), "r"(bar), "r"(c0), "r"(c1), "h"(mask) : "memory");
}
__device__ __forceinline__ void mbar_arrive_remote(uint32_t bar, uint32_t cta) {
    asm volatile("{\n.reg .b32 ra;\nmapa.shared::cluster.u32 ra, %0, %1;\nmbarrier.arrive.release.cluster.shared::cluster.b64 _, [ra];\n}\n"
                 ::"r"(bar), "r"(cta) : "memory");
}
__device__ __forceinline__ void cluster_sync_all() {
    asm volatile("barrier.cluster.arrive.release;\nbarrier.cluster.wait.acquire;" ::: "memory");
}
__device__ __forceinline__ void tma_store_2d(const CUtensorMap* tm, uint32_t src, int c0, int c1) {
    asm volatile("cp.async.bulk.tensor.2d.global.shared::cta.bulk_group [%0, {%2, %3}], [%1];"
                 ::"l"((uint64_t)tm), "r"(src), "r"(c0), "r"(c1) : "memory");
}
__device__ __forceinline__ void tma_store_commit() { asm volatile("cp.async.bulk.commit_group;" ::: "memory"); }
__device__ __forceinline__ void tma_store_wait() { asm volatile("cp.async.bulk.wait_group 0;" ::: "memory"); }
__device__ __forceinline__ void tma_prefetch_desc(const CUtensorMap* tm) { asm volatile("prefetch.tensormap [%0];" ::"l"((uint64_t)tm) : "memory"); }
__device__ __forceinline__ void named_bar_sync(int id, int n) { asm volatile("bar.sync %0, %1;" ::"r"(id), "r"(n) : "memory"); }
__device__ __forceinline__ void pdl_wait() { asm volatile("griddepcontrol.wait;" ::: "memory"); }
__device__ __forceinline__ void pdl_launch() { asm volatile("griddepcontrol.launch_dependents;" ::: "memory"); }
template <int N> __device__ __forceinline__ void reg_alloc() { asm volatile("setmaxnreg.inc.sync.aligned.u32 %0;" ::"n"(N)); }
template <int N> __device__ __forceinline__ void reg_dealloc() { asm volatile("setmaxnreg.dec.sync.aligned.u32 %0;" ::"n"(N)); }
__device__ __forceinline__ float ex2(float x) { float y; asm("ex2.approx.ftz.f32 %0, %1;" : "=f"(y) : "f"(x)); return y; }
__device__ __forceinline__ uint32_t pack_bf16(float lo, float hi) {
    uint32_t r; asm("cvt.rn.bf16x2.f32 %0, %1, %2;" : "=r"(r) : "f"(hi), "f"(lo)); return r;
}
__device__ __forceinline__ uint32_t pack_bf16_relu(float lo, float hi) {
    uint32_t r; asm("cvt.rn.relu.bf16x2.f32 %0, %1, %2;" : "=r"(r) : "f"(hi), "f"(lo)); return r;
}
__device__ __forceinline__ uint32_t mul_bf16x2(uint32_t a, uint32_t b) {
    uint32_t r; asm("mul.rn.bf16x2 %0, %1, %2;" : "=r"(r) : "r"(a), "r"(b)); return r;
}
__device__ __forceinline__ float bf_lo(uint32_t v) { return __uint_as_float(v << 16); }
__device__ __forceinline__ float bf_hi(uint32_t v) { return __uint_as_float(v & 0xFFFF0000u); }
__device__ __forceinline__ void stmatrix_x4(uint32_t addr, uint32_t r0, uint32_t r1, uint32_t r2, uint32_t r3) {
    asm volatile("stmatrix.sync.aligned.m8n8.x4.shared.b16 [%0], {%1,%2,%3,%4};" ::"r"(addr), "r"(r0), "r"(r1), "r"(r2), "r"(r3) : "memory");
}
__device__ __forceinline__ uint64_t make_desc(uint32_t addr, uint32_t lbo, uint32_t sbo, uint32_t swz) {
    return (uint64_t)((addr & 0x3FFFF) >> 4) | ((uint64_t)(lbo >> 4) << 16) | ((uint64_t)(sbo >> 4) << 32) | ((uint64_t)swz << 62);
}

__device__ __forceinline__ void wgmma_ss_n256_tb(float* d, uint64_t descA, uint64_t descB, int scaleD) {
    asm volatile("{\n.reg .pred p;\nsetp.ne.b32 p, %130, 0;\n"
      "wgmma.mma_async.sync.aligned.m64n256k16.f32.bf16.bf16 {%0,%1,%2,%3,%4,%5,%6,%7,%8,%9,%10,%11,%12,%13,%14,%15,%16,%17,%18,%19,%20,%21,%22,%23,%24,%25,%26,%27,%28,%29,%30,%31,%32,%33,%34,%35,%36,%37,%38,%39,%40,%41,%42,%43,%44,%45,%46,%47,%48,%49,%50,%51,%52,%53,%54,%55,%56,%57,%58,%59,%60,%61,%62,%63,%64,%65,%66,%67,%68,%69,%70,%71,%72,%73,%74,%75,%76,%77,%78,%79,%80,%81,%82,%83,%84,%85,%86,%87,%88,%89,%90,%91,%92,%93,%94,%95,%96,%97,%98,%99,%100,%101,%102,%103,%104,%105,%106,%107,%108,%109,%110,%111,%112,%113,%114,%115,%116,%117,%118,%119,%120,%121,%122,%123,%124,%125,%126,%127}, %128, %129, p, 1, 1, 0, 1;\n}\n"
      : "+f"(d[0]), "+f"(d[1]), "+f"(d[2]), "+f"(d[3]), "+f"(d[4]), "+f"(d[5]), "+f"(d[6]), "+f"(d[7]), "+f"(d[8]), "+f"(d[9]), "+f"(d[10]), "+f"(d[11]), "+f"(d[12]), "+f"(d[13]), "+f"(d[14]), "+f"(d[15]), "+f"(d[16]), "+f"(d[17]), "+f"(d[18]), "+f"(d[19]), "+f"(d[20]), "+f"(d[21]), "+f"(d[22]), "+f"(d[23]), "+f"(d[24]), "+f"(d[25]), "+f"(d[26]), "+f"(d[27]), "+f"(d[28]), "+f"(d[29]), "+f"(d[30]), "+f"(d[31]), "+f"(d[32]), "+f"(d[33]), "+f"(d[34]), "+f"(d[35]), "+f"(d[36]), "+f"(d[37]), "+f"(d[38]), "+f"(d[39]), "+f"(d[40]), "+f"(d[41]), "+f"(d[42]), "+f"(d[43]), "+f"(d[44]), "+f"(d[45]), "+f"(d[46]), "+f"(d[47]), "+f"(d[48]), "+f"(d[49]), "+f"(d[50]), "+f"(d[51]), "+f"(d[52]), "+f"(d[53]), "+f"(d[54]), "+f"(d[55]), "+f"(d[56]), "+f"(d[57]), "+f"(d[58]), "+f"(d[59]), "+f"(d[60]), "+f"(d[61]), "+f"(d[62]), "+f"(d[63]), "+f"(d[64]), "+f"(d[65]), "+f"(d[66]), "+f"(d[67]), "+f"(d[68]), "+f"(d[69]), "+f"(d[70]), "+f"(d[71]), "+f"(d[72]), "+f"(d[73]), "+f"(d[74]), "+f"(d[75]), "+f"(d[76]), "+f"(d[77]), "+f"(d[78]), "+f"(d[79]), "+f"(d[80]), "+f"(d[81]), "+f"(d[82]), "+f"(d[83]), "+f"(d[84]), "+f"(d[85]), "+f"(d[86]), "+f"(d[87]), "+f"(d[88]), "+f"(d[89]), "+f"(d[90]), "+f"(d[91]), "+f"(d[92]), "+f"(d[93]), "+f"(d[94]), "+f"(d[95]), "+f"(d[96]), "+f"(d[97]), "+f"(d[98]), "+f"(d[99]), "+f"(d[100]), "+f"(d[101]), "+f"(d[102]), "+f"(d[103]), "+f"(d[104]), "+f"(d[105]), "+f"(d[106]), "+f"(d[107]), "+f"(d[108]), "+f"(d[109]), "+f"(d[110]), "+f"(d[111]), "+f"(d[112]), "+f"(d[113]), "+f"(d[114]), "+f"(d[115]), "+f"(d[116]), "+f"(d[117]), "+f"(d[118]), "+f"(d[119]), "+f"(d[120]), "+f"(d[121]), "+f"(d[122]), "+f"(d[123]), "+f"(d[124]), "+f"(d[125]), "+f"(d[126]), "+f"(d[127])
      : "l"(descA), "l"(descB), "r"(scaleD));
}
__device__ __forceinline__ void wgmma_ss_n64_tb(float* d, uint64_t descA, uint64_t descB, int scaleD) {
    asm volatile("{\n.reg .pred p;\nsetp.ne.b32 p, %34, 0;\n"
      "wgmma.mma_async.sync.aligned.m64n64k16.f32.bf16.bf16 {%0,%1,%2,%3,%4,%5,%6,%7,%8,%9,%10,%11,%12,%13,%14,%15,%16,%17,%18,%19,%20,%21,%22,%23,%24,%25,%26,%27,%28,%29,%30,%31}, %32, %33, p, 1, 1, 0, 1;\n}\n"
      : "+f"(d[0]), "+f"(d[1]), "+f"(d[2]), "+f"(d[3]), "+f"(d[4]), "+f"(d[5]), "+f"(d[6]), "+f"(d[7]), "+f"(d[8]), "+f"(d[9]), "+f"(d[10]), "+f"(d[11]), "+f"(d[12]), "+f"(d[13]), "+f"(d[14]), "+f"(d[15]), "+f"(d[16]), "+f"(d[17]), "+f"(d[18]), "+f"(d[19]), "+f"(d[20]), "+f"(d[21]), "+f"(d[22]), "+f"(d[23]), "+f"(d[24]), "+f"(d[25]), "+f"(d[26]), "+f"(d[27]), "+f"(d[28]), "+f"(d[29]), "+f"(d[30]), "+f"(d[31])
      : "l"(descA), "l"(descB), "r"(scaleD));
}
__device__ __forceinline__ void wgmma_qk_n64(float* d, const uint32_t* a, uint64_t descB) {
    asm volatile("wgmma.mma_async.sync.aligned.m64n64k16.f32.bf16.bf16 {%0,%1,%2,%3,%4,%5,%6,%7,%8,%9,%10,%11,%12,%13,%14,%15,%16,%17,%18,%19,%20,%21,%22,%23,%24,%25,%26,%27,%28,%29,%30,%31}, {%32,%33,%34,%35}, %36, 0, 1, 1, 0;\n"
      : "=f"(d[0]), "=f"(d[1]), "=f"(d[2]), "=f"(d[3]), "=f"(d[4]), "=f"(d[5]), "=f"(d[6]), "=f"(d[7]), "=f"(d[8]), "=f"(d[9]), "=f"(d[10]), "=f"(d[11]), "=f"(d[12]), "=f"(d[13]), "=f"(d[14]), "=f"(d[15]), "=f"(d[16]), "=f"(d[17]), "=f"(d[18]), "=f"(d[19]), "=f"(d[20]), "=f"(d[21]), "=f"(d[22]), "=f"(d[23]), "=f"(d[24]), "=f"(d[25]), "=f"(d[26]), "=f"(d[27]), "=f"(d[28]), "=f"(d[29]), "=f"(d[30]), "=f"(d[31])
      : "r"(a[0]), "r"(a[1]), "r"(a[2]), "r"(a[3]), "l"(descB));
}
__device__ __forceinline__ void wgmma_qk_acc_n64(float* d, const uint32_t* a, uint64_t descB) {
    asm volatile("wgmma.mma_async.sync.aligned.m64n64k16.f32.bf16.bf16 {%0,%1,%2,%3,%4,%5,%6,%7,%8,%9,%10,%11,%12,%13,%14,%15,%16,%17,%18,%19,%20,%21,%22,%23,%24,%25,%26,%27,%28,%29,%30,%31}, {%32,%33,%34,%35}, %36, 1, 1, 1, 0;\n"
      : "+f"(d[0]), "+f"(d[1]), "+f"(d[2]), "+f"(d[3]), "+f"(d[4]), "+f"(d[5]), "+f"(d[6]), "+f"(d[7]), "+f"(d[8]), "+f"(d[9]), "+f"(d[10]), "+f"(d[11]), "+f"(d[12]), "+f"(d[13]), "+f"(d[14]), "+f"(d[15]), "+f"(d[16]), "+f"(d[17]), "+f"(d[18]), "+f"(d[19]), "+f"(d[20]), "+f"(d[21]), "+f"(d[22]), "+f"(d[23]), "+f"(d[24]), "+f"(d[25]), "+f"(d[26]), "+f"(d[27]), "+f"(d[28]), "+f"(d[29]), "+f"(d[30]), "+f"(d[31])
      : "r"(a[0]), "r"(a[1]), "r"(a[2]), "r"(a[3]), "l"(descB));
}

__device__ __forceinline__ void wgmma_pv(float* d, uint32_t a0, uint32_t a1, uint32_t a2, uint32_t a3, uint64_t descB) {
    asm volatile("wgmma.mma_async.sync.aligned.m64n24k16.f32.bf16.bf16 {%0,%1,%2,%3,%4,%5,%6,%7,%8,%9,%10,%11}, {%12,%13,%14,%15}, %16, 1, 1, 1, 1;\n"
                 : "+f"(d[0]), "+f"(d[1]), "+f"(d[2]), "+f"(d[3]), "+f"(d[4]), "+f"(d[5]), "+f"(d[6]), "+f"(d[7]), "+f"(d[8]), "+f"(d[9]), "+f"(d[10]), "+f"(d[11])
                 : "r"(a0), "r"(a1), "r"(a2), "r"(a3), "l"(descB));
}

__device__ __forceinline__ void k1_panel(int g, int i, int& type, int& col) {
    if (g < 6) {
        int p = g * 5 + i;
        if (p < 8) { type = 0; col = p * 64; } else { type = 1; col = (p - 8) * 64; }
    } else {
        if (i < 3) { type = 1; col = (22 + (g - 6) * 3 + i) * 64; } else { type = 2 + (g - 6); col = 0; }
    }
}

constexpr int K0_ROW_BLOCKS = 128;
__global__ void __launch_bounds__(256, 6)
k0_stats(const __nv_bfloat16* __restrict__ x, const __nv_bfloat16* __restrict__ wq, const __nv_bfloat16* __restrict__ wk,
         const __nv_bfloat16* __restrict__ wv, const __nv_bfloat16* __restrict__ w1,
         float2* __restrict__ rowstat, float* __restrict__ colsum) {
    pdl_launch();
    const int tid = threadIdx.x, warp = tid >> 5, lane = tid & 31;
    if (tid == 0) DEV_STAMP(3, 0);
    if (blockIdx.x < K0_ROW_BLOCKS) {
        const int row0 = blockIdx.x * 16 + warp * 2;
        const uint4* xp = reinterpret_cast<const uint4*>(x + (size_t)row0 * D_MODEL);
        uint4 v[2][2];
#pragma unroll
        for (int r = 0; r < 2; r++) { v[r][0] = __ldg(xp + r * 64 + lane); v[r][1] = __ldg(xp + r * 64 + 32 + lane); }
#pragma unroll
        for (int r = 0; r < 2; r++) {
            float f[16];
            const uint32_t w[8] = {v[r][0].x, v[r][0].y, v[r][0].z, v[r][0].w, v[r][1].x, v[r][1].y, v[r][1].z, v[r][1].w};
#pragma unroll
            for (int i = 0; i < 8; i++) { f[2 * i] = bf_lo(w[i]); f[2 * i + 1] = bf_hi(w[i]); }
            float sum = 0.f;
#pragma unroll
            for (int i = 0; i < 16; i++) sum += f[i];
#pragma unroll
            for (int o = 16; o > 0; o >>= 1) sum += __shfl_xor_sync(0xffffffffu, sum, o);
            const float mean = sum * (1.0f / D_MODEL);
            float sq = 0.f;
#pragma unroll
            for (int i = 0; i < 16; i++) { const float d = f[i] - mean; sq += d * d; }
#pragma unroll
            for (int o = 16; o > 0; o >>= 1) sq += __shfl_xor_sync(0xffffffffu, sq, o);
            const float rstd = rsqrtf(sq * (1.0f / D_MODEL) + 1e-5f);
            if (lane == 0) rowstat[row0 + r] = make_float2(rstd, mean * rstd);
        }
    } else {
        __shared__ float red[8][64];
        const int pb = blockIdx.x - K0_ROW_BLOCKS;
        const int g = pb / 5, i = pb % 5;
        if (g >= 6 && i == 4) return;
        int type, col; k1_panel(g, i, type, col);
        const __nv_bfloat16* w = type == 0 ? wq : type == 1 ? w1 : type == 2 ? wk : wv;
        const int ld = type == 0 ? D_MODEL : type == 1 ? F_DIM : 16;
        const int c8 = lane & 7, kr = lane >> 3;
        float sacc[8];
#pragma unroll
        for (int c = 0; c < 8; c++) sacc[c] = 0.f;
        if (type <= 1 || c8 < 2) {
            const __nv_bfloat16* wp = w + (size_t)(warp * 64 + kr) * ld + col + c8 * 8;
#pragma unroll
            for (int h = 0; h < 2; h++) {
                uint4 u[8];
#pragma unroll
                for (int k = 0; k < 8; k++) u[k] = __ldg(reinterpret_cast<const uint4*>(wp + (size_t)((h * 8 + k) * 4) * ld));
#pragma unroll
                for (int k = 0; k < 8; k++) {
                    sacc[0] += bf_lo(u[k].x); sacc[1] += bf_hi(u[k].x); sacc[2] += bf_lo(u[k].y); sacc[3] += bf_hi(u[k].y);
                    sacc[4] += bf_lo(u[k].z); sacc[5] += bf_hi(u[k].z); sacc[6] += bf_lo(u[k].w); sacc[7] += bf_hi(u[k].w);
                }
            }
        }
#pragma unroll
        for (int c = 0; c < 8; c++) {
            sacc[c] += __shfl_xor_sync(0xffffffffu, sacc[c], 8);
            sacc[c] += __shfl_xor_sync(0xffffffffu, sacc[c], 16);
        }
        if (lane < 8) {
#pragma unroll
            for (int c = 0; c < 8; c++) red[warp][lane * 8 + c] = sacc[c];
        }
        __syncthreads();
        if (tid < 64) {
            float a0 = 0.f;
#pragma unroll
            for (int w8 = 0; w8 < 8; w8++) a0 += red[w8][tid];
            colsum[pb * 64 + tid] = a0;
        }
    }
    if (tid == 0) DEV_STAMP(3, 1);
}

constexpr int K1_STAGES = 4;
constexpr int K1_PANEL_BYTES = 64 * 128;
constexpr int K1_STAGE_BYTES = 16384 + 5 * K1_PANEL_BYTES;
constexpr int K1_SMEM = K1_STAGES * K1_STAGE_BYTES + 128 + 320 * 8;
constexpr float Q_SCALE = 0.25f * 1.4426950408889634f;

__global__ void __maxnreg__(160)
k1_proj(const __grid_constant__ CUtensorMap tm_x, const __grid_constant__ CUtensorMap tm_wq,
        const __grid_constant__ CUtensorMap tm_wk, const __grid_constant__ CUtensorMap tm_wv,
        const __grid_constant__ CUtensorMap tm_w1, const __grid_constant__ CUtensorMap tm_qo,
        const __grid_constant__ CUtensorMap tm_ho, const __nv_bfloat16* __restrict__ b1,
        const float2* __restrict__ rowstat, const float* __restrict__ colsum,
        __nv_bfloat16* __restrict__ kv, float* __restrict__ kvmax) {
    extern __shared__ __align__(1024) uint8_t smem_raw[];
    const uint32_t sbase = smem_u32(smem_raw);
    const uint32_t bar_full = sbase + K1_STAGES * K1_STAGE_BYTES, bar_empty = bar_full + 8 * K1_STAGES, bar_col = bar_empty + 8 * K1_STAGES;
    const uint32_t sCol = bar_full + 128;
    const int tid = threadIdx.x, warp = tid >> 5, lane = tid & 31;
    const int rb = blockIdx.x >> 3, grp = blockIdx.x & 7;
    const int npanels = grp < 6 ? 5 : 4;
    if (tid == 0) DEV_STAMP(0, 0);

    if (tid == 256) {
        for (int s = 0; s < K1_STAGES; s++) { mbar_init(bar_full + 8 * s, 1); mbar_init(bar_empty + 8 * s, 8); }
        mbar_init(bar_col, 32);
        mbar_init_fence();
    }
    __syncthreads();
    pdl_launch();

    if (warp >= 8) {
        reg_dealloc<40>();
        if (warp == 8) {
            if (lane == 0) {
                const CUtensorMap* tms[5]; int cols[5];
#pragma unroll
                for (int i = 0; i < 5; i++) {
                    int type, col; k1_panel(grp, i, type, col);
                    tms[i] = type == 0 ? &tm_wq : type == 1 ? &tm_w1 : type == 2 ? &tm_wk : &tm_wv;
                    cols[i] = col;
                }
                for (int ks = 0; ks < 8; ks++) {
                    const int s = ks % K1_STAGES;
                    const uint32_t st = sbase + s * K1_STAGE_BYTES;
                    mbar_wait(bar_empty + 8 * s, ((ks / K1_STAGES) & 1) ^ 1);
                    mbar_expect_tx(bar_full + 8 * s, 16384 + npanels * K1_PANEL_BYTES);
                    tma_load_2d(st, &tm_x, ks * 64, rb * 128, bar_full + 8 * s);
#pragma unroll
                    for (int i = 0; i < 5; i++)
                        if (i < npanels) tma_load_2d(st + 16384 + i * K1_PANEL_BYTES, tms[i], cols[i], ks * 64, bar_full + 8 * s);
                }
            }
        } else if (warp == 9) {
            pdl_wait();
#pragma unroll
            for (int p = 0; p < 5; p++) {
                if (p < npanels) {
                    int type, col; k1_panel(grp, p, type, col);
                    const float2 cs = reinterpret_cast<const float2*>(colsum + (grp * 5 + p) * 64)[lane];
                    uint32_t bb = 0;
                    if (type == 1) bb = __ldg(reinterpret_cast<const uint32_t*>(b1 + col) + lane);
                    asm volatile("st.shared.v4.f32 [%0], {%1,%2,%3,%4};" ::"r"(sCol + (p * 64 + lane * 2) * 8),
                                 "f"(cs.x), "f"(bf_lo(bb)), "f"(cs.y), "f"(bf_hi(bb)) : "memory");
                }
            }
            mbar_arrive(bar_col);
        }
    } else {
        reg_alloc<216>();
        const int wg = warp >> 2;
        const int g = lane >> 2, t = lane & 3;
        const int wrow = (warp & 3) * 16;
        float acc[160];
#pragma unroll
        for (int i = 0; i < 160; i++) acc[i] = 0.f;
        float2 rs0, rs1;
        const uint64_t dA0 = make_desc(sbase + wg * 8192, 16, 1024, 1);
        const uint64_t dB0 = make_desc(sbase + 16384, K1_PANEL_BYTES, 1024, 1);
#define K1_MAINLOOP(FIVE)                                                                                          \
        for (int ks = 0; ks < 8; ks++) {                                                                           \
            const int s = ks % K1_STAGES;                                                                          \
            mbar_wait(bar_full + 8 * s, (ks / K1_STAGES) & 1);                                                     \
            if (ks == 0 && tid == 0) DEV_STAMP(0, 1);                                                              \
            wg_fence();                                                                                            \
            _Pragma("unroll") for (int kk = 0; kk < 4; kk++) {                                                     \
                const uint64_t dA = dA0 + (uint64_t)((s * K1_STAGE_BYTES + kk * 32) >> 4);                         \
                const uint64_t dB = dB0 + (uint64_t)((s * K1_STAGE_BYTES + kk * 2048) >> 4);                       \
                wgmma_ss_n256_tb(acc, dA, dB, (ks | kk) != 0);                                                     \
                if (FIVE) wgmma_ss_n64_tb(acc + 128, dA, dB + (uint64_t)((4 * K1_PANEL_BYTES) >> 4), (ks | kk) != 0); \
            }                                                                                                      \
            wg_commit();                                                                                           \
            if (ks == 7) {                                                                                         \
                pdl_wait();                                                                                        \
                rs0 = rowstat[rb * 128 + wg * 64 + wrow + g];                                                      \
                rs1 = rowstat[rb * 128 + wg * 64 + wrow + g + 8];                                                  \
            }                                                                                                      \
            if (ks > 0 && ks <= 4) {                                                                               \
                wg_wait<1>();                                                                                      \
                if (lane == 0) mbar_arrive(bar_empty + 8 * ((ks - 1) % K1_STAGES));                                \
            }                                                                                                      \
        }                                                                                                          \
        wg_wait<0>();
        if (npanels == 5) { K1_MAINLOOP(true) } else { K1_MAINLOOP(false) }
        if (tid == 0) DEV_STAMP(0, 2);
        mbar_wait(bar_col, 0);
        named_bar_sync(1, 256);
        const int srow = (lane & 7) + ((lane >> 3) & 1) * 8;
#pragma unroll
        for (int p = 0; p < 5; p++) {
            if (p < npanels) {
                int type, col; k1_panel(grp, p, type, col);
                float* a = acc + p * 32;
                const int nj = type <= 1 ? 8 : 2;
                const float sc = type == 0 ? Q_SCALE : 1.0f;
                const float r0x = rs0.x * sc, r0y = -rs0.y * sc, r1x = rs1.x * sc, r1y = -rs1.y * sc;
#pragma unroll
                for (int j = 0; j < 8; j++) {
                    if (j < nj) {
                        float4 c;
                        asm volatile("ld.shared.v4.f32 {%0,%1,%2,%3}, [%4];" : "=f"(c.x), "=f"(c.y), "=f"(c.z), "=f"(c.w)
                                     : "r"(sCol + (p * 64 + j * 8 + 2 * t) * 8));
                        a[4 * j] = fmaf(a[4 * j], r0x, fmaf(r0y, c.x, c.y));
                        a[4 * j + 1] = fmaf(a[4 * j + 1], r0x, fmaf(r0y, c.z, c.w));
                        a[4 * j + 2] = fmaf(a[4 * j + 2], r1x, fmaf(r1y, c.x, c.y));
                        a[4 * j + 3] = fmaf(a[4 * j + 3], r1x, fmaf(r1y, c.z, c.w));
                    }
                }
                if (type <= 1) {
                    const uint32_t stg = sbase + (p * 8 + warp) * 2048;
                    uint32_t pk[16];
                    if (type == 0) {
#pragma unroll
                        for (int j = 0; j < 8; j++) {
                            pk[2 * j] = pack_bf16(a[4 * j], a[4 * j + 1]);
                            pk[2 * j + 1] = pack_bf16(a[4 * j + 2], a[4 * j + 3]);
                        }
                    } else {
#pragma unroll
                        for (int j = 0; j < 8; j++) {
                            const uint32_t h0 = pack_bf16_relu(a[4 * j], a[4 * j + 1]), h1 = pack_bf16_relu(a[4 * j + 2], a[4 * j + 3]);
                            pk[2 * j] = mul_bf16x2(h0, h0);
                            pk[2 * j + 1] = mul_bf16x2(h1, h1);
                        }
                    }
#pragma unroll
                    for (int j = 0; j < 8; j += 2) {
                        const int c16 = j + (lane >> 4);
                        stmatrix_x4(stg + srow * 128 + ((c16 ^ (srow & 7)) << 4), pk[2 * j], pk[2 * j + 1], pk[2 * j + 2], pk[2 * j + 3]);
                    }
                    fence_proxy_async();
                    __syncwarp();
                    if (lane == 0) {
                        tma_store_2d(type == 0 ? &tm_qo : &tm_ho, stg, col, rb * 128 + warp * 16);
                        tma_store_commit();
                    }
                } else if (type == 3) {
                    const int r = wg * 64 + wrow + g;
                    const int pos0 = (r >> 2) * 64 + rb * 4 + (r & 3), pos1 = pos0 + 128;
                    uint32_t* dst = reinterpret_cast<uint32_t*>(kv + 2 * (S_LEN * 8));
                    const uint32_t r00 = pack_bf16(a[0], a[1]), r01 = pack_bf16(a[4], a[5]);
                    const uint32_t r10 = pack_bf16(a[2], a[3]), r11 = pack_bf16(a[6], a[7]);
                    dst[pos0 * 4 + t] = r00;
                    dst[S_LEN * 4 + pos0 * 4 + t] = r01;
                    dst[pos1 * 4 + t] = r10;
                    dst[S_LEN * 4 + pos1 * 4 + t] = r11;
                    float m = fmaxf(fmaxf(fmaxf(fabsf(bf_lo(r00)), fabsf(bf_hi(r00))), fmaxf(fabsf(bf_lo(r01)), fabsf(bf_hi(r01)))),
                                    fmaxf(fmaxf(fabsf(bf_lo(r10)), fabsf(bf_hi(r10))), fmaxf(fabsf(bf_lo(r11)), fabsf(bf_hi(r11)))));
#pragma unroll
                    for (int o = 16; o > 0; o >>= 1) m = fmaxf(m, __shfl_xor_sync(0xffffffffu, m, o));
                    if (lane == 0) kvmax[128 + rb * 8 + warp] = m;
                } else {
                    float* kf = reinterpret_cast<float*>(smem_raw + 96 * 1024);
                    const int r = wg * 64 + wrow + g;
                    const int pos0 = (r >> 2) * 64 + rb * 4 + (r & 3), pos1 = pos0 + 128;
                    uint32_t* dst = reinterpret_cast<uint32_t*>(kv + 4 * (S_LEN * 8));
                    dst[pos0 * 4 + t] = pack_bf16(a[0], a[1]);
                    dst[S_LEN * 4 + pos0 * 4 + t] = pack_bf16(a[4], a[5]);
                    dst[pos1 * 4 + t] = pack_bf16(a[2], a[3]);
                    dst[S_LEN * 4 + pos1 * 4 + t] = pack_bf16(a[6], a[7]);
                    kf[r * 17 + 2 * t] = a[0]; kf[r * 17 + 2 * t + 1] = a[1];
                    kf[r * 17 + 8 + 2 * t] = a[4]; kf[r * 17 + 8 + 2 * t + 1] = a[5];
                    kf[(r + 8) * 17 + 2 * t] = a[2]; kf[(r + 8) * 17 + 2 * t + 1] = a[3];
                    kf[(r + 8) * 17 + 8 + 2 * t] = a[6]; kf[(r + 8) * 17 + 8 + 2 * t + 1] = a[7];
                    named_bar_sync(1, 256);
                    if (tid < 64) {
                        const int i = tid >> 4, dim = tid & 15;
                        __nv_bfloat16* dd = kv + (dim >> 3) * (S_LEN * 8) + (rb * 4 + i) * 8 + (dim & 7);
                        float kt = 0.f;
#pragma unroll 8
                        for (int j = 0; j < 32; j++) {
                            const __nv_bfloat16 d = __float2bfloat16_rn(kf[(j * 4 + i) * 17 + dim] - kt);
                            kt += __bfloat162float(d);
                            kf[(j * 4 + i) * 17 + dim] = kt;
                            dd[j * 512] = d;
                        }
                    }
                    named_bar_sync(1, 256);
                    if (tid < 128) {
                        float n = 0.f;
#pragma unroll
                        for (int d = 0; d < 16; d++) { const float v = kf[tid * 17 + d]; n += v * v; }
                        if (!(n == n)) n = __int_as_float(0x7f800000);
#pragma unroll
                        for (int o = 8; o > 0; o >>= 1) n = fmaxf(n, __shfl_xor_sync(0xffffffffu, n, o));
                        if ((lane & 15) == 0) kvmax[rb * 8 + (tid >> 4)] = n;
                    }
                }
            }
        }
        if (tid == 0) DEV_STAMP(0, 3);
        if (lane == 0) tma_store_wait();
        if (tid == 0) DEV_STAMP(0, 4);
    }
}

constexpr int AT_KT = 64;
constexpr int AT_NCHUNK = 8;
constexpr int AT_NSTEP = S_LEN / AT_KT;
constexpr int AT_SPC = AT_NSTEP / AT_NCHUNK;
constexpr int AT_SMEM = 5 * 32768 + 256;
#define AT_SWMASK_V 0xB6DB
constexpr uint32_t AT_SWMASK = AT_SWMASK_V;

#define AT_MAGIC (383.0f + 0.00390625f - 0.5849625f)
__device__ __forceinline__ uint32_t exp2_pair_alu(float t0, float t1) {
    const uint32_t y = __byte_perm(__float_as_uint(t0), __float_as_uint(t1), 0x6521);
    const uint32_t e = y & 0x7F807F80u;
    uint32_t uh, p;
    asm("lop3.b32 %0, %1, %2, 0x3F003F00, 0xBE;" : "=r"(uh) : "r"(y), "r"(e));
    asm("fma.rn.bf16x2 %0, %1, %2, %3;" : "=r"(p) : "r"(uh), "r"(y), "r"(e));
    return p;
}

__device__ __forceinline__ void at_load_chunk(uint32_t sbase, const __nv_bfloat16* KV, uint32_t bar0, int c) {
    constexpr uint32_t cb = (S_LEN / AT_NCHUNK) * 16;
    mbar_expect_tx(bar0 + 8 * c, 4 * cb);
#pragma unroll
    for (int r = 0; r < 4; r++)
        bulk_g2s(sbase + r * 32768 + c * cb, (const uint8_t*)KV + r * 32768 + c * cb, cb, bar0 + 8 * c);
}

__device__ __forceinline__ void at_store(const float* o, __nv_bfloat16* O, int row, int lane) {
    const float l0 = __shfl_sync(0xffffffffu, o[8], lane & ~3);
    const float l1 = __shfl_sync(0xffffffffu, o[10], lane & ~3);
    const float r0 = __fdividef(1.0f, l0), r1 = __fdividef(1.0f, l1);
    const int t = lane & 3;
    uint32_t* op = reinterpret_cast<uint32_t*>(O + (size_t)(row + (lane >> 2)) * 16);
    op[t] = pack_bf16(o[0] * r0, o[1] * r0);
    op[t + 4] = pack_bf16(o[4] * r0, o[5] * r0);
    op[64 + t] = pack_bf16(o[2] * r1, o[3] * r1);
    op[64 + t + 4] = pack_bf16(o[6] * r1, o[7] * r1);
}

__global__ void __launch_bounds__(512, 1)
k2_attn(const __nv_bfloat16* __restrict__ Q, const __nv_bfloat16* __restrict__ KV, const float* __restrict__ kvmax,
        __nv_bfloat16* __restrict__ O) {
    extern __shared__ __align__(1024) uint8_t smem_raw[];
    const uint32_t sbase = smem_u32(smem_raw);
    const uint32_t bar0 = sbase + 5 * 32768;
    const int tid = threadIdx.x;
    if (tid == 0) DEV_STAMP(1, 0);
    if (tid == 0) {
        for (int i = 0; i < AT_NCHUNK; i++) mbar_init(bar0 + 8 * i, 1);
        mbar_init_fence();
    }
#pragma unroll
    for (int i = 0; i < S_LEN / 512; i++)
        asm volatile("st.shared.v4.b32 [%0], {%1,%2,%2,%2};" ::"r"(sbase + 4 * 32768 + (i * 512 + tid) * 16), "r"(0x00003F80u), "r"(0u) : "memory");
    fence_proxy_async();
    __syncthreads();
    pdl_wait();
    pdl_launch();
    if (tid == 0) DEV_STAMP(1, 1);
    if (tid == 0) { at_load_chunk(sbase, KV, bar0, 0); at_load_chunk(sbase, KV, bar0, 1); }
    const int wg = tid >> 7, warp = (tid >> 5) & 3, lane = tid & 31;
    const int g = lane >> 2, t = lane & 3;
    const int rowA = blockIdx.x * 512 + wg * 128 + warp * 16;
    uint32_t qa[4], qb[4];
    {
        const uint32_t* qp = reinterpret_cast<const uint32_t*>(Q + (size_t)(rowA + g) * 16);
        qa[0] = qp[t]; qa[2] = qp[t + 4]; qa[1] = qp[64 + t]; qa[3] = qp[64 + t + 4];
        qb[0] = qp[512 + t]; qb[2] = qp[512 + t + 4]; qb[1] = qp[512 + 64 + t]; qb[3] = qp[512 + 64 + t + 4];
    }
    const uint64_t descK0 = make_desc(sbase, 32768, 128, 0);
    const uint64_t descV0 = make_desc(sbase + 65536, 128, 32768, 0);

#define AT_EXP(P) _Pragma("unroll") for (int i = 0; i < AT_KT / 4; i++) {                       \
                if ((AT_SWMASK >> (i & 15)) & 1) P[i] = exp2_pair_alu(s[2 * i], s[2 * i + 1]);  \
                else P[i] = pack_bf16(ex2(s[2 * i]), ex2(s[2 * i + 1])); }
#define AT_PV(P, dv) _Pragma("unroll") for (int j = 0; j < AT_KT / 16; j++)                     \
                wgmma_pv(o, P[4 * j], P[4 * j + 1], P[4 * j + 2], P[4 * j + 3], (dv) + (uint64_t)(j * 16));
#define AT_STEP(PC, PN, st) {                                                                   \
                if (st == AT_SPC - 1 && mt == 0) mbar_wait(bar0 + 8 * (c + 1), 0);              \
                wg_fence();                                                                     \
                wgmma_qk_acc_n64(s, q, dK + (uint64_t)(st * AT_KT));                            \
                wg_commit();                                                                    \
                AT_PV(PC, dV + (uint64_t)(st * AT_KT));                                         \
                wg_commit();                                                                    \
                wg_wait<1>();                                                                   \
                AT_EXP(PN);                                                                     \
                wg_wait<0>(); }

#pragma unroll 1
    for (int mt = 0; mt < 2; mt++) {
        uint32_t q[4];
#pragma unroll
        for (int i = 0; i < 4; i++) q[i] = mt ? qb[i] : qa[i];
        float o[12];
#pragma unroll
        for (int i = 0; i < 12; i++) asm volatile("mov.f32 %0, 0f00000000;" : "=f"(o[i]));
        float s[AT_KT / 2];
        uint32_t p0[AT_KT / 4], p1[AT_KT / 4];
#pragma unroll
        for (int i = 0; i < AT_KT / 2; i++) {
            if ((AT_SWMASK >> ((i >> 1) & 15)) & 1) asm volatile("mov.f32 %0, %1;" : "=f"(s[i]) : "f"(AT_MAGIC));
            else asm volatile("mov.f32 %0, 0f00000000;" : "=f"(s[i]));
        }
        if (mt == 0) mbar_wait(bar0, 0);
        if (tid == 0) DEV_STAMP(1, 2 + mt);
        wg_fence();
        wgmma_qk_acc_n64(s, q, descK0);
        wg_commit();
        wg_wait<0>();
        AT_EXP(p0);
        uint64_t dK = descK0 + AT_KT, dV = descV0;
#pragma unroll 1
        for (int c = 0; c < AT_NCHUNK - 1; c++) {
            if (tid == 0 && mt == 0 && c + 2 < AT_NCHUNK) at_load_chunk(sbase, KV, bar0, c + 2);
            AT_STEP(p0, p1, 0); AT_STEP(p1, p0, 1); AT_STEP(p0, p1, 2); AT_STEP(p1, p0, 3);
            dK += AT_SPC * AT_KT; dV += AT_SPC * AT_KT;
        }
        {
            const int c = 0; (void)c;
            AT_STEP(p0, p1, 0); AT_STEP(p1, p0, 1); AT_STEP(p0, p1, 2);
            wg_fence();
            AT_PV(p1, dV + (uint64_t)(3 * AT_KT));
            wg_commit();
            wg_wait<0>();
        }
        at_store(o, O, rowA + mt * 64, lane);
    }
    if (tid == 0) DEV_STAMP(1, 4);

    bool unsafe;
    {
        float km = fmaxf(fmaxf(kvmax[lane], kvmax[lane + 32]), fmaxf(kvmax[lane + 64], kvmax[lane + 96]));
        float vm = fmaxf(fmaxf(kvmax[128 + lane], kvmax[160 + lane]), fmaxf(kvmax[192 + lane], kvmax[224 + lane]));
        float n[4];
        n[0] = bf_lo(qa[0]) * bf_lo(qa[0]) + bf_hi(qa[0]) * bf_hi(qa[0]) + bf_lo(qa[2]) * bf_lo(qa[2]) + bf_hi(qa[2]) * bf_hi(qa[2]);
        n[1] = bf_lo(qa[1]) * bf_lo(qa[1]) + bf_hi(qa[1]) * bf_hi(qa[1]) + bf_lo(qa[3]) * bf_lo(qa[3]) + bf_hi(qa[3]) * bf_hi(qa[3]);
        n[2] = bf_lo(qb[0]) * bf_lo(qb[0]) + bf_hi(qb[0]) * bf_hi(qb[0]) + bf_lo(qb[2]) * bf_lo(qb[2]) + bf_hi(qb[2]) * bf_hi(qb[2]);
        n[3] = bf_lo(qb[1]) * bf_lo(qb[1]) + bf_hi(qb[1]) * bf_hi(qb[1]) + bf_lo(qb[3]) * bf_lo(qb[3]) + bf_hi(qb[3]) * bf_hi(qb[3]);
#pragma unroll
        for (int i = 0; i < 4; i++) { n[i] += __shfl_xor_sync(0xffffffffu, n[i], 1); n[i] += __shfl_xor_sync(0xffffffffu, n[i], 2); }
#pragma unroll
        for (int o = 16; o > 0; o >>= 1) { km = fmaxf(km, __shfl_xor_sync(0xffffffffu, km, o)); vm = fmaxf(vm, __shfl_xor_sync(0xffffffffu, vm, o)); }
        const float lim = 3600.0f;
        const bool ok = (n[0] * km <= lim) && (n[1] * km <= lim) && (n[2] * km <= lim) && (n[3] * km <= lim) && (vm <= 1.0e12f);
        unsafe = __any_sync(0xffffffffu, __syncthreads_or(!ok) != 0);
    }
    if (!unsafe) return;

    if (tid == 0) {
        mbar_expect_tx(bar0, 65536);
        bulk_g2s(sbase, (const uint8_t*)KV + 4 * 32768, 32768, bar0);
        bulk_g2s(sbase + 32768, (const uint8_t*)KV + 5 * 32768, 32768, bar0);
    }
    mbar_wait(bar0, 1);
#pragma unroll 1
    for (int mt = 0; mt < 2; mt++) {
        uint32_t q[4];
#pragma unroll
        for (int i = 0; i < 4; i++) q[i] = mt ? qb[i] : qa[i];
        float o[12];
#pragma unroll
        for (int i = 0; i < 12; i++) asm volatile("mov.f32 %0, 0f00000000;" : "=f"(o[i]));
        float s[AT_KT / 2];
        float m0 = -INFINITY, m1 = -INFINITY;
        uint32_t p[AT_KT / 4];
#pragma unroll 1
        for (int st = 0; st < AT_NSTEP; st++) {
            wg_fence();
            wgmma_qk_n64(s, q, descK0 + (uint64_t)(st * AT_KT));
            wg_commit();
            wg_wait<0>();
            float x0 = m0, x1 = m1;
#pragma unroll
            for (int j = 0; j < AT_KT / 8; j++) {
                x0 = fmaxf(x0, fmaxf(s[4 * j], s[4 * j + 1]));
                x1 = fmaxf(x1, fmaxf(s[4 * j + 2], s[4 * j + 3]));
            }
            x0 = fmaxf(x0, __shfl_xor_sync(0xffffffffu, x0, 1)); x0 = fmaxf(x0, __shfl_xor_sync(0xffffffffu, x0, 2));
            x1 = fmaxf(x1, __shfl_xor_sync(0xffffffffu, x1, 1)); x1 = fmaxf(x1, __shfl_xor_sync(0xffffffffu, x1, 2));
            const float f0 = ex2(m0 - x0), f1 = ex2(m1 - x1);
            m0 = x0; m1 = x1;
#pragma unroll
            for (int j = 0; j < 3; j++) { o[4 * j] *= f0; o[4 * j + 1] *= f0; o[4 * j + 2] *= f1; o[4 * j + 3] *= f1; }
#pragma unroll
            for (int j = 0; j < AT_KT / 8; j++) {
                p[2 * j] = pack_bf16(ex2(s[4 * j] - m0), ex2(s[4 * j + 1] - m0));
                p[2 * j + 1] = pack_bf16(ex2(s[4 * j + 2] - m1), ex2(s[4 * j + 3] - m1));
            }
            wg_fence();
            AT_PV(p, descV0 + (uint64_t)(st * AT_KT));
            wg_commit();
            wg_wait<0>();
        }
        at_store(o, O, rowA + mt * 64, lane);
    }
}

#define K3_CN 4
constexpr int K3_STAGES = 8;
constexpr int K3_STAGE_BYTES = 16384 + 8192;
constexpr int K3_NKH = F_DIM / 64, K3_NKO = D_MODEL / 64, K3_NK = K3_NKH + K3_NKO;
constexpr int K3_SMEM = K3_STAGES * K3_STAGE_BYTES + 16384 + 256 + 1024;

__global__ void __launch_bounds__(288, 1)
k3_out(const __grid_constant__ CUtensorMap tm_h, const __grid_constant__ CUtensorMap tm_o,
       const __grid_constant__ CUtensorMap tm_w2, const __grid_constant__ CUtensorMap tm_wo,
       const __grid_constant__ CUtensorMap tm_x, const __grid_constant__ CUtensorMap tm_out,
       const __nv_bfloat16* __restrict__ b2) {
    extern __shared__ uint8_t smem_raw[];
    const uint32_t sbase = (smem_u32(smem_raw) + 1023) & ~1023u;
    const uint32_t sX = sbase + K3_STAGES * K3_STAGE_BYTES;
    const uint32_t bar_full = sX + 16384, bar_empty = bar_full + 8 * K3_STAGES, bar_x = bar_empty + 8 * K3_STAGES;
    const int tid = threadIdx.x, warp = tid >> 5, lane = tid & 31;
    const int rb = blockIdx.x >> 3, cb = blockIdx.x & 7;
    if (tid == 0) DEV_STAMP(2, 0);
    if (tid == 256) {
        for (int s = 0; s < K3_STAGES; s++) { mbar_init(bar_full + 8 * s, 1); mbar_init(bar_empty + 8 * s, 8 * K3_CN); }
        mbar_init(bar_x, 1);
        mbar_init_fence();
    }
    if (K3_CN > 1) cluster_sync_all(); else __syncthreads();
    const int crank = cb % K3_CN;
    constexpr int A_ROWS = 128 / K3_CN;
    constexpr uint16_t MC_MASK = (uint16_t)((1u << K3_CN) - 1);
    if (warp == 8) {
        if (lane == 0) {
            for (int ks = 0; ks < K3_NK; ks++) {
                const int s = ks % K3_STAGES;
                const uint32_t st = sbase + s * K3_STAGE_BYTES;
                if (ks == K3_NKH) pdl_wait();
                mbar_wait(bar_empty + 8 * s, ((ks / K3_STAGES) & 1) ^ 1);
                mbar_expect_tx(bar_full + 8 * s, K3_STAGE_BYTES);
                if (ks < K3_NKH) {
                    if (K3_CN > 1) tma_load_2d_mc(st + crank * A_ROWS * 128, &tm_h, ks * 64, rb * 128 + crank * A_ROWS, bar_full + 8 * s, MC_MASK);
                    else tma_load_2d(st, &tm_h, ks * 64, rb * 128, bar_full + 8 * s);
                    tma_load_2d(st + 16384, &tm_w2, cb * 64, ks * 64, bar_full + 8 * s);
                } else {
                    if (K3_CN > 1) tma_load_2d_mc(st + crank * A_ROWS * 128, &tm_o, (ks - K3_NKH) * 64, rb * 128 + crank * A_ROWS, bar_full + 8 * s, MC_MASK);
                    else tma_load_2d(st, &tm_o, (ks - K3_NKH) * 64, rb * 128, bar_full + 8 * s);
                    tma_load_2d(st + 16384, &tm_wo, cb * 64, (ks - K3_NKH) * 64, bar_full + 8 * s);
                }
                if (ks == K3_STAGES - 1) {
                    mbar_expect_tx(bar_x, 16384);
                    tma_load_2d(sX, &tm_x, cb * 64, rb * 128, bar_x);
                }
            }
        }
    } else {
        const int wg = warp >> 2;
#define K3_RELEASE(k) do { if ((k) < K3_NK - K3_STAGES) {                                                          \
            if (K3_CN > 1) { if (lane < K3_CN) mbar_arrive_remote(bar_empty + 8 * ((k) % K3_STAGES), lane); }       \
            else if (lane == 0) mbar_arrive(bar_empty + 8 * ((k) % K3_STAGES)); } } while (0)
        float accY[32], accS[32];
#pragma unroll
        for (int i = 0; i < 32; i++) { accY[i] = 0.f; accS[i] = 0.f; }
        const uint64_t dA0 = make_desc(sbase + wg * 8192, 16, 1024, 1);
        const uint64_t dB0 = make_desc(sbase + 16384, 8192, 1024, 1);
        for (int ks = 0; ks < K3_NKH; ks++) {
            const int s = ks % K3_STAGES;
            mbar_wait(bar_full + 8 * s, (ks / K3_STAGES) & 1);
            wg_fence();
#pragma unroll
            for (int kk = 0; kk < 4; kk++)
                wgmma_ss_n64_tb(accY, dA0 + (uint64_t)((s * K3_STAGE_BYTES + kk * 32) >> 4),
                                dB0 + (uint64_t)((s * K3_STAGE_BYTES + kk * 2048) >> 4), (ks | kk) != 0);
            wg_commit();
            if (ks > 0) {
                wg_wait<1>();
                K3_RELEASE(ks - 1);
            }
        }
        if (tid == 0) DEV_STAMP(2, 1);
        for (int ks = K3_NKH; ks < K3_NK; ks++) {
            const int s = ks % K3_STAGES;
            mbar_wait(bar_full + 8 * s, (ks / K3_STAGES) & 1);
            wg_fence();
#pragma unroll
            for (int kk = 0; kk < 4; kk++)
                wgmma_ss_n64_tb(accS, dA0 + (uint64_t)((s * K3_STAGE_BYTES + kk * 32) >> 4),
                                dB0 + (uint64_t)((s * K3_STAGE_BYTES + kk * 2048) >> 4), ((ks - K3_NKH) | kk) != 0);
            wg_commit();
            wg_wait<1>();
            K3_RELEASE(ks - 1);
        }
        wg_wait<0>();
        if (tid == 0) DEV_STAMP(2, 2);
        mbar_wait(bar_x, 0);
        const int g = lane >> 2, t = lane & 3;
        const int row0 = warp * 16 + g;
#pragma unroll
        for (int j = 0; j < 8; j++) {
            const uint32_t bb = __ldg(reinterpret_cast<const uint32_t*>(b2 + cb * 64 + j * 8 + 2 * t));
            const float b0 = bf_lo(bb), b1v = bf_hi(bb);
#pragma unroll
            for (int h = 0; h < 2; h++) {
                const int row = row0 + h * 8;
                const uint32_t a = sX + row * 128 + ((j ^ (row & 7)) << 4) + t * 4;
                uint32_t xv;
                asm volatile("ld.shared.b32 %0, [%1];" : "=r"(xv) : "r"(a) : "memory");
                const float z0 = accY[4 * j + 2 * h] + b0, z1 = accY[4 * j + 2 * h + 1] + b1v;
                const float g0 = __fdividef(z0, 1.0f + __expf(-z0)), g1 = __fdividef(z1, 1.0f + __expf(-z1));
                const uint32_t ov = pack_bf16(bf_lo(xv) + accS[4 * j + 2 * h] * g0, bf_hi(xv) + accS[4 * j + 2 * h + 1] * g1);
                asm volatile("st.shared.b32 [%0], %1;" ::"r"(a), "r"(ov) : "memory");
            }
        }
        fence_proxy_async();
        named_bar_sync(1 + wg, 128);
        if ((tid & 127) == 0) {
            tma_store_2d(&tm_out, sX + wg * 8192, cb * 64, rb * 128 + wg * 64);
            tma_store_commit();
            if (tid == 0) DEV_STAMP(2, 3);
            tma_store_wait();
            if (tid == 0) DEV_STAMP(2, 4);
        }
    }
    if (K3_CN > 1) { __syncwarp(); cluster_sync_all(); }
}

typedef CUresult (*EncodeFn)(CUtensorMap*, CUtensorMapDataType, cuuint32_t, void*, const cuuint64_t*, const cuuint64_t*,
                             const cuuint32_t*, const cuuint32_t*, CUtensorMapInterleave, CUtensorMapSwizzle,
                             CUtensorMapL2promotion, CUtensorMapFloatOOBfill);

struct HostState {
    bool ready;
    const void* key[11];
    CUtensorMap wq, wk, wv, w1, qo, ho, hi, oi, w2, wo, xi, out;
    void *pQ, *pKV, *pH, *pO, *pMax, *pRow, *pCol;
};
HostState g_hs;

void make_map(EncodeFn fn, CUtensorMap* m, const void* ptr, uint64_t inner, uint64_t outer, uint32_t box_in, uint32_t box_out) {
    cuuint64_t dims[2] = {inner, outer};
    cuuint64_t strides[1] = {inner * 2};
    cuuint32_t box[2] = {box_in, box_out};
    cuuint32_t es[2] = {1, 1};
    fn(m, CU_TENSOR_MAP_DATA_TYPE_BFLOAT16, 2, const_cast<void*>(ptr), dims, strides, box, es, CU_TENSOR_MAP_INTERLEAVE_NONE,
       CU_TENSOR_MAP_SWIZZLE_128B, CU_TENSOR_MAP_L2_PROMOTION_L2_256B, CU_TENSOR_MAP_FLOAT_OOB_FILL_NONE);
}

template <typename... KArgs, typename... Args>
void launch(void (*kern)(KArgs...), int grid, int block, int smem, bool pdl, int cluster, Args... args) {
    cudaLaunchConfig_t cfg = {};
    cfg.gridDim = dim3(grid); cfg.blockDim = dim3(block); cfg.dynamicSmemBytes = smem; cfg.stream = cudaStreamPerThread;
    cudaLaunchAttribute at[2];
    int n = 0;
    if (pdl) { at[n].id = cudaLaunchAttributeProgrammaticStreamSerialization; at[n].val.programmaticStreamSerializationAllowed = 1; n++; }
    if (cluster > 1) { at[n].id = cudaLaunchAttributeClusterDimension; at[n].val.clusterDim.x = cluster; at[n].val.clusterDim.y = 1; at[n].val.clusterDim.z = 1; n++; }
    cfg.attrs = at; cfg.numAttrs = n;
    cudaLaunchKernelEx(&cfg, kern, KArgs(args)...);
}

}

extern "C" void kernel_launch(void* const* d_in, const int* in_sizes, int n_in, void* d_out, int out_size) {
    (void)in_sizes; (void)n_in; (void)out_size;
    HostState& hs = g_hs;
    bool same = hs.ready;
    for (int i = 0; i < 10 && same; i++) same = hs.key[i] == d_in[i];
    same = same && hs.key[10] == d_out;
    if (!same) {
        void* fp = nullptr;
        cudaDriverEntryPointQueryResult qr;
        cudaGetDriverEntryPoint("cuTensorMapEncodeTiled", &fp, cudaEnableDefault, &qr);
        EncodeFn fn = (EncodeFn)fp;
        cudaGetSymbolAddress(&hs.pQ, g_Q); cudaGetSymbolAddress(&hs.pKV, g_KV); cudaGetSymbolAddress(&hs.pH, g_H);
        cudaGetSymbolAddress(&hs.pO, g_O); cudaGetSymbolAddress(&hs.pMax, g_kvmax);
        cudaGetSymbolAddress(&hs.pRow, g_rowstat); cudaGetSymbolAddress(&hs.pCol, g_colsum);
        make_map(fn, &hs.wq, d_in[1], 512, 512, 64, 64);
        make_map(fn, &hs.wk, d_in[2], 16, 512, 64, 64);
        make_map(fn, &hs.wv, d_in[3], 16, 512, 64, 64);
        make_map(fn, &hs.w1, d_in[6], F_DIM, 512, 64, 64);
        make_map(fn, &hs.qo, hs.pQ, 512, S_LEN, 64, 16);
        make_map(fn, &hs.ho, hs.pH, F_DIM, S_LEN, 64, 16);
        make_map(fn, &hs.hi, hs.pH, F_DIM, S_LEN, 64, 128 / K3_CN);
        make_map(fn, &hs.oi, hs.pO, 512, S_LEN, 64, 128 / K3_CN);
        make_map(fn, &hs.w2, d_in[8], 512, F_DIM, 64, 64);
        make_map(fn, &hs.wo, d_in[4], 512, 512, 64, 64);
        make_map(fn, &hs.xi, d_in[0], 512, S_LEN, 64, 128);
        make_map(fn, &hs.out, d_out, 512, S_LEN, 64, 64);
        cudaFuncSetAttribute(k1_proj, cudaFuncAttributeMaxDynamicSharedMemorySize, K1_SMEM);
        cudaFuncSetAttribute(k2_attn, cudaFuncAttributeMaxDynamicSharedMemorySize, AT_SMEM);
        cudaFuncSetAttribute(k3_out, cudaFuncAttributeMaxDynamicSharedMemorySize, K3_SMEM);
        for (int i = 0; i < 10; i++) hs.key[i] = d_in[i];
        hs.key[10] = d_out;
        hs.ready = true;
    }
    launch(k0_stats, K0_ROW_BLOCKS + 40, 256, 0, false, 1, (const __nv_bfloat16*)d_in[0], (const __nv_bfloat16*)d_in[1],
           (const __nv_bfloat16*)d_in[2], (const __nv_bfloat16*)d_in[3], (const __nv_bfloat16*)d_in[6], (float2*)hs.pRow, (float*)hs.pCol);
    launch(k1_proj, 128, 384, K1_SMEM, true, 1, hs.xi, hs.wq, hs.wk, hs.wv, hs.w1, hs.qo, hs.ho, (const __nv_bfloat16*)d_in[7],
           (const float2*)hs.pRow, (const float*)hs.pCol, (__nv_bfloat16*)hs.pKV, (float*)hs.pMax);
    launch(k2_attn, 128, 512, AT_SMEM, true, 1, (const __nv_bfloat16*)hs.pQ, (const __nv_bfloat16*)hs.pKV, (const float*)hs.pMax,
           (__nv_bfloat16*)hs.pO);
    launch(k3_out, 128, 288, K3_SMEM, true, K3_CN, hs.hi, hs.oi, hs.w2, hs.wo, hs.xi, hs.out, (const __nv_bfloat16*)d_in[9]);
}
```

```cpp
#include <cuda_runtime.h>
#include <cuda_bf16.h>
#include <cuda.h>
#include <stdint.h>

namespace {

constexpr int S_LEN = 2048, D_MODEL = 512, F_DIM = 1792;

__device__ __align__(1024) __nv_bfloat16 g_Q[S_LEN * D_MODEL];
__device__ __align__(1024) __nv_bfloat16 g_KV[6 * S_LEN * 8];
__device__ __align__(1024) __nv_bfloat16 g_H[S_LEN * F_DIM];
__device__ __align__(1024) __nv_bfloat16 g_O[S_LEN * D_MODEL];
__device__ __align__(1024) float g_kvmax[256];
__device__ __align__(1024) float2 g_rowstat[S_LEN];
__device__ __align__(1024) float g_colpart[8 * 16 * 320];
__device__ __align__(1024) int g_flags[128];

#define DEV_STAMP(k, e) do {} while (0)
__device__ __forceinline__ uint32_t smem_u32(const void* p) { return (uint32_t)__cvta_generic_to_shared(p); }
__device__ __forceinline__ void wg_fence() { asm volatile("wgmma.fence.sync.aligned;" ::: "memory"); }
__device__ __forceinline__ void wg_commit() { asm volatile("wgmma.commit_group.sync.aligned;" ::: "memory"); }
template <int N> __device__ __forceinline__ void wg_wait() { asm volatile("wgmma.wait_group.sync.aligned %0;" ::"n"(N) : "memory"); }
__device__ __forceinline__ void fence_proxy_async() { asm volatile("fence.proxy.async.shared::cta;" ::: "memory"); }
__device__ __forceinline__ void mbar_init(uint32_t bar, int cnt) { asm volatile("mbarrier.init.shared::cta.b64 [%0], %1;" ::"r"(bar), "r"(cnt) : "memory"); }
__device__ __forceinline__ void mbar_init_fence() { asm volatile("fence.mbarrier_init.release.cluster;" ::: "memory"); }
__device__ __forceinline__ void mbar_expect_tx(uint32_t bar, uint32_t bytes) {
    asm volatile("mbarrier.arrive.expect_tx.shared::cta.b64 _, [%0], %1;" ::"r"(bar), "r"(bytes) : "memory");
}
__device__ __forceinline__ void mbar_arrive(uint32_t bar) { asm volatile("mbarrier.arrive.shared::cta.b64 _, [%0];" ::"r"(bar) : "memory"); }
__device__ __forceinline__ bool mbar_try(uint32_t bar, uint32_t parity) {
    uint32_t ok;
    asm volatile("{\n.reg .pred p;\nmbarrier.try_wait.parity.shared::cta.b64 p, [%1], %2;\nselp.u32 %0, 1, 0, p;\n}\n"
                 : "=r"(ok) : "r"(bar), "r"(parity) : "memory");
    return ok != 0;
}
__device__ __forceinline__ void mbar_wait(uint32_t bar, uint32_t parity) {
    if (mbar_try(bar, parity)) return;
    uint32_t n = 0;
#pragma unroll 1
    while (!mbar_try(bar, parity)) {
        if (++n > (1u << 24)) __trap();
    }
}
__device__ __forceinline__ void bulk_g2s(uint32_t dst, const void* src, uint32_t bytes, uint32_t bar) {
    asm volatile("cp.async.bulk.shared::cluster.global.mbarrier::complete_tx::bytes [%0], [%1], %2, [%3];"
                 ::"r"(dst), "l"(src), "r"(bytes), "r"(bar) : "memory");
}
__device__ __forceinline__ void tma_load_2d(uint32_t dst, const CUtensorMap* tm, int c0, int c1, uint32_t bar) {
    asm volatile("cp.async.bulk.tensor.2d.shared::cluster.global.mbarrier::complete_tx::bytes [%0], [%1, {%3, %4}], [%2];"
                 ::"r"(dst), "l"((uint64_t)tm), "r"(bar), "r"(c0), "r"(c1) : "memory");
}
__device__ __forceinline__ void tma_load_2d_mc(uint32_t dst, const CUtensorMap* tm, int c0, int c1, uint32_t bar, uint16_t mask) {
    asm volatile("cp.async.bulk.tensor.2d.shared::cluster.global.mbarrier::complete_tx::bytes.multicast::cluster [%0], [%1, {%3, %4}], [%2], %5;"
                 ::"r"(dst), "l"((uint64_t)tm), "r"(bar), "r"(c0), "r"(c1), "h"(mask) : "memory");
}
__device__ __forceinline__ void mbar_arrive_remote(uint32_t bar, uint32_t cta) {
    asm volatile("{\n.reg .b32 ra;\nmapa.shared::cluster.u32 ra, %0, %1;\nmbarrier.arrive.shared::cluster.b64 _, [ra];\n}\n"
                 ::"r"(bar), "r"(cta) : "memory");
}
__device__ __forceinline__ void cluster_sync_all() {
    asm volatile("barrier.cluster.arrive.release;\nbarrier.cluster.wait.acquire;" ::: "memory");
}
__device__ __forceinline__ void tma_store_2d(const CUtensorMap* tm, uint32_t src, int c0, int c1) {
    asm volatile("cp.async.bulk.tensor.2d.global.shared::cta.bulk_group [%0, {%2, %3}], [%1];"
                 ::"l"((uint64_t)tm), "r"(src), "r"(c0), "r"(c1) : "memory");
}
__device__ __forceinline__ void tma_store_commit() { asm volatile("cp.async.bulk.commit_group;" ::: "memory"); }
__device__ __forceinline__ void tma_store_wait() { asm volatile("cp.async.bulk.wait_group 0;" ::: "memory"); }
__device__ __forceinline__ void tma_prefetch_desc(const CUtensorMap* tm) { asm volatile("prefetch.tensormap [%0];" ::"l"((uint64_t)tm) : "memory"); }
__device__ __forceinline__ void named_bar_sync(int id, int n) { asm volatile("bar.sync %0, %1;" ::"r"(id), "r"(n) : "memory"); }
__device__ __forceinline__ void pdl_wait() { asm volatile("griddepcontrol.wait;" ::: "memory"); }
__device__ __forceinline__ void pdl_launch() { asm volatile("griddepcontrol.launch_dependents;" ::: "memory"); }
template <int N> __device__ __forceinline__ void reg_alloc() { asm volatile("setmaxnreg.inc.sync.aligned.u32 %0;" ::"n"(N)); }
template <int N> __device__ __forceinline__ void reg_dealloc() { asm volatile("setmaxnreg.dec.sync.aligned.u32 %0;" ::"n"(N)); }
__device__ __forceinline__ float ex2(float x) { float y; asm("ex2.approx.ftz.f32 %0, %1;" : "=f"(y) : "f"(x)); return y; }
__device__ __forceinline__ uint32_t pack_bf16(float lo, float hi) {
    uint32_t r; asm("cvt.rn.bf16x2.f32 %0, %1, %2;" : "=r"(r) : "f"(hi), "f"(lo)); return r;
}
__device__ __forceinline__ uint32_t pack_bf16_relu(float lo, float hi) {
    uint32_t r; asm("cvt.rn.relu.bf16x2.f32 %0, %1, %2;" : "=r"(r) : "f"(hi), "f"(lo)); return r;
}
__device__ __forceinline__ uint32_t mul_bf16x2(uint32_t a, uint32_t b) {
    uint32_t r; asm("mul.rn.bf16x2 %0, %1, %2;" : "=r"(r) : "r"(a), "r"(b)); return r;
}
__device__ __forceinline__ float bf_lo(uint32_t v) { return __uint_as_float(v << 16); }
__device__ __forceinline__ float bf_hi(uint32_t v) { return __uint_as_float(v & 0xFFFF0000u); }
__device__ __forceinline__ void stmatrix_x4(uint32_t addr, uint32_t r0, uint32_t r1, uint32_t r2, uint32_t r3) {
    asm volatile("stmatrix.sync.aligned.m8n8.x4.shared.b16 [%0], {%1,%2,%3,%4};" ::"r"(addr), "r"(r0), "r"(r1), "r"(r2), "r"(r3) : "memory");
}
__device__ __forceinline__ uint64_t make_desc(uint32_t addr, uint32_t lbo, uint32_t sbo, uint32_t swz) {
    return (uint64_t)((addr & 0x3FFFF) >> 4) | ((uint64_t)(lbo >> 4) << 16) | ((uint64_t)(sbo >> 4) << 32) | ((uint64_t)swz << 62);
}

__device__ __forceinline__ void wgmma_ss_n256_tb(float* d, uint64_t descA, uint64_t descB, int scaleD) {
    asm volatile("{\n.reg .pred p;\nsetp.ne.b32 p, %130, 0;\n"
      "wgmma.mma_async.sync.aligned.m64n256k16.f32.bf16.bf16 {%0,%1,%2,%3,%4,%5,%6,%7,%8,%9,%10,%11,%12,%13,%14,%15,%16,%17,%18,%19,%20,%21,%22,%23,%24,%25,%26,%27,%28,%29,%30,%31,%32,%33,%34,%35,%36,%37,%38,%39,%40,%41,%42,%43,%44,%45,%46,%47,%48,%49,%50,%51,%52,%53,%54,%55,%56,%57,%58,%59,%60,%61,%62,%63,%64,%65,%66,%67,%68,%69,%70,%71,%72,%73,%74,%75,%76,%77,%78,%79,%80,%81,%82,%83,%84,%85,%86,%87,%88,%89,%90,%91,%92,%93,%94,%95,%96,%97,%98,%99,%100,%101,%102,%103,%104,%105,%106,%107,%108,%109,%110,%111,%112,%113,%114,%115,%116,%117,%118,%119,%120,%121,%122,%123,%124,%125,%126,%127}, %128, %129, p, 1, 1, 0, 1;\n}\n"
      : "+f"(d[0]), "+f"(d[1]), "+f"(d[2]), "+f"(d[3]), "+f"(d[4]), "+f"(d[5]), "+f"(d[6]), "+f"(d[7]), "+f"(d[8]), "+f"(d[9]), "+f"(d[10]), "+f"(d[11]), "+f"(d[12]), "+f"(d[13]), "+f"(d[14]), "+f"(d[15]), "+f"(d[16]), "+f"(d[17]), "+f"(d[18]), "+f"(d[19]), "+f"(d[20]), "+f"(d[21]), "+f"(d[22]), "+f"(d[23]), "+f"(d[24]), "+f"(d[25]), "+f"(d[26]), "+f"(d[27]), "+f"(d[28]), "+f"(d[29]), "+f"(d[30]), "+f"(d[31]), "+f"(d[32]), "+f"(d[33]), "+f"(d[34]), "+f"(d[35]), "+f"(d[36]), "+f"(d[37]), "+f"(d[38]), "+f"(d[39]), "+f"(d[40]), "+f"(d[41]), "+f"(d[42]), "+f"(d[43]), "+f"(d[44]), "+f"(d[45]), "+f"(d[46]), "+f"(d[47]), "+f"(d[48]), "+f"(d[49]), "+f"(d[50]), "+f"(d[51]), "+f"(d[52]), "+f"(d[53]), "+f"(d[54]), "+f"(d[55]), "+f"(d[56]), "+f"(d[57]), "+f"(d[58]), "+f"(d[59]), "+f"(d[60]), "+f"(d[61]), "+f"(d[62]), "+f"(d[63]), "+f"(d[64]), "+f"(d[65]), "+f"(d[66]), "+f"(d[67]), "+f"(d[68]), "+f"(d[69]), "+f"(d[70]), "+f"(d[71]), "+f"(d[72]), "+f"(d[73]), "+f"(d[74]), "+f"(d[75]), "+f"(d[76]), "+f"(d[77]), "+f"(d[78]), "+f"(d[79]), "+f"(d[80]), "+f"(d[81]), "+f"(d[82]), "+f"(d[83]), "+f"(d[84]), "+f"(d[85]), "+f"(d[86]), "+f"(d[87]), "+f"(d[88]), "+f"(d[89]), "+f"(d[90]), "+f"(d[91]), "+f"(d[92]), "+f"(d[93]), "+f"(d[94]), "+f"(d[95]), "+f"(d[96]), "+f"(d[97]), "+f"(d[98]), "+f"(d[99]), "+f"(d[100]), "+f"(d[101]), "+f"(d[102]), "+f"(d[103]), "+f"(d[104]), "+f"(d[105]), "+f"(d[106]), "+f"(d[107]), "+f"(d[108]), "+f"(d[109]), "+f"(d[110]), "+f"(d[111]), "+f"(d[112]), "+f"(d[113]), "+f"(d[114]), "+f"(d[115]), "+f"(d[116]), "+f"(d[117]), "+f"(d[118]), "+f"(d[119]), "+f"(d[120]), "+f"(d[121]), "+f"(d[122]), "+f"(d[123]), "+f"(d[124]), "+f"(d[125]), "+f"(d[126]), "+f"(d[127])
      : "l"(descA), "l"(descB), "r"(scaleD));
}
__device__ __forceinline__ void wgmma_ss_n128_tb(float* d, uint64_t descA, uint64_t descB, int scaleD) {
    asm volatile("{\n.reg .pred p;\nsetp.ne.b32 p, %66, 0;\n"
      "wgmma.mma_async.sync.aligned.m64n128k16.f32.bf16.bf16 {%0,%1,%2,%3,%4,%5,%6,%7,%8,%9,%10,%11,%12,%13,%14,%15,%16,%17,%18,%19,%20,%21,%22,%23,%24,%25,%26,%27,%28,%29,%30,%31,%32,%33,%34,%35,%36,%37,%38,%39,%40,%41,%42,%43,%44,%45,%46,%47,%48,%49,%50,%51,%52,%53,%54,%55,%56,%57,%58,%59,%60,%61,%62,%63}, %64, %65, p, 1, 1, 0, 1;\n}\n"
      : "+f"(d[0]), "+f"(d[1]), "+f"(d[2]), "+f"(d[3]), "+f"(d[4]), "+f"(d[5]), "+f"(d[6]), "+f"(d[7]), "+f"(d[8]), "+f"(d[9]), "+f"(d[10]), "+f"(d[11]), "+f"(d[12]), "+f"(d[13]), "+f"(d[14]), "+f"(d[15]), "+f"(d[16]), "+f"(d[17]), "+f"(d[18]), "+f"(d[19]), "+f"(d[20]), "+f"(d[21]), "+f"(d[22]), "+f"(d[23]), "+f"(d[24]), "+f"(d[25]), "+f"(d[26]), "+f"(d[27]), "+f"(d[28]), "+f"(d[29]), "+f"(d[30]), "+f"(d[31]), "+f"(d[32]), "+f"(d[33]), "+f"(d[34]), "+f"(d[35]), "+f"(d[36]), "+f"(d[37]), "+f"(d[38]), "+f"(d[39]), "+f"(d[40]), "+f"(d[41]), "+f"(d[42]), "+f"(d[43]), "+f"(d[44]), "+f"(d[45]), "+f"(d[46]), "+f"(d[47]), "+f"(d[48]), "+f"(d[49]), "+f"(d[50]), "+f"(d[51]), "+f"(d[52]), "+f"(d[53]), "+f"(d[54]), "+f"(d[55]), "+f"(d[56]), "+f"(d[57]), "+f"(d[58]), "+f"(d[59]), "+f"(d[60]), "+f"(d[61]), "+f"(d[62]), "+f"(d[63])
      : "l"(descA), "l"(descB), "r"(scaleD));
}
__device__ __forceinline__ void wgmma_ss_n64_tb(float* d, uint64_t descA, uint64_t descB, int scaleD) {
    asm volatile("{\n.reg .pred p;\nsetp.ne.b32 p, %34, 0;\n"
      "wgmma.mma_async.sync.aligned.m64n64k16.f32.bf16.bf16 {%0,%1,%2,%3,%4,%5,%6,%7,%8,%9,%10,%11,%12,%13,%14,%15,%16,%17,%18,%19,%20,%21,%22,%23,%24,%25,%26,%27,%28,%29,%30,%31}, %32, %33, p, 1, 1, 0, 1;\n}\n"
      : "+f"(d[0]), "+f"(d[1]), "+f"(d[2]), "+f"(d[3]), "+f"(d[4]), "+f"(d[5]), "+f"(d[6]), "+f"(d[7]), "+f"(d[8]), "+f"(d[9]), "+f"(d[10]), "+f"(d[11]), "+f"(d[12]), "+f"(d[13]), "+f"(d[14]), "+f"(d[15]), "+f"(d[16]), "+f"(d[17]), "+f"(d[18]), "+f"(d[19]), "+f"(d[20]), "+f"(d[21]), "+f"(d[22]), "+f"(d[23]), "+f"(d[24]), "+f"(d[25]), "+f"(d[26]), "+f"(d[27]), "+f"(d[28]), "+f"(d[29]), "+f"(d[30]), "+f"(d[31])
      : "l"(descA), "l"(descB), "r"(scaleD));
}
__device__ __forceinline__ void wgmma_qk_n64(float* d, const uint32_t* a, uint64_t descB) {
    asm volatile("wgmma.mma_async.sync.aligned.m64n64k16.f32.bf16.bf16 {%0,%1,%2,%3,%4,%5,%6,%7,%8,%9,%10,%11,%12,%13,%14,%15,%16,%17,%18,%19,%20,%21,%22,%23,%24,%25,%26,%27,%28,%29,%30,%31}, {%32,%33,%34,%35}, %36, 0, 1, 1, 0;\n"
      : "=f"(d[0]), "=f"(d[1]), "=f"(d[2]), "=f"(d[3]), "=f"(d[4]), "=f"(d[5]), "=f"(d[6]), "=f"(d[7]), "=f"(d[8]), "=f"(d[9]), "=f"(d[10]), "=f"(d[11]), "=f"(d[12]), "=f"(d[13]), "=f"(d[14]), "=f"(d[15]), "=f"(d[16]), "=f"(d[17]), "=f"(d[18]), "=f"(d[19]), "=f"(d[20]), "=f"(d[21]), "=f"(d[22]), "=f"(d[23]), "=f"(d[24]), "=f"(d[25]), "=f"(d[26]), "=f"(d[27]), "=f"(d[28]), "=f"(d[29]), "=f"(d[30]), "=f"(d[31])
      : "r"(a[0]), "r"(a[1]), "r"(a[2]), "r"(a[3]), "l"(descB));
}
__device__ __forceinline__ void wgmma_qk_acc_n64(float* d, const uint32_t* a, uint64_t descB) {
    asm volatile("wgmma.mma_async.sync.aligned.m64n64k16.f32.bf16.bf16 {%0,%1,%2,%3,%4,%5,%6,%7,%8,%9,%10,%11,%12,%13,%14,%15,%16,%17,%18,%19,%20,%21,%22,%23,%24,%25,%26,%27,%28,%29,%30,%31}, {%32,%33,%34,%35}, %36, 1, 1, 1, 0;\n"
      : "+f"(d[0]), "+f"(d[1]), "+f"(d[2]), "+f"(d[3]), "+f"(d[4]), "+f"(d[5]), "+f"(d[6]), "+f"(d[7]), "+f"(d[8]), "+f"(d[9]), "+f"(d[10]), "+f"(d[11]), "+f"(d[12]), "+f"(d[13]), "+f"(d[14]), "+f"(d[15]), "+f"(d[16]), "+f"(d[17]), "+f"(d[18]), "+f"(d[19]), "+f"(d[20]), "+f"(d[21]), "+f"(d[22]), "+f"(d[23]), "+f"(d[24]), "+f"(d[25]), "+f"(d[26]), "+f"(d[27]), "+f"(d[28]), "+f"(d[29]), "+f"(d[30]), "+f"(d[31])
      : "r"(a[0]), "r"(a[1]), "r"(a[2]), "r"(a[3]), "l"(descB));
}

__device__ __forceinline__ void wgmma_pv(float* d, uint32_t a0, uint32_t a1, uint32_t a2, uint32_t a3, uint64_t descB) {
    asm volatile("wgmma.mma_async.sync.aligned.m64n24k16.f32.bf16.bf16 {%0,%1,%2,%3,%4,%5,%6,%7,%8,%9,%10,%11}, {%12,%13,%14,%15}, %16, 1, 1, 1, 1;\n"
                 : "+f"(d[0]), "+f"(d[1]), "+f"(d[2]), "+f"(d[3]), "+f"(d[4]), "+f"(d[5]), "+f"(d[6]), "+f"(d[7]), "+f"(d[8]), "+f"(d[9]), "+f"(d[10]), "+f"(d[11])
                 : "r"(a0), "r"(a1), "r"(a2), "r"(a3), "l"(descB));
}

__device__ __forceinline__ void k1_panel(int g, int i, int& type, int& col) {
    if (g < 6) {
        int p = g * 5 + i;
        if (p < 8) { type = 0; col = p * 64; } else { type = 1; col = (p - 8) * 64; }
    } else {
        if (i < 3) { type = 1; col = (22 + (g - 6) * 3 + i) * 64; } else { type = 2 + (g - 6); col = 0; }
    }
}

constexpr int K1_STAGES = 4;
constexpr int K1_PANEL_BYTES = 64 * 128;
constexpr int K1_STAGE_BYTES = 16384 + 5 * K1_PANEL_BYTES;
constexpr int K1_SMEM = K1_STAGES * K1_STAGE_BYTES + 128 + 320 * 8;
constexpr float Q_SCALE = 0.25f * 1.4426950408889634f;

__global__ void __launch_bounds__(384, 1)
k1_proj(const __grid_constant__ CUtensorMap tm_x, const __grid_constant__ CUtensorMap tm_wq,
        const __grid_constant__ CUtensorMap tm_wk, const __grid_constant__ CUtensorMap tm_wv,
        const __grid_constant__ CUtensorMap tm_w1, const __grid_constant__ CUtensorMap tm_qo,
        const __grid_constant__ CUtensorMap tm_ho, const __nv_bfloat16* __restrict__ x,
        const __nv_bfloat16* __restrict__ wq, const __nv_bfloat16* __restrict__ wk, const __nv_bfloat16* __restrict__ wv,
        const __nv_bfloat16* __restrict__ w1, const __nv_bfloat16* __restrict__ b1,
        float2* rowstat, float* colpart, int* flags,
        __nv_bfloat16* __restrict__ kv, float* __restrict__ kvmax) {
    extern __shared__ __align__(1024) uint8_t smem_raw[];
    const uint32_t sbase = smem_u32(smem_raw);
    const uint32_t bar_full = sbase + K1_STAGES * K1_STAGE_BYTES, bar_empty = bar_full + 8 * K1_STAGES, bar_col = bar_empty + 8 * K1_STAGES;
    const uint32_t sCol = bar_full + 128;
    const int tid = threadIdx.x, warp = tid >> 5, lane = tid & 31;
    const int rb = blockIdx.x >> 3, grp = blockIdx.x & 7;
    const int npanels = grp < 6 ? 5 : 4;
    if (tid == 0) DEV_STAMP(0, 0);

    if (tid == 256) {
        for (int s = 0; s < K1_STAGES; s++) { mbar_init(bar_full + 8 * s, 1); mbar_init(bar_empty + 8 * s, 8); }
        mbar_init(bar_col, 96);
        mbar_init_fence();
    }
    __syncthreads();
    pdl_launch();

    if (warp >= 8) {
        reg_dealloc<88>();
        if (warp == 8) {
            if (lane == 0) {
                const CUtensorMap* tms[5]; int cols[5];
#pragma unroll
                for (int i = 0; i < 5; i++) {
                    int type, col; k1_panel(grp, i, type, col);
                    tms[i] = type == 0 ? &tm_wq : type == 1 ? &tm_w1 : type == 2 ? &tm_wk : &tm_wv;
                    cols[i] = col;
                }
                for (int ks = 0; ks < 8; ks++) {
                    const int s = ks % K1_STAGES;
                    const uint32_t st = sbase + s * K1_STAGE_BYTES;
                    mbar_wait(bar_empty + 8 * s, ((ks / K1_STAGES) & 1) ^ 1);
                    mbar_expect_tx(bar_full + 8 * s, 16384 + npanels * K1_PANEL_BYTES);
                    tma_load_2d(st, &tm_x, ks * 64, rb * 128, bar_full + 8 * s);
#pragma unroll
                    for (int i = 0; i < 5; i++)
                        if (i < npanels) tma_load_2d(st + 16384 + i * K1_PANEL_BYTES, tms[i], cols[i], ks * 64, bar_full + 8 * s);
                }
            }
        } else {
            const int ht = tid - 288;
            if (warp == 9) {
                const int row0 = rb * 128 + grp * 16;
                const uint4* xp = reinterpret_cast<const uint4*>(x + (size_t)row0 * D_MODEL);
#pragma unroll 1
                for (int r4 = 0; r4 < 16; r4 += 4) {
                    uint4 v[4][2];
#pragma unroll
                    for (int r = 0; r < 4; r++) { v[r][0] = __ldg(xp + (r4 + r) * 64 + lane); v[r][1] = __ldg(xp + (r4 + r) * 64 + 32 + lane); }
#pragma unroll
                    for (int r = 0; r < 4; r++) {
                        float f[16];
                        const uint32_t w[8] = {v[r][0].x, v[r][0].y, v[r][0].z, v[r][0].w, v[r][1].x, v[r][1].y, v[r][1].z, v[r][1].w};
#pragma unroll
                        for (int i = 0; i < 8; i++) { f[2 * i] = bf_lo(w[i]); f[2 * i + 1] = bf_hi(w[i]); }
                        float sum = 0.f;
#pragma unroll
                        for (int i = 0; i < 16; i++) sum += f[i];
#pragma unroll
                        for (int o = 16; o > 0; o >>= 1) sum += __shfl_xor_sync(0xffffffffu, sum, o);
                        const float mean = sum * (1.0f / D_MODEL);
                        float sq = 0.f;
#pragma unroll
                        for (int i = 0; i < 16; i++) { const float d = f[i] - mean; sq += d * d; }
#pragma unroll
                        for (int o = 16; o > 0; o >>= 1) sq += __shfl_xor_sync(0xffffffffu, sq, o);
                        const float rstd = rsqrtf(sq * (1.0f / D_MODEL) + 1e-5f);
                        if (lane == 0) rowstat[row0 + r4 + r] = make_float2(rstd, mean * rstd);
                    }
                }
            } else {
                const int cg = ht - 32;
                if (cg < npanels * 8) {
                    int type, col; k1_panel(grp, cg >> 3, type, col);
                    const __nv_bfloat16* w = type == 0 ? wq : type == 1 ? w1 : type == 2 ? wk : wv;
                    const int ld = type == 0 ? D_MODEL : type == 1 ? F_DIM : 16;
                    float sacc[8];
#pragma unroll
                    for (int c = 0; c < 8; c++) sacc[c] = 0.f;
                    if (type <= 1 || (cg & 7) < 2) {
                        const __nv_bfloat16* wp = w + (size_t)(rb * 32) * ld + col + (cg & 7) * 8;
#pragma unroll 1
                        for (int h = 0; h < 4; h++) {
                            uint4 u[8];
#pragma unroll
                            for (int k = 0; k < 8; k++) u[k] = __ldg(reinterpret_cast<const uint4*>(wp + (size_t)(h * 8 + k) * ld));
#pragma unroll
                            for (int k = 0; k < 8; k++) {
                                sacc[0] += bf_lo(u[k].x); sacc[1] += bf_hi(u[k].x); sacc[2] += bf_lo(u[k].y); sacc[3] += bf_hi(u[k].y);
                                sacc[4] += bf_lo(u[k].z); sacc[5] += bf_hi(u[k].z); sacc[6] += bf_lo(u[k].w); sacc[7] += bf_hi(u[k].w);
                            }
                        }
                    }
                    float4* dst = reinterpret_cast<float4*>(colpart + (grp * 16 + rb) * 320 + cg * 8);
                    dst[0] = make_float4(sacc[0], sacc[1], sacc[2], sacc[3]);
                    dst[1] = make_float4(sacc[4], sacc[5], sacc[6], sacc[7]);
                }
            }
            __threadfence();
            named_bar_sync(4, 96);
            if (ht == 0) asm volatile("st.release.gpu.global.s32 [%0], %1;" ::"l"(flags + blockIdx.x), "r"(1) : "memory");
            if (ht < 24) {
                const int* f = flags + (ht < 8 ? rb * 8 + ht : (ht - 8) * 8 + grp);
                int v = 0;
#pragma unroll 1
                for (uint32_t n = 0; n < (1u << 22) && v == 0; n++)
                    asm volatile("ld.acquire.gpu.global.s32 %0, [%1];" : "=r"(v) : "l"(f) : "memory");
            }
            named_bar_sync(4, 96);
            for (int c2 = ht; c2 < npanels * 32; c2 += 96) {
                int type, col; k1_panel(grp, c2 >> 5, type, col);
                float s0 = 0.f, s1 = 0.f;
#pragma unroll
                for (int k = 0; k < 16; k++) {
                    const float2 v = __ldcg(reinterpret_cast<const float2*>(colpart + (grp * 16 + k) * 320) + c2);
                    s0 += v.x; s1 += v.y;
                }
                uint32_t bb = 0;
                if (type == 1) bb = __ldg(reinterpret_cast<const uint32_t*>(b1 + col) + (c2 & 31));
                asm volatile("st.shared.v4.f32 [%0], {%1,%2,%3,%4};" ::"r"(sCol + c2 * 16), "f"(s0), "f"(bf_lo(bb)), "f"(s1), "f"(bf_hi(bb)) : "memory");
            }
            mbar_arrive(bar_col);
        }
    } else {
        reg_alloc<208>();
        const int wg = warp >> 2;
        const int g = lane >> 2, t = lane & 3;
        const int wrow = (warp & 3) * 16;
        float acc[160];
#pragma unroll
        for (int i = 0; i < 160; i++) acc[i] = 0.f;
        float2 rs0, rs1;
        const uint64_t dA0 = make_desc(sbase + wg * 8192, 16, 1024, 1);
        const uint64_t dB0 = make_desc(sbase + 16384, K1_PANEL_BYTES, 1024, 1);
#define K1_MAINLOOP(FIVE)                                                                                          \
        for (int ks = 0; ks < 8; ks++) {                                                                           \
            const int s = ks % K1_STAGES;                                                                          \
            mbar_wait(bar_full + 8 * s, (ks / K1_STAGES) & 1);                                                     \
            if (ks == 0 && tid == 0) DEV_STAMP(0, 1);                                                              \
            wg_fence();                                                                                            \
            _Pragma("unroll") for (int kk = 0; kk < 4; kk++) {                                                     \
                const uint64_t dA = dA0 + (uint64_t)((s * K1_STAGE_BYTES + kk * 32) >> 4);                         \
                const uint64_t dB = dB0 + (uint64_t)((s * K1_STAGE_BYTES + kk * 2048) >> 4);                       \
                wgmma_ss_n256_tb(acc, dA, dB, (ks | kk) != 0);                                                     \
                if (FIVE) wgmma_ss_n64_tb(acc + 128, dA, dB + (uint64_t)((4 * K1_PANEL_BYTES) >> 4), (ks | kk) != 0); \
            }                                                                                                      \
            wg_commit();                                                                                           \
            if (ks == 7) {                                                                                         \
                mbar_wait(bar_col, 0);                                                                             \
                rs0 = __ldcg(rowstat + rb * 128 + wg * 64 + wrow + g);                                             \
                rs1 = __ldcg(rowstat + rb * 128 + wg * 64 + wrow + g + 8);                                         \
            }                                                                                                      \
            if (ks > 0 && ks <= 4) {                                                                               \
                wg_wait<1>();                                                                                      \
                if (lane == 0) mbar_arrive(bar_empty + 8 * ((ks - 1) % K1_STAGES));                                \
            }                                                                                                      \
        }                                                                                                          \
        wg_wait<0>();
        if (npanels == 5) { K1_MAINLOOP(true) } else { K1_MAINLOOP(false) }
        if (tid == 0) DEV_STAMP(0, 2);
        named_bar_sync(1, 256);
        const int srow = (lane & 7) + ((lane >> 3) & 1) * 8;
#pragma unroll
        for (int p = 0; p < 5; p++) {
            if (p < npanels) {
                int type, col; k1_panel(grp, p, type, col);
                float* a = acc + p * 32;
                const int nj = type <= 1 ? 8 : 2;
                const float sc = type == 0 ? Q_SCALE : 1.0f;
                const float r0x = rs0.x * sc, r0y = -rs0.y * sc, r1x = rs1.x * sc, r1y = -rs1.y * sc;
#pragma unroll
                for (int j = 0; j < 8; j++) {
                    if (j < nj) {
                        float4 c;
                        asm volatile("ld.shared.v4.f32 {%0,%1,%2,%3}, [%4];" : "=f"(c.x), "=f"(c.y), "=f"(c.z), "=f"(c.w)
                                     : "r"(sCol + (p * 64 + j * 8 + 2 * t) * 8));
                        a[4 * j] = fmaf(a[4 * j], r0x, fmaf(r0y, c.x, c.y));
                        a[4 * j + 1] = fmaf(a[4 * j + 1], r0x, fmaf(r0y, c.z, c.w));
                        a[4 * j + 2] = fmaf(a[4 * j + 2], r1x, fmaf(r1y, c.x, c.y));
                        a[4 * j + 3] = fmaf(a[4 * j + 3], r1x, fmaf(r1y, c.z, c.w));
                    }
                }
                if (type <= 1) {
                    const uint32_t stg = sbase + (p * 8 + warp) * 2048;
                    uint32_t pk[16];
                    if (type == 0) {
#pragma unroll
                        for (int j = 0; j < 8; j++) {
                            pk[2 * j] = pack_bf16(a[4 * j], a[4 * j + 1]);
                            pk[2 * j + 1] = pack_bf16(a[4 * j + 2], a[4 * j + 3]);
                        }
                    } else {
#pragma unroll
                        for (int j = 0; j < 8; j++) {
                            const uint32_t h0 = pack_bf16_relu(a[4 * j], a[4 * j + 1]), h1 = pack_bf16_relu(a[4 * j + 2], a[4 * j + 3]);
                            pk[2 * j] = mul_bf16x2(h0, h0);
                            pk[2 * j + 1] = mul_bf16x2(h1, h1);
                        }
                    }
#pragma unroll
                    for (int j = 0; j < 8; j += 2) {
                        const int c16 = j + (lane >> 4);
                        stmatrix_x4(stg + srow * 128 + ((c16 ^ (srow & 7)) << 4), pk[2 * j], pk[2 * j + 1], pk[2 * j + 2], pk[2 * j + 3]);
                    }
                    fence_proxy_async();
                    __syncwarp();
                    if (lane == 0) {
                        tma_store_2d(type == 0 ? &tm_qo : &tm_ho, stg, col, rb * 128 + warp * 16);
                        tma_store_commit();
                    }
                } else if (type == 3) {
                    const int r = wg * 64 + wrow + g;
                    const int pos0 = (r >> 2) * 64 + rb * 4 + (r & 3), pos1 = pos0 + 128;
                    uint32_t* dst = reinterpret_cast<uint32_t*>(kv + 2 * (S_LEN * 8));
                    const uint32_t r00 = pack_bf16(a[0], a[1]), r01 = pack_bf16(a[4], a[5]);
                    const uint32_t r10 = pack_bf16(a[2], a[3]), r11 = pack_bf16(a[6], a[7]);
                    dst[pos0 * 4 + t] = r00;
                    dst[S_LEN * 4 + pos0 * 4 + t] = r01;
                    dst[pos1 * 4 + t] = r10;
                    dst[S_LEN * 4 + pos1 * 4 + t] = r11;
                    float m = fmaxf(fmaxf(fmaxf(fabsf(bf_lo(r00)), fabsf(bf_hi(r00))), fmaxf(fabsf(bf_lo(r01)), fabsf(bf_hi(r01)))),
                                    fmaxf(fmaxf(fabsf(bf_lo(r10)), fabsf(bf_hi(r10))), fmaxf(fabsf(bf_lo(r11)), fabsf(bf_hi(r11)))));
#pragma unroll
                    for (int o = 16; o > 0; o >>= 1) m = fmaxf(m, __shfl_xor_sync(0xffffffffu, m, o));
                    if (lane == 0) kvmax[128 + rb * 8 + warp] = m;
                } else {
                    float* kf = reinterpret_cast<float*>(smem_raw + 96 * 1024);
                    const int r = wg * 64 + wrow + g;
                    const int pos0 = (r >> 2) * 64 + rb * 4 + (r & 3), pos1 = pos0 + 128;
                    uint32_t* dst = reinterpret_cast<uint32_t*>(kv + 4 * (S_LEN * 8));
                    dst[pos0 * 4 + t] = pack_bf16(a[0], a[1]);
                    dst[S_LEN * 4 + pos0 * 4 + t] = pack_bf16(a[4], a[5]);
                    dst[pos1 * 4 + t] = pack_bf16(a[2], a[3]);
                    dst[S_LEN * 4 + pos1 * 4 + t] = pack_bf16(a[6], a[7]);
                    kf[r * 17 + 2 * t] = a[0]; kf[r * 17 + 2 * t + 1] = a[1];
                    kf[r * 17 + 8 + 2 * t] = a[4]; kf[r * 17 + 8 + 2 * t + 1] = a[5];
                    kf[(r + 8) * 17 + 2 * t] = a[2]; kf[(r + 8) * 17 + 2 * t + 1] = a[3];
                    kf[(r + 8) * 17 + 8 + 2 * t] = a[6]; kf[(r + 8) * 17 + 8 + 2 * t + 1] = a[7];
                    named_bar_sync(1, 256);
                    if (tid < 64) {
                        const int i = tid >> 4, dim = tid & 15;
                        __nv_bfloat16* dd = kv + (dim >> 3) * (S_LEN * 8) + (rb * 4 + i) * 8 + (dim & 7);
                        float kt = 0.f;
#pragma unroll 8
                        for (int j = 0; j < 32; j++) {
                            const __nv_bfloat16 d = __float2bfloat16_rn(kf[(j * 4 + i) * 17 + dim] - kt);
                            kt += __bfloat162float(d);
                            kf[(j * 4 + i) * 17 + dim] = kt;
                            dd[j * 512] = d;
                        }
                    }
                    named_bar_sync(1, 256);
                    if (tid < 128) {
                        float n = 0.f;
#pragma unroll
                        for (int d = 0; d < 16; d++) { const float v = kf[tid * 17 + d]; n += v * v; }
                        if (!(n == n)) n = __int_as_float(0x7f800000);
#pragma unroll
                        for (int o = 8; o > 0; o >>= 1) n = fmaxf(n, __shfl_xor_sync(0xffffffffu, n, o));
                        if ((lane & 15) == 0) kvmax[rb * 8 + (tid >> 4)] = n;
                    }
                }
            }
        }
        if (tid == 0) DEV_STAMP(0, 3);
        if (lane == 0) tma_store_wait();
        if (tid == 0) DEV_STAMP(0, 4);
    }
}

constexpr int AT_KT = 64;
constexpr int AT_NCHUNK = 8;
constexpr int AT_NSTEP = S_LEN / AT_KT;
constexpr int AT_SPC = AT_NSTEP / AT_NCHUNK;
constexpr int AT_SMEM = 5 * 32768 + 256;
#define AT_SWMASK_V 0xB6DB
constexpr uint32_t AT_SWMASK = AT_SWMASK_V;

#define AT_MAGIC (383.0f + 0.00390625f - 0.5849625f)
__device__ __forceinline__ uint32_t exp2_pair_alu(float t0, float t1) {
    const uint32_t y = __byte_perm(__float_as_uint(t0), __float_as_uint(t1), 0x6521);
    const uint32_t e = y & 0x7F807F80u;
    uint32_t uh, p;
    asm("lop3.b32 %0, %1, %2, 0x3F003F00, 0xBE;" : "=r"(uh) : "r"(y), "r"(e));
    asm("fma.rn.bf16x2 %0, %1, %2, %3;" : "=r"(p) : "r"(uh), "r"(y), "r"(e));
    return p;
}

__device__ __forceinline__ void at_load_chunk(uint32_t sbase, const __nv_bfloat16* KV, uint32_t bar0, int c) {
    constexpr uint32_t cb = (S_LEN / AT_NCHUNK) * 16;
    mbar_expect_tx(bar0 + 8 * c, 4 * cb);
#pragma unroll
    for (int r = 0; r < 4; r++)
        bulk_g2s(sbase + r * 32768 + c * cb, (const uint8_t*)KV + r * 32768 + c * cb, cb, bar0 + 8 * c);
}

__device__ __forceinline__ void at_store(const float* o, __nv_bfloat16* O, int row, int lane) {
    const float l0 = __shfl_sync(0xffffffffu, o[8], lane & ~3);
    const float l1 = __shfl_sync(0xffffffffu, o[10], lane & ~3);
    const float r0 = __fdividef(1.0f, l0), r1 = __fdividef(1.0f, l1);
    const int t = lane & 3;
    uint32_t* op = reinterpret_cast<uint32_t*>(O + (size_t)(row + (lane >> 2)) * 16);
    op[t] = pack_bf16(o[0] * r0, o[1] * r0);
    op[t + 4] = pack_bf16(o[4] * r0, o[5] * r0);
    op[64 + t] = pack_bf16(o[2] * r1, o[3] * r1);
    op[64 + t + 4] = pack_bf16(o[6] * r1, o[7] * r1);
}

__global__ void __launch_bounds__(512, 1)
k2_attn(const __nv_bfloat16* __restrict__ Q, const __nv_bfloat16* __restrict__ KV, const float* __restrict__ kvmax,
        __nv_bfloat16* __restrict__ O, int* __restrict__ flags) {
    extern __shared__ __align__(1024) uint8_t smem_raw[];
    const uint32_t sbase = smem_u32(smem_raw);
    const uint32_t bar0 = sbase + 5 * 32768;
    const int tid = threadIdx.x;
    if (tid == 0) DEV_STAMP(1, 0);
    if (tid == 0) {
        for (int i = 0; i < AT_NCHUNK; i++) mbar_init(bar0 + 8 * i, 1);
        mbar_init_fence();
    }
#pragma unroll
    for (int i = 0; i < S_LEN / 512; i++)
        asm volatile("st.shared.v4.b32 [%0], {%1,%2,%2,%2};" ::"r"(sbase + 4 * 32768 + (i * 512 + tid) * 16), "r"(0x00003F80u), "r"(0u) : "memory");
    fence_proxy_async();
    __syncthreads();
    pdl_wait();
    pdl_launch();
    if (tid == 0) DEV_STAMP(1, 1);
    if (tid == 0) { at_load_chunk(sbase, KV, bar0, 0); at_load_chunk(sbase, KV, bar0, 1); }
    if (tid == 32) flags[blockIdx.x] = 0;
    const int wg = tid >> 7, warp = (tid >> 5) & 3, lane = tid & 31;
    const int g = lane >> 2, t = lane & 3;
    const int rowA = blockIdx.x * 512 + wg * 128 + warp * 16;
    uint32_t qa[4], qb[4];
    {
        const uint32_t* qp = reinterpret_cast<const uint32_t*>(Q + (size_t)(rowA + g) * 16);
        qa[0] = qp[t]; qa[2] = qp[t + 4]; qa[1] = qp[64 + t]; qa[3] = qp[64 + t + 4];
        qb[0] = qp[512 + t]; qb[2] = qp[512 + t + 4]; qb[1] = qp[512 + 64 + t]; qb[3] = qp[512 + 64 + t + 4];
    }
    const uint64_t descK0 = make_desc(sbase, 32768, 128, 0);
    const uint64_t descV0 = make_desc(sbase + 65536, 128, 32768, 0);

#define AT_EXP(P) _Pragma("unroll") for (int i = 0; i < AT_KT / 4; i++) {                       \
                if ((AT_SWMASK >> (i & 15)) & 1) P[i] = exp2_pair_alu(s[2 * i], s[2 * i + 1]);  \
                else P[i] = pack_bf16(ex2(s[2 * i]), ex2(s[2 * i + 1])); }
#define AT_PV(P, dv) _Pragma("unroll") for (int j = 0; j < AT_KT / 16; j++)                     \
                wgmma_pv(o, P[4 * j], P[4 * j + 1], P[4 * j + 2], P[4 * j + 3], (dv) + (uint64_t)(j * 16));
#define AT_STEP(PC, PN, st) {                                                                   \
                if (st == AT_SPC - 1 && mt == 0) mbar_wait(bar0 + 8 * (c + 1), 0);              \
                wg_fence();                                                                     \
                wgmma_qk_acc_n64(s, q, dK + (uint64_t)(st * AT_KT));                            \
                wg_commit();                                                                    \
                AT_PV(PC, dV + (uint64_t)(st * AT_KT));                                         \
                wg_commit();                                                                    \
                wg_wait<1>();                                                                   \
                AT_EXP(PN);                                                                     \
                wg_wait<0>(); }

#pragma unroll 1
    for (int mt = 0; mt < 2; mt++) {
        uint32_t q[4];
#pragma unroll
        for (int i = 0; i < 4; i++) q[i] = mt ? qb[i] : qa[i];
        float o[12];
#pragma unroll
        for (int i = 0; i < 12; i++) asm volatile("mov.f32 %0, 0f00000000;" : "=f"(o[i]));
        float s[AT_KT / 2];
        uint32_t p0[AT_KT / 4], p1[AT_KT / 4];
#pragma unroll
        for (int i = 0; i < AT_KT / 2; i++) {
            if ((AT_SWMASK >> ((i >> 1) & 15)) & 1) asm volatile("mov.f32 %0, %1;" : "=f"(s[i]) : "f"(AT_MAGIC));
            else asm volatile("mov.f32 %0, 0f00000000;" : "=f"(s[i]));
        }
        if (mt == 0) mbar_wait(bar0, 0);
        if (tid == 0) DEV_STAMP(1, 2 + mt);
        wg_fence();
        wgmma_qk_acc_n64(s, q, descK0);
        wg_commit();
        wg_wait<0>();
        AT_EXP(p0);
        uint64_t dK = descK0 + AT_KT, dV = descV0;
#pragma unroll 1
        for (int c = 0; c < AT_NCHUNK - 1; c++) {
            if (tid == 0 && mt == 0 && c + 2 < AT_NCHUNK) at_load_chunk(sbase, KV, bar0, c + 2);
            AT_STEP(p0, p1, 0); AT_STEP(p1, p0, 1); AT_STEP(p0, p1, 2); AT_STEP(p1, p0, 3);
            dK += AT_SPC * AT_KT; dV += AT_SPC * AT_KT;
        }
        {
            const int c = 0; (void)c;
            AT_STEP(p0, p1, 0); AT_STEP(p1, p0, 1); AT_STEP(p0, p1, 2);
            wg_fence();
            AT_PV(p1, dV + (uint64_t)(3 * AT_KT));
            wg_commit();
            wg_wait<0>();
        }
        at_store(o, O, rowA + mt * 64, lane);
    }
    if (tid == 0) DEV_STAMP(1, 4);

    bool unsafe;
    {
        float km = fmaxf(fmaxf(kvmax[lane], kvmax[lane + 32]), fmaxf(kvmax[lane + 64], kvmax[lane + 96]));
        float vm = fmaxf(fmaxf(kvmax[128 + lane], kvmax[160 + lane]), fmaxf(kvmax[192 + lane], kvmax[224 + lane]));
        float n[4];
        n[0] = bf_lo(qa[0]) * bf_lo(qa[0]) + bf_hi(qa[0]) * bf_hi(qa[0]) + bf_lo(qa[2]) * bf_lo(qa[2]) + bf_hi(qa[2]) * bf_hi(qa[2]);
        n[1] = bf_lo(qa[1]) * bf_lo(qa[1]) + bf_hi(qa[1]) * bf_hi(qa[1]) + bf_lo(qa[3]) * bf_lo(qa[3]) + bf_hi(qa[3]) * bf_hi(qa[3]);
        n[2] = bf_lo(qb[0]) * bf_lo(qb[0]) + bf_hi(qb[0]) * bf_hi(qb[0]) + bf_lo(qb[2]) * bf_lo(qb[2]) + bf_hi(qb[2]) * bf_hi(qb[2]);
        n[3] = bf_lo(qb[1]) * bf_lo(qb[1]) + bf_hi(qb[1]) * bf_hi(qb[1]) + bf_lo(qb[3]) * bf_lo(qb[3]) + bf_hi(qb[3]) * bf_hi(qb[3]);
#pragma unroll
        for (int i = 0; i < 4; i++) { n[i] += __shfl_xor_sync(0xffffffffu, n[i], 1); n[i] += __shfl_xor_sync(0xffffffffu, n[i], 2); }
#pragma unroll
        for (int o = 16; o > 0; o >>= 1) { km = fmaxf(km, __shfl_xor_sync(0xffffffffu, km, o)); vm = fmaxf(vm, __shfl_xor_sync(0xffffffffu, vm, o)); }
        const float lim = 3600.0f;
        const bool ok = (n[0] * km <= lim) && (n[1] * km <= lim) && (n[2] * km <= lim) && (n[3] * km <= lim) && (vm <= 1.0e12f);
        unsafe = __any_sync(0xffffffffu, __syncthreads_or(!ok) != 0);
    }
    if (!unsafe) return;

    if (tid == 0) {
        mbar_expect_tx(bar0, 65536);
        bulk_g2s(sbase, (const uint8_t*)KV + 4 * 32768, 32768, bar0);
        bulk_g2s(sbase + 32768, (const uint8_t*)KV + 5 * 32768, 32768, bar0);
    }
    mbar_wait(bar0, 1);
#pragma unroll 1
    for (int mt = 0; mt < 2; mt++) {
        uint32_t q[4];
#pragma unroll
        for (int i = 0; i < 4; i++) q[i] = mt ? qb[i] : qa[i];
        float o[12];
#pragma unroll
        for (int i = 0; i < 12; i++) asm volatile("mov.f32 %0, 0f00000000;" : "=f"(o[i]));
        float s[AT_KT / 2];
        float m0 = -INFINITY, m1 = -INFINITY;
        uint32_t p[AT_KT / 4];
#pragma unroll 1
        for (int st = 0; st < AT_NSTEP; st++) {
            wg_fence();
            wgmma_qk_n64(s, q, descK0 + (uint64_t)(st * AT_KT));
            wg_commit();
            wg_wait<0>();
            float x0 = m0, x1 = m1;
#pragma unroll
            for (int j = 0; j < AT_KT / 8; j++) {
                x0 = fmaxf(x0, fmaxf(s[4 * j], s[4 * j + 1]));
                x1 = fmaxf(x1, fmaxf(s[4 * j + 2], s[4 * j + 3]));
            }
            x0 = fmaxf(x0, __shfl_xor_sync(0xffffffffu, x0, 1)); x0 = fmaxf(x0, __shfl_xor_sync(0xffffffffu, x0, 2));
            x1 = fmaxf(x1, __shfl_xor_sync(0xffffffffu, x1, 1)); x1 = fmaxf(x1, __shfl_xor_sync(0xffffffffu, x1, 2));
            const float f0 = ex2(m0 - x0), f1 = ex2(m1 - x1);
            m0 = x0; m1 = x1;
#pragma unroll
            for (int j = 0; j < 3; j++) { o[4 * j] *= f0; o[4 * j + 1] *= f0; o[4 * j + 2] *= f1; o[4 * j + 3] *= f1; }
#pragma unroll
            for (int j = 0; j < AT_KT / 8; j++) {
                p[2 * j] = pack_bf16(ex2(s[4 * j] - m0), ex2(s[4 * j + 1] - m0));
                p[2 * j + 1] = pack_bf16(ex2(s[4 * j + 2] - m1), ex2(s[4 * j + 3] - m1));
            }
            wg_fence();
            AT_PV(p, descV0 + (uint64_t)(st * AT_KT));
            wg_commit();
            wg_wait<0>();
        }
        at_store(o, O, rowA + mt * 64, lane);
    }
}

constexpr int K3_STAGES = 4;
constexpr int K3_STAGE_BYTES = 32768;
constexpr int K3_NK = 18, K3_NKH1 = 10;
constexpr int K3_XCH = K3_STAGES * K3_STAGE_BYTES;
constexpr int K3_X = K3_XCH + 65536;
constexpr int K3_SMEM = K3_X + 16384 + 256;

__global__ void __launch_bounds__(384, 1)
k3_out(const __grid_constant__ CUtensorMap tm_h, const __grid_constant__ CUtensorMap tm_o,
       const __grid_constant__ CUtensorMap tm_w2, const __grid_constant__ CUtensorMap tm_wo,
       const __grid_constant__ CUtensorMap tm_x, const __grid_constant__ CUtensorMap tm_out,
       const __nv_bfloat16* __restrict__ b2) {
    extern __shared__ __align__(1024) uint8_t smem_raw[];
    const uint32_t sbase = smem_u32(smem_raw);
    const uint32_t sX = sbase + K3_X;
    const uint32_t bar_full = sX + 16384, bar_empty = bar_full + 8 * K3_STAGES, bar_x = bar_empty + 8 * K3_STAGES;
    const int tid = threadIdx.x, warp = tid >> 5, lane = tid & 31;
    const int rank = blockIdx.x & 1, cb = (blockIdx.x >> 1) & 3, rb = blockIdx.x >> 3;
    if (tid == 0) DEV_STAMP(2, 0);
    if (tid == 256) {
        for (int s = 0; s < K3_STAGES; s++) { mbar_init(bar_full + 8 * s, 1); mbar_init(bar_empty + 8 * s, 8); }
        mbar_init(bar_x, 1);
        mbar_init_fence();
    }
    __syncthreads();
    if (warp >= 8) {
        if (tid == 256) {
            for (int ks = 0; ks < K3_NK; ks++) {
                const int s = ks % K3_STAGES;
                const uint32_t st = sbase + s * K3_STAGE_BYTES;
                const bool isH = rank == 0 || ks < K3_NKH1;
                if (rank == 1 && ks == K3_NKH1) pdl_wait();
                mbar_wait(bar_empty + 8 * s, ((ks / K3_STAGES) & 1) ^ 1);
                mbar_expect_tx(bar_full + 8 * s, K3_STAGE_BYTES);
                const int k0 = isH ? (ks + rank * K3_NK) * 64 : (ks - K3_NKH1) * 64;
                tma_load_2d(st, isH ? &tm_h : &tm_o, k0, rb * 128, bar_full + 8 * s);
                tma_load_2d(st + 16384, isH ? &tm_w2 : &tm_wo, cb * 128, k0, bar_full + 8 * s);
                tma_load_2d(st + 24576, isH ? &tm_w2 : &tm_wo, cb * 128 + 64, k0, bar_full + 8 * s);
                if (ks == K3_STAGES - 1) {
                    mbar_expect_tx(bar_x, 16384);
                    tma_load_2d(sX, &tm_x, cb * 128 + rank * 64, rb * 128, bar_x);
                }
            }
        }
        __syncwarp();
        cluster_sync_all();
    } else {
        const int wg = warp >> 2;
        float accY[64], accS[64];
#pragma unroll
        for (int i = 0; i < 64; i++) { asm volatile("mov.f32 %0, 0f00000000;" : "=f"(accY[i])); asm volatile("mov.f32 %0, 0f00000000;" : "=f"(accS[i])); }
        const uint64_t dA0 = make_desc(sbase + wg * 8192, 16, 1024, 1);
        const uint64_t dB0 = make_desc(sbase + 16384, 8192, 1024, 1);
#define K3_ITER(ACC, FIRST) {                                                                                      \
            const int s = ks % K3_STAGES;                                                                          \
            mbar_wait(bar_full + 8 * s, (ks / K3_STAGES) & 1);                                                     \
            wg_fence();                                                                                            \
            _Pragma("unroll") for (int kk = 0; kk < 4; kk++)                                                       \
                wgmma_ss_n128_tb(ACC, dA0 + (uint64_t)((s * K3_STAGE_BYTES + kk * 32) >> 4),                       \
                                 dB0 + (uint64_t)((s * K3_STAGE_BYTES + kk * 2048) >> 4), ((ks - (FIRST)) | kk) != 0); \
            wg_commit();                                                                                           \
            if (ks > 0) {                                                                                          \
                wg_wait<1>();                                                                                      \
                if (lane == 0 && ks - 1 < K3_NK - K3_STAGES) mbar_arrive(bar_empty + 8 * ((ks - 1) % K3_STAGES));  \
            } }
        const int nY = rank == 0 ? K3_NK : K3_NKH1;
        for (int ks = 0; ks < nY; ks++) K3_ITER(accY, 0)
        if (tid == 0) DEV_STAMP(2, 1);
        for (int ks = nY; ks < K3_NK; ks++) K3_ITER(accS, K3_NKH1)
        wg_wait<0>();
        if (tid == 0) DEV_STAMP(2, 2);
        uint32_t peer;
        asm volatile("mapa.shared::cluster.u32 %0, %1, %2;" : "=r"(peer) : "r"(sbase + K3_XCH + tid * 16), "r"(rank ^ 1));
        if (rank == 0) {
#pragma unroll
            for (int i = 0; i < 8; i++)
                asm volatile("st.shared::cluster.v4.f32 [%0], {%1,%2,%3,%4};" ::"r"(peer + i * 4096),
                             "f"(accY[32 + 4 * i]), "f"(accY[33 + 4 * i]), "f"(accY[34 + 4 * i]), "f"(accY[35 + 4 * i]) : "memory");
        } else {
#pragma unroll
            for (int i = 0; i < 8; i++) {
                asm volatile("st.shared::cluster.v4.f32 [%0], {%1,%2,%3,%4};" ::"r"(peer + i * 4096),
                             "f"(accY[4 * i]), "f"(accY[4 * i + 1]), "f"(accY[4 * i + 2]), "f"(accY[4 * i + 3]) : "memory");
                asm volatile("st.shared::cluster.v4.f32 [%0], {%1,%2,%3,%4};" ::"r"(peer + 32768 + i * 4096),
                             "f"(accS[4 * i]), "f"(accS[4 * i + 1]), "f"(accS[4 * i + 2]), "f"(accS[4 * i + 3]) : "memory");
            }
#pragma unroll
            for (int i = 0; i < 32; i++) { accY[i] = accY[32 + i]; accS[i] = accS[32 + i]; }
        }
        cluster_sync_all();
        const uint32_t mine = sbase + K3_XCH + tid * 16;
#pragma unroll
        for (int i = 0; i < 8; i++) {
            float4 v;
            asm volatile("ld.shared.v4.f32 {%0,%1,%2,%3}, [%4];" : "=f"(v.x), "=f"(v.y), "=f"(v.z), "=f"(v.w) : "r"(mine + i * 4096) : "memory");
            accY[4 * i] += v.x; accY[4 * i + 1] += v.y; accY[4 * i + 2] += v.z; accY[4 * i + 3] += v.w;
            if (rank == 0) {
                asm volatile("ld.shared.v4.f32 {%0,%1,%2,%3}, [%4];" : "=f"(accS[4 * i]), "=f"(accS[4 * i + 1]), "=f"(accS[4 * i + 2]), "=f"(accS[4 * i + 3])
                             : "r"(mine + 32768 + i * 4096) : "memory");
            }
        }
        mbar_wait(bar_x, 0);
        const int g = lane >> 2, t = lane & 3;
        const int row0 = warp * 16 + g;
        const int colb = cb * 128 + rank * 64;
#pragma unroll
        for (int j = 0; j < 8; j++) {
            const uint32_t bb = __ldg(reinterpret_cast<const uint32_t*>(b2 + colb + j * 8 + 2 * t));
            const float b0 = bf_lo(bb), b1v = bf_hi(bb);
#pragma unroll
            for (int h = 0; h < 2; h++) {
                const int row = row0 + h * 8;
                const uint32_t a = sX + row * 128 + ((j ^ (row & 7)) << 4) + t * 4;
                uint32_t xv;
                asm volatile("ld.shared.b32 %0, [%1];" : "=r"(xv) : "r"(a) : "memory");
                const float z0 = accY[4 * j + 2 * h] + b0, z1 = accY[4 * j + 2 * h + 1] + b1v;
                const float g0 = __fdividef(z0, 1.0f + __expf(-z0)), g1 = __fdividef(z1, 1.0f + __expf(-z1));
                const uint32_t ov = pack_bf16(bf_lo(xv) + accS[4 * j + 2 * h] * g0, bf_hi(xv) + accS[4 * j + 2 * h + 1] * g1);
                asm volatile("st.shared.b32 [%0], %1;" ::"r"(a), "r"(ov) : "memory");
            }
        }
        fence_proxy_async();
        __syncwarp();
        if (lane == 0) {
            tma_store_2d(&tm_out, sX + warp * 2048, colb, rb * 128 + warp * 16);
            tma_store_commit();
            if (tid == 0) DEV_STAMP(2, 3);
            tma_store_wait();
            if (tid == 0) DEV_STAMP(2, 4);
        }
    }
}

typedef CUresult (*EncodeFn)(CUtensorMap*, CUtensorMapDataType, cuuint32_t, void*, const cuuint64_t*, const cuuint64_t*,
                             const cuuint32_t*, const cuuint32_t*, CUtensorMapInterleave, CUtensorMapSwizzle,
                             CUtensorMapL2promotion, CUtensorMapFloatOOBfill);

struct HostState {
    bool ready;
    const void* key[11];
    CUtensorMap wq, wk, wv, w1, qo, ho, hi, oi, w2, wo, xi, out;
    void *pQ, *pKV, *pH, *pO, *pMax, *pRow, *pCol, *pFlag;
};
HostState g_hs;

void make_map(EncodeFn fn, CUtensorMap* m, const void* ptr, uint64_t inner, uint64_t outer, uint32_t box_in, uint32_t box_out) {
    cuuint64_t dims[2] = {inner, outer};
    cuuint64_t strides[1] = {inner * 2};
    cuuint32_t box[2] = {box_in, box_out};
    cuuint32_t es[2] = {1, 1};
    fn(m, CU_TENSOR_MAP_DATA_TYPE_BFLOAT16, 2, const_cast<void*>(ptr), dims, strides, box, es, CU_TENSOR_MAP_INTERLEAVE_NONE,
       CU_TENSOR_MAP_SWIZZLE_128B, CU_TENSOR_MAP_L2_PROMOTION_L2_256B, CU_TENSOR_MAP_FLOAT_OOB_FILL_NONE);
}

template <typename... KArgs, typename... Args>
void launch(void (*kern)(KArgs...), int grid, int block, int smem, bool pdl, int cluster, Args... args) {
    cudaLaunchConfig_t cfg = {};
    cfg.gridDim = dim3(grid); cfg.blockDim = dim3(block); cfg.dynamicSmemBytes = smem; cfg.stream = cudaStreamPerThread;
    cudaLaunchAttribute at[2];
    int n = 0;
    if (pdl) { at[n].id = cudaLaunchAttributeProgrammaticStreamSerialization; at[n].val.programmaticStreamSerializationAllowed = 1; n++; }
    if (cluster > 1) { at[n].id = cudaLaunchAttributeClusterDimension; at[n].val.clusterDim.x = cluster; at[n].val.clusterDim.y = 1; at[n].val.clusterDim.z = 1; n++; }
    cfg.attrs = at; cfg.numAttrs = n;
    cudaLaunchKernelEx(&cfg, kern, KArgs(args)...);
}

}

extern "C" void kernel_launch(void* const* d_in, const int* in_sizes, int n_in, void* d_out, int out_size) {
    (void)in_sizes; (void)n_in; (void)out_size;
    HostState& hs = g_hs;
    bool same = hs.ready;
    for (int i = 0; i < 10 && same; i++) same = hs.key[i] == d_in[i];
    same = same && hs.key[10] == d_out;
    if (!same) {
        void* fp = nullptr;
        cudaDriverEntryPointQueryResult qr;
        cudaGetDriverEntryPoint("cuTensorMapEncodeTiled", &fp, cudaEnableDefault, &qr);
        EncodeFn fn = (EncodeFn)fp;
        cudaGetSymbolAddress(&hs.pQ, g_Q); cudaGetSymbolAddress(&hs.pKV, g_KV); cudaGetSymbolAddress(&hs.pH, g_H);
        cudaGetSymbolAddress(&hs.pO, g_O); cudaGetSymbolAddress(&hs.pMax, g_kvmax);
        cudaGetSymbolAddress(&hs.pRow, g_rowstat); cudaGetSymbolAddress(&hs.pCol, g_colpart); cudaGetSymbolAddress(&hs.pFlag, g_flags);
        make_map(fn, &hs.wq, d_in[1], 512, 512, 64, 64);
        make_map(fn, &hs.wk, d_in[2], 16, 512, 64, 64);
        make_map(fn, &hs.wv, d_in[3], 16, 512, 64, 64);
        make_map(fn, &hs.w1, d_in[6], F_DIM, 512, 64, 64);
        make_map(fn, &hs.qo, hs.pQ, 512, S_LEN, 64, 16);
        make_map(fn, &hs.ho, hs.pH, F_DIM, S_LEN, 64, 16);
        make_map(fn, &hs.hi, hs.pH, F_DIM, S_LEN, 64, 128);
        make_map(fn, &hs.oi, hs.pO, 512, S_LEN, 64, 128);
        make_map(fn, &hs.w2, d_in[8], 512, F_DIM, 64, 64);
        make_map(fn, &hs.wo, d_in[4], 512, 512, 64, 64);
        make_map(fn, &hs.xi, d_in[0], 512, S_LEN, 64, 128);
        make_map(fn, &hs.out, d_out, 512, S_LEN, 64, 16);
        cudaFuncSetAttribute(k1_proj, cudaFuncAttributeMaxDynamicSharedMemorySize, K1_SMEM);
        cudaFuncSetAttribute(k2_attn, cudaFuncAttributeMaxDynamicSharedMemorySize, AT_SMEM);
        cudaFuncSetAttribute(k3_out, cudaFuncAttributeMaxDynamicSharedMemorySize, K3_SMEM);
        for (int i = 0; i < 10; i++) hs.key[i] = d_in[i];
        hs.key[10] = d_out;
        hs.ready = true;
    }
    launch(k1_proj, 128, 384, K1_SMEM, false, 1, hs.xi, hs.wq, hs.wk, hs.wv, hs.w1, hs.qo, hs.ho, (const __nv_bfloat16*)d_in[0],
           (const __nv_bfloat16*)d_in[1], (const __nv_bfloat16*)d_in[2], (const __nv_bfloat16*)d_in[3], (const __nv_bfloat16*)d_in[6],
           (const __nv_bfloat16*)d_in[7], (float2*)hs.pRow, (float*)hs.pCol, (int*)hs.pFlag, (__nv_bfloat16*)hs.pKV, (float*)hs.pMax);
    launch(k2_attn, 128, 512, AT_SMEM, true, 1, (const __nv_bfloat16*)hs.pQ, (const __nv_bfloat16*)hs.pKV, (const float*)hs.pMax,
           (__nv_bfloat16*)hs.pO, (int*)hs.pFlag);
    launch(k3_out, 128, 384, K3_SMEM, true, 2, hs.hi, hs.oi, hs.w2, hs.wo, hs.xi, hs.out, (const __nv_bfloat16*)d_in[9]);
}
```

```cpp
#include <cuda_runtime.h>
#include <cuda_bf16.h>
#include <cuda.h>
#include <stdint.h>

namespace {

constexpr int S_LEN = 2048, D_MODEL = 512, F_DIM = 1792;

__device__ __align__(1024) __nv_bfloat16 g_Q[S_LEN * D_MODEL];
__device__ __align__(1024) __nv_bfloat16 g_KV[6 * S_LEN * 8];
__device__ __align__(1024) __nv_bfloat16 g_G[S_LEN * D_MODEL];
__device__ __align__(1024) __nv_bfloat16 g_H[S_LEN * F_DIM];
__device__ __align__(1024) __nv_bfloat16 g_O[S_LEN * D_MODEL];
__device__ __align__(1024) float g_kvmax[256];
__device__ __align__(1024) float2 g_rowstat[S_LEN];
__device__ __align__(1024) float g_colpart[8 * 16 * 320];

#define DEV_STAMP(k, e) do {} while (0)
__device__ __forceinline__ uint32_t smem_u32(const void* p) { return (uint32_t)__cvta_generic_to_shared(p); }
__device__ __forceinline__ void wg_fence() { asm volatile("wgmma.fence.sync.aligned;" ::: "memory"); }
__device__ __forceinline__ void wg_commit() { asm volatile("wgmma.commit_group.sync.aligned;" ::: "memory"); }
template <int N> __device__ __forceinline__ void wg_wait() { asm volatile("wgmma.wait_group.sync.aligned %0;" ::"n"(N) : "memory"); }
template <int N> __device__ __forceinline__ void fence_regs(float* r) {
#pragma unroll
    for (int i = 0; i < N; i++) asm volatile("" : "+f"(r[i])::"memory");
}
__device__ __forceinline__ void fence_proxy_async() { asm volatile("fence.proxy.async.shared::cta;" ::: "memory"); }
__device__ __forceinline__ void mbar_init(uint32_t bar, int cnt) { asm volatile("mbarrier.init.shared::cta.b64 [%0], %1;" ::"r"(bar), "r"(cnt) : "memory"); }
__device__ __forceinline__ void mbar_init_fence() { asm volatile("fence.mbarrier_init.release.cluster;" ::: "memory"); }
__device__ __forceinline__ void mbar_expect_tx(uint32_t bar, uint32_t bytes) {
    asm volatile("mbarrier.arrive.expect_tx.shared::cta.b64 _, [%0], %1;" ::"r"(bar), "r"(bytes) : "memory");
}
__device__ __forceinline__ void mbar_arrive(uint32_t bar) { asm volatile("mbarrier.arrive.shared::cta.b64 _, [%0];" ::"r"(bar) : "memory"); }
__device__ __forceinline__ bool mbar_try(uint32_t bar, uint32_t parity) {
    uint32_t ok;
    asm volatile("{\n.reg .pred p;\nmbarrier.try_wait.parity.shared::cta.b64 p, [%1], %2;\nselp.u32 %0, 1, 0, p;\n}\n"
                 : "=r"(ok) : "r"(bar), "r"(parity) : "memory");
    return ok != 0;
}
__device__ __forceinline__ void mbar_wait(uint32_t bar, uint32_t parity) {
    if (mbar_try(bar, parity)) return;
    const long long t0 = clock64();
#pragma unroll 1
    while (!mbar_try(bar, parity)) {
        if (clock64() - t0 > 20000000ll) {
            break;
        }
    }
}
__device__ __forceinline__ void bulk_g2s(uint32_t dst, const void* src, uint32_t bytes, uint32_t bar) {
    asm volatile("cp.async.bulk.shared::cluster.global.mbarrier::complete_tx::bytes [%0], [%1], %2, [%3];"
                 ::"r"(dst), "l"(src), "r"(bytes), "r"(bar) : "memory");
}
__device__ __forceinline__ void tma_load_2d(uint32_t dst, const CUtensorMap* tm, int c0, int c1, uint32_t bar) {
    asm volatile("cp.async.bulk.tensor.2d.shared::cluster.global.mbarrier::complete_tx::bytes [%0], [%1, {%3, %4}], [%2];"
                 ::"r"(dst), "l"((uint64_t)tm), "r"(bar), "r"(c0), "r"(c1) : "memory");
}
__device__ __forceinline__ void tma_load_2d_mc(uint32_t dst, const CUtensorMap* tm, int c0, int c1, uint32_t bar, uint16_t mask) {
    asm volatile("cp.async.bulk.tensor.2d.shared::cluster.global.mbarrier::complete_tx::bytes.multicast::cluster [%0], [%1, {%3, %4}], [%2], %5;"
                 ::"r"(dst), "l"((uint64_t)tm), "r"(bar), "r"(c0), "r"(c1), "h"(mask) : "memory");
}
__device__ __forceinline__ void mbar_arrive_remote(uint32_t bar, uint32_t cta) {
    asm volatile("{\n.reg .b32 ra;\nmapa.shared::cluster.u32 ra, %0, %1;\nmbarrier.arrive.shared::cluster.b64 _, [ra];\n}\n"
                 ::"r"(bar), "r"(cta) : "memory");
}
__device__ __forceinline__ void cluster_sync_relaxed() {
    asm volatile("barrier.cluster.arrive.relaxed;\nbarrier.cluster.wait;" ::: "memory");
}
__device__ __forceinline__ uint2 ld_relaxed_v2(const void* p) {
    uint2 v; asm volatile("ld.relaxed.gpu.global.v2.b32 {%0,%1}, [%2];" : "=r"(v.x), "=r"(v.y) : "l"(p) : "memory"); return v;
}
constexpr uint32_t NOT_READY = 0u;
__device__ __forceinline__ float xch_enc(float v) { return __uint_as_float((v == 0.f ? 0u : __float_as_uint(v)) ^ 0x80000000u); }
__device__ __forceinline__ float xch_dec(uint32_t u) { return __uint_as_float(u ^ 0x80000000u); }
__device__ __forceinline__ void tma_store_2d(const CUtensorMap* tm, uint32_t src, int c0, int c1) {
    asm volatile("cp.async.bulk.tensor.2d.global.shared::cta.bulk_group [%0, {%2, %3}], [%1];"
                 ::"l"((uint64_t)tm), "r"(src), "r"(c0), "r"(c1) : "memory");
}
__device__ __forceinline__ void tma_store_commit() { asm volatile("cp.async.bulk.commit_group;" ::: "memory"); }
__device__ __forceinline__ void tma_store_wait() { asm volatile("cp.async.bulk.wait_group 0;" ::: "memory"); }
__device__ __forceinline__ void tma_prefetch_desc(const CUtensorMap* tm) { asm volatile("prefetch.tensormap [%0];" ::"l"((uint64_t)tm) : "memory"); }
__device__ __forceinline__ void named_bar_sync(int id, int n) { asm volatile("bar.sync %0, %1;" ::"r"(id), "r"(n) : "memory"); }
__device__ __forceinline__ void pdl_wait() { asm volatile("griddepcontrol.wait;" ::: "memory"); }
__device__ __forceinline__ void pdl_launch() { asm volatile("griddepcontrol.launch_dependents;" ::: "memory"); }
template <int N> __device__ __forceinline__ void reg_alloc() { asm volatile("setmaxnreg.inc.sync.aligned.u32 %0;" ::"n"(N)); }
template <int N> __device__ __forceinline__ void reg_dealloc() { asm volatile("setmaxnreg.dec.sync.aligned.u32 %0;" ::"n"(N)); }
__device__ __forceinline__ float ex2(float x) { float y; asm("ex2.approx.ftz.f32 %0, %1;" : "=f"(y) : "f"(x)); return y; }
__device__ __forceinline__ uint32_t pack_bf16(float lo, float hi) {
    uint32_t r; asm("cvt.rn.bf16x2.f32 %0, %1, %2;" : "=r"(r) : "f"(hi), "f"(lo)); return r;
}
__device__ __forceinline__ uint32_t pack_bf16_relu(float lo, float hi) {
    uint32_t r; asm("cvt.rn.relu.bf16x2.f32 %0, %1, %2;" : "=r"(r) : "f"(hi), "f"(lo)); return r;
}
__device__ __forceinline__ uint32_t mul_bf16x2(uint32_t a, uint32_t b) {
    uint32_t r; asm("mul.rn.bf16x2 %0, %1, %2;" : "=r"(r) : "r"(a), "r"(b)); return r;
}
__device__ __forceinline__ float bf_lo(uint32_t v) { return __uint_as_float(v << 16); }
__device__ __forceinline__ float bf_hi(uint32_t v) { return __uint_as_float(v & 0xFFFF0000u); }
__device__ __forceinline__ void stmatrix_x4(uint32_t addr, uint32_t r0, uint32_t r1, uint32_t r2, uint32_t r3) {
    asm volatile("stmatrix.sync.aligned.m8n8.x4.shared.b16 [%0], {%1,%2,%3,%4};" ::"r"(addr), "r"(r0), "r"(r1), "r"(r2), "r"(r3) : "memory");
}
__device__ __forceinline__ uint64_t make_desc(uint32_t addr, uint32_t lbo, uint32_t sbo, uint32_t swz) {
    return (uint64_t)((addr & 0x3FFFF) >> 4) | ((uint64_t)(lbo >> 4) << 16) | ((uint64_t)(sbo >> 4) << 32) | ((uint64_t)swz << 62);
}

__device__ __forceinline__ uint64_t desc64(uint32_t lo, uint32_t hi) {
    uint64_t d; asm("mov.b64 %0, {%1, %2};" : "=l"(d) : "r"(lo), "r"(hi)); return d;
}

__device__ __forceinline__ void wgmma_ss_n256_tb(float* d, uint64_t descA, uint64_t descB, int scaleD) {
    asm volatile("{\n.reg .pred p;\nsetp.ne.b32 p, %130, 0;\n"
      "wgmma.mma_async.sync.aligned.m64n256k16.f32.bf16.bf16 {%0,%1,%2,%3,%4,%5,%6,%7,%8,%9,%10,%11,%12,%13,%14,%15,%16,%17,%18,%19,%20,%21,%22,%23,%24,%25,%26,%27,%28,%29,%30,%31,%32,%33,%34,%35,%36,%37,%38,%39,%40,%41,%42,%43,%44,%45,%46,%47,%48,%49,%50,%51,%52,%53,%54,%55,%56,%57,%58,%59,%60,%61,%62,%63,%64,%65,%66,%67,%68,%69,%70,%71,%72,%73,%74,%75,%76,%77,%78,%79,%80,%81,%82,%83,%84,%85,%86,%87,%88,%89,%90,%91,%92,%93,%94,%95,%96,%97,%98,%99,%100,%101,%102,%103,%104,%105,%106,%107,%108,%109,%110,%111,%112,%113,%114,%115,%116,%117,%118,%119,%120,%121,%122,%123,%124,%125,%126,%127}, %128, %129, p, 1, 1, 0, 1;\n}\n"
      : "+f"(d[0]), "+f"(d[1]), "+f"(d[2]), "+f"(d[3]), "+f"(d[4]), "+f"(d[5]), "+f"(d[6]), "+f"(d[7]), "+f"(d[8]), "+f"(d[9]), "+f"(d[10]), "+f"(d[11]), "+f"(d[12]), "+f"(d[13]), "+f"(d[14]), "+f"(d[15]), "+f"(d[16]), "+f"(d[17]), "+f"(d[18]), "+f"(d[19]), "+f"(d[20]), "+f"(d[21]), "+f"(d[22]), "+f"(d[23]), "+f"(d[24]), "+f"(d[25]), "+f"(d[26]), "+f"(d[27]), "+f"(d[28]), "+f"(d[29]), "+f"(d[30]), "+f"(d[31]), "+f"(d[32]), "+f"(d[33]), "+f"(d[34]), "+f"(d[35]), "+f"(d[36]), "+f"(d[37]), "+f"(d[38]), "+f"(d[39]), "+f"(d[40]), "+f"(d[41]), "+f"(d[42]), "+f"(d[43]), "+f"(d[44]), "+f"(d[45]), "+f"(d[46]), "+f"(d[47]), "+f"(d[48]), "+f"(d[49]), "+f"(d[50]), "+f"(d[51]), "+f"(d[52]), "+f"(d[53]), "+f"(d[54]), "+f"(d[55]), "+f"(d[56]), "+f"(d[57]), "+f"(d[58]), "+f"(d[59]), "+f"(d[60]), "+f"(d[61]), "+f"(d[62]), "+f"(d[63]), "+f"(d[64]), "+f"(d[65]), "+f"(d[66]), "+f"(d[67]), "+f"(d[68]), "+f"(d[69]), "+f"(d[70]), "+f"(d[71]), "+f"(d[72]), "+f"(d[73]), "+f"(d[74]), "+f"(d[75]), "+f"(d[76]), "+f"(d[77]), "+f"(d[78]), "+f"(d[79]), "+f"(d[80]), "+f"(d[81]), "+f"(d[82]), "+f"(d[83]), "+f"(d[84]), "+f"(d[85]), "+f"(d[86]), "+f"(d[87]), "+f"(d[88]), "+f"(d[89]), "+f"(d[90]), "+f"(d[91]), "+f"(d[92]), "+f"(d[93]), "+f"(d[94]), "+f"(d[95]), "+f"(d[96]), "+f"(d[97]), "+f"(d[98]), "+f"(d[99]), "+f"(d[100]), "+f"(d[101]), "+f"(d[102]), "+f"(d[103]), "+f"(d[104]), "+f"(d[105]), "+f"(d[106]), "+f"(d[107]), "+f"(d[108]), "+f"(d[109]), "+f"(d[110]), "+f"(d[111]), "+f"(d[112]), "+f"(d[113]), "+f"(d[114]), "+f"(d[115]), "+f"(d[116]), "+f"(d[117]), "+f"(d[118]), "+f"(d[119]), "+f"(d[120]), "+f"(d[121]), "+f"(d[122]), "+f"(d[123]), "+f"(d[124]), "+f"(d[125]), "+f"(d[126]), "+f"(d[127])
      : "l"(descA), "l"(descB), "r"(scaleD));
}
__device__ __forceinline__ void wgmma_ss_n128_tb(float* d, uint64_t descA, uint64_t descB, int scaleD) {
    asm volatile("{\n.reg .pred p;\nsetp.ne.b32 p, %66, 0;\n"
      "wgmma.mma_async.sync.aligned.m64n128k16.f32.bf16.bf16 {%0,%1,%2,%3,%4,%5,%6,%7,%8,%9,%10,%11,%12,%13,%14,%15,%16,%17,%18,%19,%20,%21,%22,%23,%24,%25,%26,%27,%28,%29,%30,%31,%32,%33,%34,%35,%36,%37,%38,%39,%40,%41,%42,%43,%44,%45,%46,%47,%48,%49,%50,%51,%52,%53,%54,%55,%56,%57,%58,%59,%60,%61,%62,%63}, %64, %65, p, 1, 1, 0, 1;\n}\n"
      : "+f"(d[0]), "+f"(d[1]), "+f"(d[2]), "+f"(d[3]), "+f"(d[4]), "+f"(d[5]), "+f"(d[6]), "+f"(d[7]), "+f"(d[8]), "+f"(d[9]), "+f"(d[10]), "+f"(d[11]), "+f"(d[12]), "+f"(d[13]), "+f"(d[14]), "+f"(d[15]), "+f"(d[16]), "+f"(d[17]), "+f"(d[18]), "+f"(d[19]), "+f"(d[20]), "+f"(d[21]), "+f"(d[22]), "+f"(d[23]), "+f"(d[24]), "+f"(d[25]), "+f"(d[26]), "+f"(d[27]), "+f"(d[28]), "+f"(d[29]), "+f"(d[30]), "+f"(d[31]), "+f"(d[32]), "+f"(d[33]), "+f"(d[34]), "+f"(d[35]), "+f"(d[36]), "+f"(d[37]), "+f"(d[38]), "+f"(d[39]), "+f"(d[40]), "+f"(d[41]), "+f"(d[42]), "+f"(d[43]), "+f"(d[44]), "+f"(d[45]), "+f"(d[46]), "+f"(d[47]), "+f"(d[48]), "+f"(d[49]), "+f"(d[50]), "+f"(d[51]), "+f"(d[52]), "+f"(d[53]), "+f"(d[54]), "+f"(d[55]), "+f"(d[56]), "+f"(d[57]), "+f"(d[58]), "+f"(d[59]), "+f"(d[60]), "+f"(d[61]), "+f"(d[62]), "+f"(d[63])
      : "l"(descA), "l"(descB), "r"(scaleD));
}
__device__ __forceinline__ void wgmma_ss_n64_tb(float* d, uint64_t descA, uint64_t descB, int scaleD) {
    asm volatile("{\n.reg .pred p;\nsetp.ne.b32 p, %34, 0;\n"
      "wgmma.mma_async.sync.aligned.m64n64k16.f32.bf16.bf16 {%0,%1,%2,%3,%4,%5,%6,%7,%8,%9,%10,%11,%12,%13,%14,%15,%16,%17,%18,%19,%20,%21,%22,%23,%24,%25,%26,%27,%28,%29,%30,%31}, %32, %33, p, 1, 1, 0, 1;\n}\n"
      : "+f"(d[0]), "+f"(d[1]), "+f"(d[2]), "+f"(d[3]), "+f"(d[4]), "+f"(d[5]), "+f"(d[6]), "+f"(d[7]), "+f"(d[8]), "+f"(d[9]), "+f"(d[10]), "+f"(d[11]), "+f"(d[12]), "+f"(d[13]), "+f"(d[14]), "+f"(d[15]), "+f"(d[16]), "+f"(d[17]), "+f"(d[18]), "+f"(d[19]), "+f"(d[20]), "+f"(d[21]), "+f"(d[22]), "+f"(d[23]), "+f"(d[24]), "+f"(d[25]), "+f"(d[26]), "+f"(d[27]), "+f"(d[28]), "+f"(d[29]), "+f"(d[30]), "+f"(d[31])
      : "l"(descA), "l"(descB), "r"(scaleD));
}
__device__ __forceinline__ void wgmma_qk_acc_n64(float* d, const uint32_t* a, uint64_t descB) {
    asm volatile("wgmma.mma_async.sync.aligned.m64n64k16.f32.bf16.bf16 {%0,%1,%2,%3,%4,%5,%6,%7,%8,%9,%10,%11,%12,%13,%14,%15,%16,%17,%18,%19,%20,%21,%22,%23,%24,%25,%26,%27,%28,%29,%30,%31}, {%32,%33,%34,%35}, %36, 1, 1, 1, 0;\n"
      : "+f"(d[0]), "+f"(d[1]), "+f"(d[2]), "+f"(d[3]), "+f"(d[4]), "+f"(d[5]), "+f"(d[6]), "+f"(d[7]), "+f"(d[8]), "+f"(d[9]), "+f"(d[10]), "+f"(d[11]), "+f"(d[12]), "+f"(d[13]), "+f"(d[14]), "+f"(d[15]), "+f"(d[16]), "+f"(d[17]), "+f"(d[18]), "+f"(d[19]), "+f"(d[20]), "+f"(d[21]), "+f"(d[22]), "+f"(d[23]), "+f"(d[24]), "+f"(d[25]), "+f"(d[26]), "+f"(d[27]), "+f"(d[28]), "+f"(d[29]), "+f"(d[30]), "+f"(d[31])
      : "r"(a[0]), "r"(a[1]), "r"(a[2]), "r"(a[3]), "l"(descB));
}

__device__ __forceinline__ void wgmma_pv(float* d, uint32_t a0, uint32_t a1, uint32_t a2, uint32_t a3, uint64_t descB) {
    asm volatile("wgmma.mma_async.sync.aligned.m64n24k16.f32.bf16.bf16 {%0,%1,%2,%3,%4,%5,%6,%7,%8,%9,%10,%11}, {%12,%13,%14,%15}, %16, 1, 1, 1, 1;\n"
                 : "+f"(d[0]), "+f"(d[1]), "+f"(d[2]), "+f"(d[3]), "+f"(d[4]), "+f"(d[5]), "+f"(d[6]), "+f"(d[7]), "+f"(d[8]), "+f"(d[9]), "+f"(d[10]), "+f"(d[11])
                 : "r"(a0), "r"(a1), "r"(a2), "r"(a3), "l"(descB));
}

__device__ __forceinline__ void k1_panel(int g, int i, int& type, int& col) {
    if (g < 6) {
        int p = g * 5 + i;
        if (p < 8) { type = 0; col = p * 64; } else { type = 1; col = (p - 8) * 64; }
    } else {
        if (i < 3) { type = 1; col = (22 + (g - 6) * 3 + i) * 64; } else { type = 2 + (g - 6); col = 0; }
    }
}

constexpr int K1_STAGES = 4;
constexpr int K1_PANEL_BYTES = 64 * 128;
constexpr int K1_STAGE_BYTES = 16384 + 5 * K1_PANEL_BYTES;
constexpr int K1_SMEM = K1_STAGES * K1_STAGE_BYTES + 128 + 320 * 8;
constexpr float Q_SCALE = 0.25f * 1.4426950408889634f;

__global__ void __launch_bounds__(384, 1)
k1_proj(const __grid_constant__ CUtensorMap tm_x, const __grid_constant__ CUtensorMap tm_wq,
        const __grid_constant__ CUtensorMap tm_wk, const __grid_constant__ CUtensorMap tm_wv,
        const __grid_constant__ CUtensorMap tm_w1, const __grid_constant__ CUtensorMap tm_qo,
        const __grid_constant__ CUtensorMap tm_ho, const __nv_bfloat16* __restrict__ x,
        const __nv_bfloat16* __restrict__ wq, const __nv_bfloat16* __restrict__ wk, const __nv_bfloat16* __restrict__ wv,
        const __nv_bfloat16* __restrict__ w1, const __nv_bfloat16* __restrict__ b1,
        float2* rowstat, float* colpart,
        __nv_bfloat16* __restrict__ kv, float* __restrict__ kvmax) {
    extern __shared__ __align__(1024) uint8_t smem_raw[];
    const uint32_t sbase = smem_u32(smem_raw);
    const uint32_t bar_full = sbase + K1_STAGES * K1_STAGE_BYTES, bar_empty = bar_full + 8 * K1_STAGES, bar_col = bar_empty + 8 * K1_STAGES;
    const uint32_t sCol = bar_full + 128;
    const int tid = threadIdx.x, warp = __shfl_sync(0xffffffffu, tid >> 5, 0), lane = tid & 31;
    const int crank = blockIdx.x & 1, grp = (blockIdx.x >> 1) & 7, rb = (blockIdx.x >> 4) * 2 + crank;
    const int npanels = grp < 6 ? 5 : 4;
    if (tid == 0) DEV_STAMP(0, 0);

    const int row0 = rb * 128 + grp * 16 + warp * 2;
    uint4 v[2][2], u[8];
    if (warp < 8) {
            const uint4* xp = reinterpret_cast<const uint4*>(x + (size_t)row0 * D_MODEL);
#pragma unroll
            for (int r = 0; r < 2; r++) { v[r][0] = __ldg(xp + r * 64 + lane); v[r][1] = __ldg(xp + r * 64 + 32 + lane); }
            int type = 0, col = 0;
            if (warp < npanels) k1_panel(grp, warp, type, col);
            const bool cvalid = warp < npanels && (type <= 1 || (lane & 7) < 2);
            if (cvalid) {
                const __nv_bfloat16* w = type == 0 ? wq : type == 1 ? w1 : type == 2 ? wk : wv;
                const int ld = type == 0 ? D_MODEL : type == 1 ? F_DIM : 16;
                const __nv_bfloat16* wp = w + (size_t)(rb * 32 + (lane >> 3)) * ld + col + (lane & 7) * 8;
#pragma unroll
                for (int k = 0; k < 8; k++) u[k] = __ldg(reinterpret_cast<const uint4*>(wp + (size_t)(k * 4) * ld));
            } else {
#pragma unroll
                for (int k = 0; k < 8; k++) u[k] = make_uint4(0, 0, 0, 0);
            }
    }
    if (tid == 256) {
        for (int s = 0; s < K1_STAGES; s++) { mbar_init(bar_full + 8 * s, 1); mbar_init(bar_empty + 8 * s, 16); }
        mbar_init(bar_col, 96);
        mbar_init_fence();
    }
    cluster_sync_relaxed();
    pdl_launch();

    if (warp >= 8) {
        reg_dealloc<88>();
            if (warp == 8) {
            if (lane == 0) {
                const CUtensorMap* tms[5]; int cols[5];
#pragma unroll
                for (int i = 0; i < 5; i++) {
                    int type, col; k1_panel(grp, i, type, col);
                    tms[i] = type == 0 ? &tm_wq : type == 1 ? &tm_w1 : type == 2 ? &tm_wk : &tm_wv;
                    cols[i] = col;
                }
                for (int ks = 0; ks < 8; ks++) {
                    const int s = ks % K1_STAGES;
                    const uint32_t st = sbase + s * K1_STAGE_BYTES;
                    mbar_wait(bar_empty + 8 * s, ((ks / K1_STAGES) & 1) ^ 1);
                    mbar_expect_tx(bar_full + 8 * s, 16384 + npanels * K1_PANEL_BYTES);
                    tma_load_2d(st, &tm_x, ks * 64, rb * 128, bar_full + 8 * s);
#pragma unroll
                    for (int i = 0; i < 5; i++)
                        if (i < npanels && ((i + ks + crank) & 1) == 0)
                            tma_load_2d_mc(st + 16384 + i * K1_PANEL_BYTES, tms[i], cols[i], ks * 64, bar_full + 8 * s, (uint16_t)3);
                }
            }
        } else {
            const int ht = tid - 288;
            for (int c2 = ht; c2 < npanels * 32; c2 += 96) {
                int type, col; k1_panel(grp, c2 >> 5, type, col);
                uint32_t bb = 0;
                if (type == 1) bb = __ldg(reinterpret_cast<const uint32_t*>(b1 + col) + (c2 & 31));
                uint2 pv[16];
                bool okv = false;
#pragma unroll 1
                for (uint32_t n = 0; n < (1u << 14) && !okv; n++) {
                    okv = true;
#pragma unroll
                    for (int k = 0; k < 16; k++) pv[k] = ld_relaxed_v2(colpart + (grp * 16 + k) * 320 + c2 * 2);
#pragma unroll
                    for (int k = 0; k < 16; k++) okv = okv && pv[k].x != NOT_READY && pv[k].y != NOT_READY;
                    if (!okv) __nanosleep(200);
                }
                float s0 = 0.f, s1 = 0.f;
#pragma unroll
                for (int k = 0; k < 16; k++) { s0 += xch_dec(pv[k].x); s1 += xch_dec(pv[k].y); }
                asm volatile("st.shared.v4.f32 [%0], {%1,%2,%3,%4};" ::"r"(sCol + c2 * 16), "f"(s0), "f"(bf_lo(bb)), "f"(s1), "f"(bf_hi(bb)) : "memory");
            }
            mbar_arrive(bar_col);
            if (ht == 0) DEV_STAMP(0, 7);
        }
    } else {
        reg_alloc<208>();
        const int wg = warp >> 2;
        const int g = lane >> 2, t = lane & 3;
        const int wrow = (warp & 3) * 16;
        {
#pragma unroll
            for (int r = 0; r < 2; r++) {
                float f[16];
                const uint32_t w[8] = {v[r][0].x, v[r][0].y, v[r][0].z, v[r][0].w, v[r][1].x, v[r][1].y, v[r][1].z, v[r][1].w};
#pragma unroll
                for (int i = 0; i < 8; i++) { f[2 * i] = bf_lo(w[i]); f[2 * i + 1] = bf_hi(w[i]); }
                float sum = 0.f;
#pragma unroll
                for (int i = 0; i < 16; i++) sum += f[i];
#pragma unroll
                for (int o = 16; o > 0; o >>= 1) sum += __shfl_xor_sync(0xffffffffu, sum, o);
                const float mean = sum * (1.0f / D_MODEL);
                float sq = 0.f;
#pragma unroll
                for (int i = 0; i < 16; i++) { const float d = f[i] - mean; sq += d * d; }
#pragma unroll
                for (int o = 16; o > 0; o >>= 1) sq += __shfl_xor_sync(0xffffffffu, sq, o);
                const float rstd = rsqrtf(sq * (1.0f / D_MODEL) + 1e-5f);
                if (lane == 0) rowstat[row0 + r] = make_float2(xch_enc(rstd), mean * rstd);
            }
            if (warp < npanels) {
                float sacc[8];
#pragma unroll
                for (int c = 0; c < 8; c++) sacc[c] = 0.f;
#pragma unroll
                for (int k = 0; k < 8; k++) {
                    sacc[0] += bf_lo(u[k].x); sacc[1] += bf_hi(u[k].x); sacc[2] += bf_lo(u[k].y); sacc[3] += bf_hi(u[k].y);
                    sacc[4] += bf_lo(u[k].z); sacc[5] += bf_hi(u[k].z); sacc[6] += bf_lo(u[k].w); sacc[7] += bf_hi(u[k].w);
                }
#pragma unroll
                for (int c = 0; c < 8; c++) {
                    sacc[c] += __shfl_xor_sync(0xffffffffu, sacc[c], 8);
                    sacc[c] += __shfl_xor_sync(0xffffffffu, sacc[c], 16);
                }
                if (lane < 8) {
                    float4* dst = reinterpret_cast<float4*>(colpart + (grp * 16 + rb) * 320 + warp * 64 + lane * 8);
                    dst[0] = make_float4(xch_enc(sacc[0]), xch_enc(sacc[1]), xch_enc(sacc[2]), xch_enc(sacc[3]));
                    dst[1] = make_float4(xch_enc(sacc[4]), xch_enc(sacc[5]), xch_enc(sacc[6]), xch_enc(sacc[7]));
                }
            }
        }
        float acc[160];
#pragma unroll
        for (int i = 0; i < 160; i++) acc[i] = 0.f;
        float2 rs0, rs1;
        const uint64_t dA0 = make_desc(sbase + wg * 8192, 16, 1024, 1);
        const uint64_t dB0 = make_desc(sbase + 16384, K1_PANEL_BYTES, 1024, 1);
#define K1_MAINLOOP(FIVE)                                                                                          \
        for (int ks = 0; ks < 8; ks++) {                                                                           \
            const int s = ks % K1_STAGES;                                                                          \
            mbar_wait(bar_full + 8 * s, (ks / K1_STAGES) & 1);                                                     \
            if (ks == 0 && tid == 0) DEV_STAMP(0, 1);                                                              \
            wg_fence();                                                                                            \
            _Pragma("unroll") for (int kk = 0; kk < 4; kk++) {                                                     \
                const uint64_t dA = dA0 + (uint64_t)((s * K1_STAGE_BYTES + kk * 32) >> 4);                         \
                const uint64_t dB = dB0 + (uint64_t)((s * K1_STAGE_BYTES + kk * 2048) >> 4);                       \
                wgmma_ss_n256_tb(acc, dA, dB, (ks | kk) != 0);                                                     \
                if (FIVE) wgmma_ss_n64_tb(acc + 128, dA, dB + (uint64_t)((4 * K1_PANEL_BYTES) >> 4), (ks | kk) != 0); \
            }                                                                                                      \
            wg_commit();                                                                                           \
            if (ks == 7) {                                                                                         \
                uint2 r0, r1;                                                                                      \
                uint32_t n = 0;                                                                                    \
                _Pragma("unroll 1") do {                                                                           \
                    r0 = ld_relaxed_v2(rowstat + rb * 128 + wg * 64 + wrow + g);                                   \
                    r1 = ld_relaxed_v2(rowstat + rb * 128 + wg * 64 + wrow + g + 8);                               \
                } while ((r0.x == NOT_READY || r1.x == NOT_READY) && ++n < (1u << 14));                            \
                rs0 = make_float2(xch_dec(r0.x), __uint_as_float(r0.y));                                           \
                rs1 = make_float2(xch_dec(r1.x), __uint_as_float(r1.y));                                           \
                mbar_wait(bar_col, 0);                                                                             \
            }                                                                                                      \
            if (ks > 0 && ks <= 4) {                                                                               \
                wg_wait<1>();                                                                                      \
                if (lane < 2) mbar_arrive_remote(bar_empty + 8 * ((ks - 1) % K1_STAGES), lane);                    \
            }                                                                                                      \
        }                                                                                                          \
        wg_wait<0>();
        if (npanels == 5) { K1_MAINLOOP(true) } else { K1_MAINLOOP(false) }
        fence_regs<160>(acc);
        if (tid == 0) DEV_STAMP(0, 2);
        named_bar_sync(1, 256);
        const int srow = (lane & 7) + ((lane >> 3) & 1) * 8;
#pragma unroll
        for (int p = 0; p < 5; p++) {
            if (p < npanels) {
                int type, col; k1_panel(grp, p, type, col);
                float* a = acc + p * 32;
                const int nj = type <= 1 ? 8 : 2;
                const float sc = type == 0 ? Q_SCALE : 1.0f;
                const float r0x = rs0.x * sc, r0y = -rs0.y * sc, r1x = rs1.x * sc, r1y = -rs1.y * sc;
#pragma unroll
                for (int j = 0; j < 8; j++) {
                    if (j < nj) {
                        float4 c;
                        asm volatile("ld.shared.v4.f32 {%0,%1,%2,%3}, [%4];" : "=f"(c.x), "=f"(c.y), "=f"(c.z), "=f"(c.w)
                                     : "r"(sCol + (p * 64 + j * 8 + 2 * t) * 8));
                        a[4 * j] = fmaf(a[4 * j], r0x, fmaf(r0y, c.x, c.y));
                        a[4 * j + 1] = fmaf(a[4 * j + 1], r0x, fmaf(r0y, c.z, c.w));
                        a[4 * j + 2] = fmaf(a[4 * j + 2], r1x, fmaf(r1y, c.x, c.y));
                        a[4 * j + 3] = fmaf(a[4 * j + 3], r1x, fmaf(r1y, c.z, c.w));
                    }
                }
                if (type <= 1) {
                    const uint32_t stg = sbase + (p * 8 + warp) * 2048;
                    uint32_t pk[16];
                    if (type == 0) {
#pragma unroll
                        for (int j = 0; j < 8; j++) {
                            pk[2 * j] = pack_bf16(a[4 * j], a[4 * j + 1]);
                            pk[2 * j + 1] = pack_bf16(a[4 * j + 2], a[4 * j + 3]);
                        }
                    } else {
#pragma unroll
                        for (int j = 0; j < 8; j++) {
                            const uint32_t h0 = pack_bf16_relu(a[4 * j], a[4 * j + 1]), h1 = pack_bf16_relu(a[4 * j + 2], a[4 * j + 3]);
                            pk[2 * j] = mul_bf16x2(h0, h0);
                            pk[2 * j + 1] = mul_bf16x2(h1, h1);
                        }
                    }
#pragma unroll
                    for (int j = 0; j < 8; j += 2) {
                        const int c16 = j + (lane >> 4);
                        stmatrix_x4(stg + srow * 128 + ((c16 ^ (srow & 7)) << 4), pk[2 * j], pk[2 * j + 1], pk[2 * j + 2], pk[2 * j + 3]);
                    }
                    fence_proxy_async();
                    __syncwarp();
                    if (lane == 0) {
                        tma_store_2d(type == 0 ? &tm_qo : &tm_ho, stg, col, rb * 128 + warp * 16);
                        tma_store_commit();
                    }
                } else if (type == 3) {
                    const int r = wg * 64 + wrow + g;
                    const int pos0 = (r >> 2) * 64 + rb * 4 + (r & 3), pos1 = pos0 + 128;
                    uint32_t* dst = reinterpret_cast<uint32_t*>(kv);
                    const uint32_t r00 = pack_bf16(a[0], a[1]), r01 = pack_bf16(a[4], a[5]);
                    const uint32_t r10 = pack_bf16(a[2], a[3]), r11 = pack_bf16(a[6], a[7]);
                    dst[(pos0 >> 4) * 128 + (pos0 & 15) * 4 + t] = r00;
                    dst[16384 + pos0 * 4 + t] = r01;
                    dst[(pos1 >> 4) * 128 + (pos1 & 15) * 4 + t] = r10;
                    dst[16384 + pos1 * 4 + t] = r11;
                    float m = fmaxf(fmaxf(fmaxf(fabsf(bf_lo(r00)), fabsf(bf_hi(r00))), fmaxf(fabsf(bf_lo(r01)), fabsf(bf_hi(r01)))),
                                    fmaxf(fmaxf(fabsf(bf_lo(r10)), fabsf(bf_hi(r10))), fmaxf(fabsf(bf_lo(r11)), fabsf(bf_hi(r11)))));
#pragma unroll
                    for (int o = 16; o > 0; o >>= 1) m = fmaxf(m, __shfl_xor_sync(0xffffffffu, m, o));
                    if (lane == 0) kvmax[128 + rb * 8 + warp] = m;
                } else {
                    float* kf = reinterpret_cast<float*>(smem_raw + 96 * 1024);
                    const int r = wg * 64 + wrow + g;
                    const int pos0 = (r >> 2) * 64 + rb * 4 + (r & 3), pos1 = pos0 + 128;
                    uint32_t* dst = reinterpret_cast<uint32_t*>(kv) + 32768;
                    dst[(pos0 >> 3) * 64 + (pos0 & 7) * 4 + t] = pack_bf16(a[0], a[1]);
                    dst[(pos0 >> 3) * 64 + 32 + (pos0 & 7) * 4 + t] = pack_bf16(a[4], a[5]);
                    dst[(pos1 >> 3) * 64 + (pos1 & 7) * 4 + t] = pack_bf16(a[2], a[3]);
                    dst[(pos1 >> 3) * 64 + 32 + (pos1 & 7) * 4 + t] = pack_bf16(a[6], a[7]);
                    kf[r * 17 + 2 * t] = a[0]; kf[r * 17 + 2 * t + 1] = a[1];
                    kf[r * 17 + 8 + 2 * t] = a[4]; kf[r * 17 + 8 + 2 * t + 1] = a[5];
                    kf[(r + 8) * 17 + 2 * t] = a[2]; kf[(r + 8) * 17 + 2 * t + 1] = a[3];
                    kf[(r + 8) * 17 + 8 + 2 * t] = a[6]; kf[(r + 8) * 17 + 8 + 2 * t + 1] = a[7];
                    named_bar_sync(1, 256);
                    if (tid < 64) {
                        const int i = tid >> 4, dim = tid & 15;
                        const int c = rb * 4 + i;
                        const int inner = (dim >> 3) * 64 + (c & 7) * 8 + (dim & 7);
                        float kt = 0.f;
#pragma unroll 8
                        for (int j = 0; j < 32; j++) {
                            const __nv_bfloat16 d = __float2bfloat16_rn(kf[(j * 4 + i) * 17 + dim] - kt);
                            kt += __bfloat162float(d);
                            kf[(j * 4 + i) * 17 + dim] = kt;
                            const int grp8 = j * 8 + (c >> 3);
                            kv[(grp8 < 128 ? grp8 * 256 + 128 : 49152 + (grp8 - 128) * 128) + inner] = d;
                        }
                    }
                    named_bar_sync(1, 256);
                    if (tid < 128) {
                        float n = 0.f;
#pragma unroll
                        for (int d = 0; d < 16; d++) { const float v = kf[tid * 17 + d]; n += v * v; }
                        if (!(n == n)) n = __int_as_float(0x7f800000);
#pragma unroll
                        for (int o = 8; o > 0; o >>= 1) n = fmaxf(n, __shfl_xor_sync(0xffffffffu, n, o));
                        if ((lane & 15) == 0) kvmax[rb * 8 + (tid >> 4)] = n;
                    }
                }
            }
        }
        if (tid == 0) DEV_STAMP(0, 3);
        if (lane == 0) tma_store_wait();
        if (tid == 0) DEV_STAMP(0, 4);
    }
}

constexpr int AT_KT = 64;
constexpr int AT_NCHUNK = 8;
constexpr int AT_NSTEP = S_LEN / AT_KT;
constexpr int AT_SPC = AT_NSTEP / AT_NCHUNK;
constexpr int AT_ONES = 131072;
constexpr int F2_STAGES = 4;
constexpr int F2_STAGE_BYTES = 8192 + 16384;
constexpr int F2_BASE = 132096;
constexpr int F2_NK = F_DIM / 64;
constexpr int AT_BAR = F2_BASE + F2_STAGES * F2_STAGE_BYTES;
constexpr int AT_SMEM = AT_BAR + 256;
#define AT_SWMASK_V 0xB6DB
constexpr uint32_t AT_SWMASK = AT_SWMASK_V;

#define AT_MAGIC (383.0f + 0.00390625f - 0.5849625f)
__device__ __forceinline__ uint32_t exp2_pair_alu(float t0, float t1) {
    uint32_t y;
    asm("prmt.b32 %0, %1, %2, 0x6521;" : "=r"(y) : "f"(t0), "f"(t1));
    const uint32_t e = y & 0x7F807F80u;
    uint32_t uh, p;
    asm("lop3.b32 %0, %1, %2, 0x3F003F00, 0xBE;" : "=r"(uh) : "r"(y), "r"(e));
    asm("fma.rn.bf16x2 %0, %1, %2, %3;" : "=r"(p) : "r"(uh), "r"(y), "r"(e));
    return p;
}

__device__ __forceinline__ void at_load_chunk(uint32_t sbase, const __nv_bfloat16* KV, uint32_t bar0, int c) {
    const uint8_t* src = reinterpret_cast<const uint8_t*>(KV);
    const uint32_t off = c < 4 ? c * 16384 : 98304 + (c - 4) * 8192, bytes = c < 4 ? 16384 : 8192;
    mbar_expect_tx(bar0 + 8 * c, bytes + 4096);
    bulk_g2s(sbase + off, src + off, bytes, bar0 + 8 * c);
    bulk_g2s(sbase + 65536 + c * 4096, src + 65536 + c * 4096, 4096, bar0 + 8 * c);
}

__device__ __forceinline__ void at_store(const float* o, __nv_bfloat16* O, int row, int lane) {
    const float l0 = __shfl_sync(0xffffffffu, o[8], lane & ~3);
    const float l1 = __shfl_sync(0xffffffffu, o[10], lane & ~3);
    const float r0 = __fdividef(1.0f, l0), r1 = __fdividef(1.0f, l1);
    const int t = lane & 3;
    uint32_t* op = reinterpret_cast<uint32_t*>(O + (size_t)(row + (lane >> 2)) * 16);
    op[t] = pack_bf16(o[0] * r0, o[1] * r0);
    op[t + 4] = pack_bf16(o[4] * r0, o[5] * r0);
    op[64 + t] = pack_bf16(o[2] * r1, o[3] * r1);
    op[64 + t + 4] = pack_bf16(o[6] * r1, o[7] * r1);
}

__device__ __forceinline__ void mma16816(float* c, const uint32_t* a, uint32_t b0, uint32_t b1) {
    asm volatile("mma.sync.aligned.m16n8k16.row.col.f32.bf16.bf16.f32 {%0,%1,%2,%3}, {%4,%5,%6,%7}, {%8,%9}, {%0,%1,%2,%3};"
                 : "+f"(c[0]), "+f"(c[1]), "+f"(c[2]), "+f"(c[3]) : "r"(a[0]), "r"(a[1]), "r"(a[2]), "r"(a[3]), "r"(b0), "r"(b1));
}
__device__ __forceinline__ void attn_fallback(const __nv_bfloat16* Q, const __nv_bfloat16* KV, __nv_bfloat16* O, uint32_t sbase) {
    const int tid = threadIdx.x;
    const int lane = tid & 31, g = lane >> 2, t = lane & 3;
    const uint32_t* Kg = reinterpret_cast<const uint32_t*>(KV + 65536);
#pragma unroll 1
    for (int mt = 0; mt < 2; mt++) {
        const int row = blockIdx.x * 512 + (tid >> 7) * 128 + mt * 64 + ((tid >> 5) & 3) * 16;
        const uint32_t* qp = reinterpret_cast<const uint32_t*>(Q + (size_t)(row + g) * 16);
        const uint32_t q[4] = {qp[t], qp[64 + t], qp[t + 4], qp[64 + t + 4]};
        float o[12];
#pragma unroll
        for (int i = 0; i < 12; i++) o[i] = 0.f;
        float m0 = -INFINITY, m1 = -INFINITY;
#pragma unroll 1
        for (int kt = 0; kt < S_LEN / 16; kt++) {
            float s[8];
#pragma unroll
            for (int i = 0; i < 8; i++) s[i] = 0.f;
#pragma unroll
            for (int h = 0; h < 2; h++) {
                const uint32_t* kp = Kg + (kt * 2 + h) * 64 + g * 4 + t;
                mma16816(s + 4 * h, q, kp[0], kp[32]);
            }
            float x0 = fmaxf(fmaxf(s[0], s[1]), fmaxf(s[4], s[5])), x1 = fmaxf(fmaxf(s[2], s[3]), fmaxf(s[6], s[7]));
            x0 = fmaxf(x0, __shfl_xor_sync(0xffffffffu, x0, 1)); x0 = fmaxf(x0, __shfl_xor_sync(0xffffffffu, x0, 2));
            x1 = fmaxf(x1, __shfl_xor_sync(0xffffffffu, x1, 1)); x1 = fmaxf(x1, __shfl_xor_sync(0xffffffffu, x1, 2));
            x0 = fmaxf(x0, m0); x1 = fmaxf(x1, m1);
            const float f0 = ex2(m0 - x0), f1 = ex2(m1 - x1);
            m0 = x0; m1 = x1;
#pragma unroll
            for (int j = 0; j < 3; j++) { o[4 * j] *= f0; o[4 * j + 1] *= f0; o[4 * j + 2] *= f1; o[4 * j + 3] *= f1; }
            const uint32_t p[4] = {pack_bf16(ex2(s[0] - m0), ex2(s[1] - m0)), pack_bf16(ex2(s[2] - m1), ex2(s[3] - m1)),
                                   pack_bf16(ex2(s[4] - m0), ex2(s[5] - m0)), pack_bf16(ex2(s[6] - m1), ex2(s[7] - m1))};
#pragma unroll
            for (int j = 0; j < 3; j++) {
                const uint32_t base = sbase + (j == 0 ? kt * 512 : j == 1 ? 65536 + kt * 256 : AT_ONES) + (lane & 15) * 16;
                uint32_t b0, b1;
                asm volatile("ldmatrix.sync.aligned.m8n8.x2.trans.shared.b16 {%0,%1}, [%2];" : "=r"(b0), "=r"(b1) : "r"(base));
                mma16816(o + 4 * j, p, b0, b1);
            }
        }
        at_store(o, O, row, lane);
    }
}

__global__ void __launch_bounds__(640, 1)
k2_attn(const __grid_constant__ CUtensorMap tm_h, const __grid_constant__ CUtensorMap tm_w2,
        const __nv_bfloat16* __restrict__ Q, const __nv_bfloat16* __restrict__ KV, const float* __restrict__ kvmax,
        const __nv_bfloat16* __restrict__ b2, __nv_bfloat16* __restrict__ O, __nv_bfloat16* __restrict__ G,
        uint2* __restrict__ rowstat, uint2* __restrict__ colpart) {
    extern __shared__ __align__(1024) uint8_t smem_raw[];
    const uint32_t sbase = smem_u32(smem_raw);
    const uint32_t bar0 = sbase + AT_BAR, f2_full = bar0 + 64, f2_empty = f2_full + 64;
    const int tid = threadIdx.x;
    const int wg = __shfl_sync(0xffffffffu, tid >> 7, 0);
    const int warp = (tid >> 5) & 3, lane = tid & 31;
    const int g = lane >> 2, t = lane & 3;
    if (tid == 0) DEV_STAMP(1, 0);
    if (tid == 0) {
        for (int i = 0; i < AT_NCHUNK; i++) mbar_init(bar0 + 8 * i, 1);
        for (int i = 0; i < F2_STAGES; i++) { mbar_init(f2_full + 8 * i, 1); mbar_init(f2_empty + 8 * i, 4); }
        mbar_init_fence();
    }
    if (tid < 16) asm volatile("st.shared.v4.b32 [%0], {%1,%2,%2,%2};" ::"r"(sbase + AT_ONES + tid * 16), "r"(0x00003F80u), "r"(0u) : "memory");
    fence_proxy_async();
    __syncthreads();

    if (wg == 4) {
        const int rb = blockIdx.x >> 2, cb = blockIdx.x & 3;
        const uint32_t fb = sbase + F2_BASE;
        const bool leader = tid == 512;
        if (leader) {
#pragma unroll
            for (int s = 0; s < F2_STAGES; s++) {
                mbar_expect_tx(f2_full + 8 * s, F2_STAGE_BYTES);
                tma_load_2d(fb + s * F2_STAGE_BYTES + 8192, &tm_w2, cb * 128, s * 64, f2_full + 8 * s);
                tma_load_2d(fb + s * F2_STAGE_BYTES + 16384, &tm_w2, cb * 128 + 64, s * 64, f2_full + 8 * s);
            }
            pdl_wait();
#pragma unroll
            for (int s = 0; s < F2_STAGES; s++) tma_load_2d(fb + s * F2_STAGE_BYTES, &tm_h, s * 64, rb * 64, f2_full + 8 * s);
        }
        __syncwarp();
        const uint64_t dA0 = make_desc(fb, 16, 1024, 1);
        const uint64_t dB0 = make_desc(fb + 8192, 8192, 1024, 1);
        float acc[64];
#pragma unroll
        for (int i = 0; i < 64; i++) asm volatile("mov.f32 %0, 0f00000000;" : "=f"(acc[i]));
#pragma unroll 1
        for (int ks = 0; ks < F2_NK; ks++) {
            const int s = ks % F2_STAGES;
            mbar_wait(f2_full + 8 * s, (ks / F2_STAGES) & 1);
            wg_fence();
#pragma unroll
            for (int kk = 0; kk < 4; kk++)
                wgmma_ss_n128_tb(acc, dA0 + (uint64_t)((s * F2_STAGE_BYTES + kk * 32) >> 4),
                                 dB0 + (uint64_t)((s * F2_STAGE_BYTES + kk * 2048) >> 4), 1);
            wg_commit();
            wg_wait<1>();
            if (ks > 0 && ks - 1 + F2_STAGES < F2_NK) {
                const int ps = (ks - 1) % F2_STAGES, k0 = (ks - 1 + F2_STAGES) * 64;
                if (lane == 0) mbar_arrive(f2_empty + 8 * ps);
                if (leader) {
                    mbar_wait(f2_empty + 8 * ps, ((ks - 1) / F2_STAGES) & 1);
                    mbar_expect_tx(f2_full + 8 * ps, F2_STAGE_BYTES);
                    tma_load_2d(fb + ps * F2_STAGE_BYTES, &tm_h, k0, rb * 64, f2_full + 8 * ps);
                    tma_load_2d(fb + ps * F2_STAGE_BYTES + 8192, &tm_w2, cb * 128, k0, f2_full + 8 * ps);
                    tma_load_2d(fb + ps * F2_STAGE_BYTES + 16384, &tm_w2, cb * 128 + 64, k0, f2_full + 8 * ps);
                }
                __syncwarp();
            }
        }
        wg_wait<0>();
        fence_regs<64>(acc);
        uint32_t* gp = reinterpret_cast<uint32_t*>(G + (size_t)(rb * 64 + warp * 16 + g) * D_MODEL + cb * 128) + t;
#pragma unroll
        for (int j = 0; j < 16; j++) {
            const uint32_t bb = __ldg(reinterpret_cast<const uint32_t*>(b2 + cb * 128 + j * 8) + t);
            const float b0 = bf_lo(bb), b1v = bf_hi(bb);
            const float z0 = acc[4 * j] + b0, z1 = acc[4 * j + 1] + b1v, z2 = acc[4 * j + 2] + b0, z3 = acc[4 * j + 3] + b1v;
            gp[j * 4] = pack_bf16(__fdividef(z0, 1.0f + __expf(-z0)), __fdividef(z1, 1.0f + __expf(-z1)));
            gp[j * 4 + 8 * (D_MODEL / 2)] = pack_bf16(__fdividef(z2, 1.0f + __expf(-z2)), __fdividef(z3, 1.0f + __expf(-z3)));
        }
        if (leader) DEV_STAMP(1, 5);
        return;
    }

    pdl_wait();
    pdl_launch();
    if (tid == 0) DEV_STAMP(1, 1);
    if (tid == 0) { at_load_chunk(sbase, KV, bar0, 0); at_load_chunk(sbase, KV, bar0, 1); at_load_chunk(sbase, KV, bar0, 2); }
    if (tid >= 128 && tid < 288) colpart[blockIdx.x * 160 + tid - 128] = make_uint2(NOT_READY, NOT_READY);
    if (tid >= 288 && tid < 304) rowstat[blockIdx.x * 16 + tid - 288] = make_uint2(NOT_READY, NOT_READY);
    const int rowA = blockIdx.x * 512 + wg * 128 + warp * 16;
    const uint32_t* qp = reinterpret_cast<const uint32_t*>(Q + (size_t)(rowA + g) * 16);
    const uint32_t lo0 = ((sbase & 0x3FFFF) >> 4) | (8u << 16);

#define AT_EXP(P) _Pragma("unroll") for (int i = 0; i < AT_KT / 4; i++) {                       \
                if ((AT_SWMASK >> (i & 15)) & 1) P[i] = exp2_pair_alu(s[2 * i], s[2 * i + 1]);  \
                else P[i] = pack_bf16(ex2(s[2 * i]), ex2(s[2 * i + 1])); }
#define AT_PV(P, st) _Pragma("unroll") for (int j = 0; j < AT_KT / 16; j++)                     \
                wgmma_pv(o, P[4 * j], P[4 * j + 1], P[4 * j + 2], P[4 * j + 3],                 \
                         desc64(vlo + ((st) * 4 + j) * 32, vhi - ((st) * 4 + j) * 16));
#define AT_PIPE 0
#define AT_STEP(st, PC, PN, klo, khi) {                                                         \
                wg_wait<0>();                                                                   \
                fence_regs<AT_KT / 2>(s);                                                       \
                AT_EXP(p0);                                                                     \
                if (st == AT_SPC - 1 && mt == 0) mbar_wait(bar0 + 8 * (c + 1), 0);              \
                wg_fence();                                                                     \
                wgmma_qk_acc_n64(s, q, desc64(klo, khi));                                       \
                AT_PV(p0, st);                                                                  \
                wg_commit(); }

#pragma unroll 1
    for (int mt = 0; mt < 2; mt++) {
        uint32_t q[4];
        q[0] = qp[mt * 512 + t]; q[2] = qp[mt * 512 + t + 4]; q[1] = qp[mt * 512 + 64 + t]; q[3] = qp[mt * 512 + 64 + t + 4];
        float o[12];
#pragma unroll
        for (int i = 0; i < 12; i++) asm volatile("mov.f32 %0, 0f00000000;" : "=f"(o[i]));
        float s[AT_KT / 2];
        uint32_t p0[AT_KT / 4], p1[AT_KT / 4];
        (void)p1;
#pragma unroll
        for (int i = 0; i < AT_KT / 2; i++) {
            if ((AT_SWMASK >> ((i >> 1) & 15)) & 1) asm volatile("mov.f32 %0, %1;" : "=f"(s[i]) : "f"(AT_MAGIC));
            else asm volatile("mov.f32 %0, 0f00000000;" : "=f"(s[i]));
        }
        if (mt == 0) mbar_wait(bar0, 0);
        if (tid == 0) DEV_STAMP(1, 2 + mt);
        uint32_t klo = lo0 + 16, vlo = lo0, vhi = 4096;
        wg_fence();
        wgmma_qk_acc_n64(s, q, desc64(klo, 32));
        wg_commit();
        uint32_t kst = 256, khi = 32;
#pragma unroll 1
        for (int c = 0; c < AT_NCHUNK - 1; c++) {
            if (tid == 0 && mt == 0 && c + 3 < AT_NCHUNK) at_load_chunk(sbase, KV, bar0, c + 3);
            AT_STEP(0, p0, p1, klo + kst, khi); AT_STEP(1, p1, p0, klo + 2 * kst, khi); AT_STEP(2, p0, p1, klo + 3 * kst, khi);
            if (c == 3) { klo = lo0 + (98304 >> 4); kst = 128; khi = 16; } else klo += 4 * kst;
            AT_STEP(3, p1, p0, klo, khi);
            vlo += 512; vhi -= 256;
        }
        {
            const int c = 0; (void)c;
            AT_STEP(0, p0, p1, klo + 128, 16); AT_STEP(1, p1, p0, klo + 256, 16); AT_STEP(2, p0, p1, klo + 384, 16);
            wg_wait<0>();
            fence_regs<AT_KT / 2>(s);
            AT_EXP(p0);
            wg_fence();
            AT_PV(p0, 3);
            wg_commit();
            wg_wait<0>();
            fence_regs<12>(o);
        }
        at_store(o, O, rowA + mt * 64, lane);
    }
    if (tid == 0) DEV_STAMP(1, 4);

    bool unsafe;
    {
        float km = fmaxf(fmaxf(kvmax[lane], kvmax[lane + 32]), fmaxf(kvmax[lane + 64], kvmax[lane + 96]));
        float vm = fmaxf(fmaxf(kvmax[128 + lane], kvmax[160 + lane]), fmaxf(kvmax[192 + lane], kvmax[224 + lane]));
#pragma unroll
        for (int o = 16; o > 0; o >>= 1) { km = fmaxf(km, __shfl_xor_sync(0xffffffffu, km, o)); vm = fmaxf(vm, __shfl_xor_sync(0xffffffffu, vm, o)); }
        const uint4* qr = reinterpret_cast<const uint4*>(Q + (size_t)(rowA + (lane >> 4) * 64 + (lane & 15)) * 16);
        const uint4 qa = qr[0], qb = qr[1];
        const uint32_t qw[8] = {qa.x, qa.y, qa.z, qa.w, qb.x, qb.y, qb.z, qb.w};
        float qn = 0.f;
#pragma unroll
        for (int i = 0; i < 8; i++) qn += bf_lo(qw[i]) * bf_lo(qw[i]) + bf_hi(qw[i]) * bf_hi(qw[i]);
        const bool ok = (qn * km <= 3600.0f) && (vm <= 1.0e12f);
        unsafe = __any_sync(0xffffffffu, !ok);
    }
    if (!unsafe) return;

    attn_fallback(Q, KV, O, sbase);
}

constexpr int K3_STAGE_BYTES = 16384 + 8192;
constexpr int K3_X = 8 * K3_STAGE_BYTES;
constexpr int K3_G = K3_X + 16384;
constexpr int K3_SMEM = K3_G + 16384 + 256;

__global__ void __launch_bounds__(256, 1)
k3_out(const __grid_constant__ CUtensorMap tm_o, const __grid_constant__ CUtensorMap tm_wo,
       const __grid_constant__ CUtensorMap tm_x, const __grid_constant__ CUtensorMap tm_g,
       const __grid_constant__ CUtensorMap tm_out) {
    extern __shared__ __align__(1024) uint8_t smem_raw[];
    const uint32_t sbase = smem_u32(smem_raw);
    const uint32_t sX = sbase + K3_X, sG = sbase + K3_G;
    const uint32_t bar_full = sG + 16384, bar_x = bar_full + 64;
    const int tid = threadIdx.x, warp = __shfl_sync(0xffffffffu, tid >> 5, 0), lane = tid & 31;
    const int rb = blockIdx.x >> 3, cb = blockIdx.x & 7;
    if (tid == 0) {
        DEV_STAMP(2, 0);
        for (int s = 0; s < 8; s++) mbar_init(bar_full + 8 * s, 1);
        mbar_init(bar_x, 1);
        mbar_init_fence();
        for (int s = 0; s < 8; s++) {
            mbar_expect_tx(bar_full + 8 * s, K3_STAGE_BYTES);
            tma_load_2d(sbase + s * K3_STAGE_BYTES + 16384, &tm_wo, cb * 64, s * 64, bar_full + 8 * s);
        }
        mbar_expect_tx(bar_x, 32768);
        tma_load_2d(sX, &tm_x, cb * 64, rb * 128, bar_x);
        pdl_wait();
        DEV_STAMP(2, 1);
        for (int s = 0; s < 8; s++) tma_load_2d(sbase + s * K3_STAGE_BYTES, &tm_o, s * 64, rb * 128, bar_full + 8 * s);
        tma_load_2d(sG, &tm_g, cb * 64, rb * 128, bar_x);
    }
    __syncthreads();
    const int wg = warp >> 2;
    float acc[32];
#pragma unroll
    for (int i = 0; i < 32; i++) asm volatile("mov.f32 %0, 0f00000000;" : "=f"(acc[i]));
    const uint64_t dA0 = make_desc(sbase + wg * 8192, 16, 1024, 1);
    const uint64_t dB0 = make_desc(sbase + 16384, 8192, 1024, 1);
#pragma unroll 1
    for (int ks = 0; ks < 8; ks++) {
        mbar_wait(bar_full + 8 * ks, 0);
        wg_fence();
#pragma unroll
        for (int kk = 0; kk < 4; kk++)
            wgmma_ss_n64_tb(acc, dA0 + (uint64_t)((ks * K3_STAGE_BYTES + kk * 32) >> 4),
                            dB0 + (uint64_t)((ks * K3_STAGE_BYTES + kk * 2048) >> 4), 1);
        wg_commit();
    }
    wg_wait<0>();
    fence_regs<32>(acc);
    if (tid == 0) DEV_STAMP(2, 2);
    mbar_wait(bar_x, 0);
    const int g = lane >> 2, t = lane & 3;
    const int row0 = warp * 16 + g;
#pragma unroll
    for (int j = 0; j < 8; j++) {
#pragma unroll
        for (int h = 0; h < 2; h++) {
            const int row = row0 + h * 8;
            const uint32_t off = row * 128 + ((j ^ (row & 7)) << 4) + t * 4;
            uint32_t xv, gv;
            asm volatile("ld.shared.b32 %0, [%1];" : "=r"(xv) : "r"(sX + off) : "memory");
            asm volatile("ld.shared.b32 %0, [%1];" : "=r"(gv) : "r"(sG + off) : "memory");
            const uint32_t ov = pack_bf16(fmaf(acc[4 * j + 2 * h], bf_lo(gv), bf_lo(xv)), fmaf(acc[4 * j + 2 * h + 1], bf_hi(gv), bf_hi(xv)));
            asm volatile("st.shared.b32 [%0], %1;" ::"r"(sX + off), "r"(ov) : "memory");
        }
    }
    fence_proxy_async();
    __syncwarp();
    if (lane == 0) {
        tma_store_2d(&tm_out, sX + warp * 2048, cb * 64, rb * 128 + warp * 16);
        tma_store_commit();
        if (tid == 0) DEV_STAMP(2, 3);
        tma_store_wait();
        if (tid == 0) DEV_STAMP(2, 4);
    }
}

typedef CUresult (*EncodeFn)(CUtensorMap*, CUtensorMapDataType, cuuint32_t, void*, const cuuint64_t*, const cuuint64_t*,
                             const cuuint32_t*, const cuuint32_t*, CUtensorMapInterleave, CUtensorMapSwizzle,
                             CUtensorMapL2promotion, CUtensorMapFloatOOBfill);

struct HostState {
    bool ready;
    const void* key[11];
    CUtensorMap wq, wk, wv, w1, qo, ho, hi, oi, w2, wo, xi, gi, out;
    void *pQ, *pKV, *pH, *pO, *pMax, *pRow, *pCol, *pFlag, *pG;
};
HostState g_hs;

void make_map(EncodeFn fn, CUtensorMap* m, const void* ptr, uint64_t inner, uint64_t outer, uint32_t box_in, uint32_t box_out) {
    cuuint64_t dims[2] = {inner, outer};
    cuuint64_t strides[1] = {inner * 2};
    cuuint32_t box[2] = {box_in, box_out};
    cuuint32_t es[2] = {1, 1};
    fn(m, CU_TENSOR_MAP_DATA_TYPE_BFLOAT16, 2, const_cast<void*>(ptr), dims, strides, box, es, CU_TENSOR_MAP_INTERLEAVE_NONE,
       CU_TENSOR_MAP_SWIZZLE_128B, CU_TENSOR_MAP_L2_PROMOTION_L2_256B, CU_TENSOR_MAP_FLOAT_OOB_FILL_NONE);
}

template <typename... KArgs, typename... Args>
void launch(void (*kern)(KArgs...), int grid, int block, int smem, bool pdl, int cluster, Args... args) {
    cudaLaunchConfig_t cfg = {};
    cfg.gridDim = dim3(grid); cfg.blockDim = dim3(block); cfg.dynamicSmemBytes = smem; cfg.stream = cudaStreamPerThread;
    cudaLaunchAttribute at[2];
    int n = 0;
    if (pdl) { at[n].id = cudaLaunchAttributeProgrammaticStreamSerialization; at[n].val.programmaticStreamSerializationAllowed = 1; n++; }
    if (cluster > 1) { at[n].id = cudaLaunchAttributeClusterDimension; at[n].val.clusterDim.x = cluster; at[n].val.clusterDim.y = 1; at[n].val.clusterDim.z = 1; n++; }
    cfg.attrs = at; cfg.numAttrs = n;
    cudaLaunchKernelEx(&cfg, kern, KArgs(args)...);
}

}

extern "C" void kernel_launch(void* const* d_in, const int* in_sizes, int n_in, void* d_out, int out_size) {
    (void)in_sizes; (void)n_in; (void)out_size;
    HostState& hs = g_hs;
    bool same = hs.ready;
    for (int i = 0; i < 10 && same; i++) same = hs.key[i] == d_in[i];
    same = same && hs.key[10] == d_out;
    if (!same) {
        void* fp = nullptr;
        cudaDriverEntryPointQueryResult qr;
        cudaGetDriverEntryPoint("cuTensorMapEncodeTiled", &fp, cudaEnableDefault, &qr);
        EncodeFn fn = (EncodeFn)fp;
        cudaGetSymbolAddress(&hs.pQ, g_Q); cudaGetSymbolAddress(&hs.pKV, g_KV); cudaGetSymbolAddress(&hs.pH, g_H);
        cudaGetSymbolAddress(&hs.pO, g_O); cudaGetSymbolAddress(&hs.pMax, g_kvmax);
        cudaGetSymbolAddress(&hs.pRow, g_rowstat); cudaGetSymbolAddress(&hs.pCol, g_colpart); cudaGetSymbolAddress(&hs.pG, g_G);
        make_map(fn, &hs.wq, d_in[1], 512, 512, 64, 64);
        make_map(fn, &hs.wk, d_in[2], 16, 512, 64, 64);
        make_map(fn, &hs.wv, d_in[3], 16, 512, 64, 64);
        make_map(fn, &hs.w1, d_in[6], F_DIM, 512, 64, 64);
        make_map(fn, &hs.qo, hs.pQ, 512, S_LEN, 64, 16);
        make_map(fn, &hs.ho, hs.pH, F_DIM, S_LEN, 64, 16);
        make_map(fn, &hs.hi, hs.pH, F_DIM, S_LEN, 64, 64);
        make_map(fn, &hs.gi, hs.pG, 512, S_LEN, 64, 128);
        make_map(fn, &hs.oi, hs.pO, 512, S_LEN, 64, 128);
        make_map(fn, &hs.w2, d_in[8], 512, F_DIM, 64, 64);
        make_map(fn, &hs.wo, d_in[4], 512, 512, 64, 64);
        make_map(fn, &hs.xi, d_in[0], 512, S_LEN, 64, 128);
        make_map(fn, &hs.out, d_out, 512, S_LEN, 64, 16);
        cudaFuncSetAttribute(k1_proj, cudaFuncAttributeMaxDynamicSharedMemorySize, K1_SMEM);
        cudaFuncSetAttribute(k2_attn, cudaFuncAttributeMaxDynamicSharedMemorySize, AT_SMEM);
        cudaFuncSetAttribute(k3_out, cudaFuncAttributeMaxDynamicSharedMemorySize, K3_SMEM);
        for (int i = 0; i < 10; i++) hs.key[i] = d_in[i];
        hs.key[10] = d_out;
        hs.ready = true;
    }
    launch(k1_proj, 128, 384, K1_SMEM, false, 2, hs.xi, hs.wq, hs.wk, hs.wv, hs.w1, hs.qo, hs.ho, (const __nv_bfloat16*)d_in[0],
           (const __nv_bfloat16*)d_in[1], (const __nv_bfloat16*)d_in[2], (const __nv_bfloat16*)d_in[3], (const __nv_bfloat16*)d_in[6],
           (const __nv_bfloat16*)d_in[7], (float2*)hs.pRow, (float*)hs.pCol, (__nv_bfloat16*)hs.pKV, (float*)hs.pMax);
    launch(k2_attn, 128, 640, AT_SMEM, true, 1, hs.hi, hs.w2, (const __nv_bfloat16*)hs.pQ, (const __nv_bfloat16*)hs.pKV,
           (const float*)hs.pMax, (const __nv_bfloat16*)d_in[9], (__nv_bfloat16*)hs.pO, (__nv_bfloat16*)hs.pG, (uint2*)hs.pRow, (uint2*)hs.pCol);
    launch(k3_out, 128, 256, K3_SMEM, true, 1, hs.oi, hs.wo, hs.xi, hs.gi, hs.out);
}
```

```cpp
#include <cuda_runtime.h>
#include <cuda_bf16.h>
#include <cuda.h>
#include <stdint.h>

namespace {

constexpr int S_LEN = 2048, D_MODEL = 512, F_DIM = 1792;

__device__ __align__(1024) __nv_bfloat16 g_Q[S_LEN * D_MODEL];
__device__ __align__(1024) __nv_bfloat16 g_KV[6 * S_LEN * 8];
__device__ __align__(1024) __nv_bfloat16 g_G[S_LEN * D_MODEL];
__device__ __align__(1024) __nv_bfloat16 g_H[S_LEN * F_DIM];
__device__ __align__(1024) __nv_bfloat16 g_O[S_LEN * D_MODEL];
__device__ __align__(1024) float g_kvmax[256];
__device__ __align__(1024) float2 g_rowstat[S_LEN];
__device__ __align__(1024) float g_colpart[8 * 16 * 320];

#define DEV_STAMP(k, e) do {} while (0)
__device__ __forceinline__ uint32_t smem_u32(const void* p) { return (uint32_t)__cvta_generic_to_shared(p); }
__device__ __forceinline__ void wg_fence() { asm volatile("wgmma.fence.sync.aligned;" ::: "memory"); }
__device__ __forceinline__ void wg_commit() { asm volatile("wgmma.commit_group.sync.aligned;" ::: "memory"); }
template <int N> __device__ __forceinline__ void wg_wait() { asm volatile("wgmma.wait_group.sync.aligned %0;" ::"n"(N) : "memory"); }
template <int N> __device__ __forceinline__ void fence_regs(float* r) {
#pragma unroll
    for (int i = 0; i < N; i++) asm volatile("" : "+f"(r[i])::"memory");
}
__device__ __forceinline__ void fence_proxy_async() { asm volatile("fence.proxy.async.shared::cta;" ::: "memory"); }
__device__ __forceinline__ void mbar_init(uint32_t bar, int cnt) { asm volatile("mbarrier.init.shared::cta.b64 [%0], %1;" ::"r"(bar), "r"(cnt) : "memory"); }
__device__ __forceinline__ void mbar_init_fence() { asm volatile("fence.mbarrier_init.release.cluster;" ::: "memory"); }
__device__ __forceinline__ void mbar_expect_tx(uint32_t bar, uint32_t bytes) {
    asm volatile("mbarrier.arrive.expect_tx.shared::cta.b64 _, [%0], %1;" ::"r"(bar), "r"(bytes) : "memory");
}
__device__ __forceinline__ void mbar_arrive(uint32_t bar) { asm volatile("mbarrier.arrive.shared::cta.b64 _, [%0];" ::"r"(bar) : "memory"); }
__device__ __forceinline__ bool mbar_try(uint32_t bar, uint32_t parity) {
    uint32_t ok;
    asm volatile("{\n.reg .pred p;\nmbarrier.try_wait.parity.shared::cta.b64 p, [%1], %2;\nselp.u32 %0, 1, 0, p;\n}\n"
                 : "=r"(ok) : "r"(bar), "r"(parity) : "memory");
    return ok != 0;
}
__device__ __forceinline__ void mbar_wait(uint32_t bar, uint32_t parity) {
    if (mbar_try(bar, parity)) return;
    const long long t0 = clock64();
#pragma unroll 1
    while (!mbar_try(bar, parity)) {
        if (clock64() - t0 > 20000000ll) {
            break;
        }
    }
}
__device__ __forceinline__ void bulk_g2s(uint32_t dst, const void* src, uint32_t bytes, uint32_t bar) {
    asm volatile("cp.async.bulk.shared::cluster.global.mbarrier::complete_tx::bytes [%0], [%1], %2, [%3];"
                 ::"r"(dst), "l"(src), "r"(bytes), "r"(bar) : "memory");
}
__device__ __forceinline__ void tma_load_2d(uint32_t dst, const CUtensorMap* tm, int c0, int c1, uint32_t bar) {
    asm volatile("cp.async.bulk.tensor.2d.shared::cluster.global.mbarrier::complete_tx::bytes [%0], [%1, {%3, %4}], [%2];"
                 ::"r"(dst), "l"((uint64_t)tm), "r"(bar), "r"(c0), "r"(c1) : "memory");
}
__device__ __forceinline__ void tma_load_2d_mc(uint32_t dst, const CUtensorMap* tm, int c0, int c1, uint32_t bar, uint16_t mask) {
    asm volatile("cp.async.bulk.tensor.2d.shared::cluster.global.mbarrier::complete_tx::bytes.multicast::cluster [%0], [%1, {%3, %4}], [%2], %5;"
                 ::"r"(dst), "l"((uint64_t)tm), "r"(bar), "r"(c0), "r"(c1), "h"(mask) : "memory");
}
__device__ __forceinline__ void mbar_arrive_remote(uint32_t bar, uint32_t cta) {
    asm volatile("{\n.reg .b32 ra;\nmapa.shared::cluster.u32 ra, %0, %1;\nmbarrier.arrive.shared::cluster.b64 _, [ra];\n}\n"
                 ::"r"(bar), "r"(cta) : "memory");
}
__device__ __forceinline__ void cluster_sync_relaxed() {
    asm volatile("barrier.cluster.arrive.relaxed;\nbarrier.cluster.wait;" ::: "memory");
}
__device__ __forceinline__ uint2 ld_relaxed_v2(const void* p) {
    uint2 v; asm volatile("ld.relaxed.gpu.global.v2.b32 {%0,%1}, [%2];" : "=r"(v.x), "=r"(v.y) : "l"(p) : "memory"); return v;
}
constexpr uint32_t NOT_READY = 0u;
__device__ __forceinline__ float xch_enc(float v) { return __uint_as_float((v == 0.f ? 0u : __float_as_uint(v)) ^ 0x80000000u); }
__device__ __forceinline__ float xch_dec(uint32_t u) { return __uint_as_float(u ^ 0x80000000u); }
__device__ __forceinline__ void tma_store_2d(const CUtensorMap* tm, uint32_t src, int c0, int c1) {
    asm volatile("cp.async.bulk.tensor.2d.global.shared::cta.bulk_group [%0, {%2, %3}], [%1];"
                 ::"l"((uint64_t)tm), "r"(src), "r"(c0), "r"(c1) : "memory");
}
__device__ __forceinline__ void tma_store_commit() { asm volatile("cp.async.bulk.commit_group;" ::: "memory"); }
__device__ __forceinline__ void tma_store_wait() { asm volatile("cp.async.bulk.wait_group 0;" ::: "memory"); }
__device__ __forceinline__ void tma_prefetch_desc(const CUtensorMap* tm) { asm volatile("prefetch.tensormap [%0];" ::"l"((uint64_t)tm) : "memory"); }
__device__ __forceinline__ void named_bar_sync(int id, int n) { asm volatile("bar.sync %0, %1;" ::"r"(id), "r"(n) : "memory"); }
__device__ __forceinline__ void pdl_wait() { asm volatile("griddepcontrol.wait;" ::: "memory"); }
__device__ __forceinline__ void pdl_launch() { asm volatile("griddepcontrol.launch_dependents;" ::: "memory"); }
template <int N> __device__ __forceinline__ void reg_alloc() { asm volatile("setmaxnreg.inc.sync.aligned.u32 %0;" ::"n"(N)); }
template <int N> __device__ __forceinline__ void reg_dealloc() { asm volatile("setmaxnreg.dec.sync.aligned.u32 %0;" ::"n"(N)); }
__device__ __forceinline__ float ex2(float x) { float y; asm("ex2.approx.ftz.f32 %0, %1;" : "=f"(y) : "f"(x)); return y; }
__device__ __forceinline__ uint32_t pack_bf16(float lo, float hi) {
    uint32_t r; asm("cvt.rn.bf16x2.f32 %0, %1, %2;" : "=r"(r) : "f"(hi), "f"(lo)); return r;
}
__device__ __forceinline__ uint32_t pack_bf16_relu(float lo, float hi) {
    uint32_t r; asm("cvt.rn.relu.bf16x2.f32 %0, %1, %2;" : "=r"(r) : "f"(hi), "f"(lo)); return r;
}
__device__ __forceinline__ uint32_t mul_bf16x2(uint32_t a, uint32_t b) {
    uint32_t r; asm("mul.rn.bf16x2 %0, %1, %2;" : "=r"(r) : "r"(a), "r"(b)); return r;
}
__device__ __forceinline__ float bf_lo(uint32_t v) { return __uint_as_float(v << 16); }
__device__ __forceinline__ float bf_hi(uint32_t v) { return __uint_as_float(v & 0xFFFF0000u); }
__device__ __forceinline__ void stmatrix_x4(uint32_t addr, uint32_t r0, uint32_t r1, uint32_t r2, uint32_t r3) {
    asm volatile("stmatrix.sync.aligned.m8n8.x4.shared.b16 [%0], {%1,%2,%3,%4};" ::"r"(addr), "r"(r0), "r"(r1), "r"(r2), "r"(r3) : "memory");
}
__device__ __forceinline__ uint64_t make_desc(uint32_t addr, uint32_t lbo, uint32_t sbo, uint32_t swz) {
    return (uint64_t)((addr & 0x3FFFF) >> 4) | ((uint64_t)(lbo >> 4) << 16) | ((uint64_t)(sbo >> 4) << 32) | ((uint64_t)swz << 62);
}

__device__ __forceinline__ uint64_t desc64(uint32_t lo, uint32_t hi) {
    uint64_t d; asm("mov.b64 %0, {%1, %2};" : "=l"(d) : "r"(lo), "r"(hi)); return d;
}

__device__ __forceinline__ void wgmma_ss_n256_tb(float* d, uint64_t descA, uint64_t descB, int scaleD) {
    asm volatile("{\n.reg .pred p;\nsetp.ne.b32 p, %130, 0;\n"
      "wgmma.mma_async.sync.aligned.m64n256k16.f32.bf16.bf16 {%0,%1,%2,%3,%4,%5,%6,%7,%8,%9,%10,%11,%12,%13,%14,%15,%16,%17,%18,%19,%20,%21,%22,%23,%24,%25,%26,%27,%28,%29,%30,%31,%32,%33,%34,%35,%36,%37,%38,%39,%40,%41,%42,%43,%44,%45,%46,%47,%48,%49,%50,%51,%52,%53,%54,%55,%56,%57,%58,%59,%60,%61,%62,%63,%64,%65,%66,%67,%68,%69,%70,%71,%72,%73,%74,%75,%76,%77,%78,%79,%80,%81,%82,%83,%84,%85,%86,%87,%88,%89,%90,%91,%92,%93,%94,%95,%96,%97,%98,%99,%100,%101,%102,%103,%104,%105,%106,%107,%108,%109,%110,%111,%112,%113,%114,%115,%116,%117,%118,%119,%120,%121,%122,%123,%124,%125,%126,%127}, %128, %129, p, 1, 1, 0, 1;\n}\n"
      : "+f"(d[0]), "+f"(d[1]), "+f"(d[2]), "+f"(d[3]), "+f"(d[4]), "+f"(d[5]), "+f"(d[6]), "+f"(d[7]), "+f"(d[8]), "+f"(d[9]), "+f"(d[10]), "+f"(d[11]), "+f"(d[12]), "+f"(d[13]), "+f"(d[14]), "+f"(d[15]), "+f"(d[16]), "+f"(d[17]), "+f"(d[18]), "+f"(d[19]), "+f"(d[20]), "+f"(d[21]), "+f"(d[22]), "+f"(d[23]), "+f"(d[24]), "+f"(d[25]), "+f"(d[26]), "+f"(d[27]), "+f"(d[28]), "+f"(d[29]), "+f"(d[30]), "+f"(d[31]), "+f"(d[32]), "+f"(d[33]), "+f"(d[34]), "+f"(d[35]), "+f"(d[36]), "+f"(d[37]), "+f"(d[38]), "+f"(d[39]), "+f"(d[40]), "+f"(d[41]), "+f"(d[42]), "+f"(d[43]), "+f"(d[44]), "+f"(d[45]), "+f"(d[46]), "+f"(d[47]), "+f"(d[48]), "+f"(d[49]), "+f"(d[50]), "+f"(d[51]), "+f"(d[52]), "+f"(d[53]), "+f"(d[54]), "+f"(d[55]), "+f"(d[56]), "+f"(d[57]), "+f"(d[58]), "+f"(d[59]), "+f"(d[60]), "+f"(d[61]), "+f"(d[62]), "+f"(d[63]), "+f"(d[64]), "+f"(d[65]), "+f"(d[66]), "+f"(d[67]), "+f"(d[68]), "+f"(d[69]), "+f"(d[70]), "+f"(d[71]), "+f"(d[72]), "+f"(d[73]), "+f"(d[74]), "+f"(d[75]), "+f"(d[76]), "+f"(d[77]), "+f"(d[78]), "+f"(d[79]), "+f"(d[80]), "+f"(d[81]), "+f"(d[82]), "+f"(d[83]), "+f"(d[84]), "+f"(d[85]), "+f"(d[86]), "+f"(d[87]), "+f"(d[88]), "+f"(d[89]), "+f"(d[90]), "+f"(d[91]), "+f"(d[92]), "+f"(d[93]), "+f"(d[94]), "+f"(d[95]), "+f"(d[96]), "+f"(d[97]), "+f"(d[98]), "+f"(d[99]), "+f"(d[100]), "+f"(d[101]), "+f"(d[102]), "+f"(d[103]), "+f"(d[104]), "+f"(d[105]), "+f"(d[106]), "+f"(d[107]), "+f"(d[108]), "+f"(d[109]), "+f"(d[110]), "+f"(d[111]), "+f"(d[112]), "+f"(d[113]), "+f"(d[114]), "+f"(d[115]), "+f"(d[116]), "+f"(d[117]), "+f"(d[118]), "+f"(d[119]), "+f"(d[120]), "+f"(d[121]), "+f"(d[122]), "+f"(d[123]), "+f"(d[124]), "+f"(d[125]), "+f"(d[126]), "+f"(d[127])
      : "l"(descA), "l"(descB), "r"(scaleD));
}
__device__ __forceinline__ void wgmma_ss_n128_tb(float* d, uint64_t descA, uint64_t descB, int scaleD) {
    asm volatile("{\n.reg .pred p;\nsetp.ne.b32 p, %66, 0;\n"
      "wgmma.mma_async.sync.aligned.m64n128k16.f32.bf16.bf16 {%0,%1,%2,%3,%4,%5,%6,%7,%8,%9,%10,%11,%12,%13,%14,%15,%16,%17,%18,%19,%20,%21,%22,%23,%24,%25,%26,%27,%28,%29,%30,%31,%32,%33,%34,%35,%36,%37,%38,%39,%40,%41,%42,%43,%44,%45,%46,%47,%48,%49,%50,%51,%52,%53,%54,%55,%56,%57,%58,%59,%60,%61,%62,%63}, %64, %65, p, 1, 1, 0, 1;\n}\n"
      : "+f"(d[0]), "+f"(d[1]), "+f"(d[2]), "+f"(d[3]), "+f"(d[4]), "+f"(d[5]), "+f"(d[6]), "+f"(d[7]), "+f"(d[8]), "+f"(d[9]), "+f"(d[10]), "+f"(d[11]), "+f"(d[12]), "+f"(d[13]), "+f"(d[14]), "+f"(d[15]), "+f"(d[16]), "+f"(d[17]), "+f"(d[18]), "+f"(d[19]), "+f"(d[20]), "+f"(d[21]), "+f"(d[22]), "+f"(d[23]), "+f"(d[24]), "+f"(d[25]), "+f"(d[26]), "+f"(d[27]), "+f"(d[28]), "+f"(d[29]), "+f"(d[30]), "+f"(d[31]), "+f"(d[32]), "+f"(d[33]), "+f"(d[34]), "+f"(d[35]), "+f"(d[36]), "+f"(d[37]), "+f"(d[38]), "+f"(d[39]), "+f"(d[40]), "+f"(d[41]), "+f"(d[42]), "+f"(d[43]), "+f"(d[44]), "+f"(d[45]), "+f"(d[46]), "+f"(d[47]), "+f"(d[48]), "+f"(d[49]), "+f"(d[50]), "+f"(d[51]), "+f"(d[52]), "+f"(d[53]), "+f"(d[54]), "+f"(d[55]), "+f"(d[56]), "+f"(d[57]), "+f"(d[58]), "+f"(d[59]), "+f"(d[60]), "+f"(d[61]), "+f"(d[62]), "+f"(d[63])
      : "l"(descA), "l"(descB), "r"(scaleD));
}
__device__ __forceinline__ void wgmma_ss_n64_tb(float* d, uint64_t descA, uint64_t descB, int scaleD) {
    asm volatile("{\n.reg .pred p;\nsetp.ne.b32 p, %34, 0;\n"
      "wgmma.mma_async.sync.aligned.m64n64k16.f32.bf16.bf16 {%0,%1,%2,%3,%4,%5,%6,%7,%8,%9,%10,%11,%12,%13,%14,%15,%16,%17,%18,%19,%20,%21,%22,%23,%24,%25,%26,%27,%28,%29,%30,%31}, %32, %33, p, 1, 1, 0, 1;\n}\n"
      : "+f"(d[0]), "+f"(d[1]), "+f"(d[2]), "+f"(d[3]), "+f"(d[4]), "+f"(d[5]), "+f"(d[6]), "+f"(d[7]), "+f"(d[8]), "+f"(d[9]), "+f"(d[10]), "+f"(d[11]), "+f"(d[12]), "+f"(d[13]), "+f"(d[14]), "+f"(d[15]), "+f"(d[16]), "+f"(d[17]), "+f"(d[18]), "+f"(d[19]), "+f"(d[20]), "+f"(d[21]), "+f"(d[22]), "+f"(d[23]), "+f"(d[24]), "+f"(d[25]), "+f"(d[26]), "+f"(d[27]), "+f"(d[28]), "+f"(d[29]), "+f"(d[30]), "+f"(d[31])
      : "l"(descA), "l"(descB), "r"(scaleD));
}
__device__ __forceinline__ void wgmma_qk_acc_n64(float* d, const uint32_t* a, uint64_t descB) {
    asm volatile("wgmma.mma_async.sync.aligned.m64n64k16.f32.bf16.bf16 {%0,%1,%2,%3,%4,%5,%6,%7,%8,%9,%10,%11,%12,%13,%14,%15,%16,%17,%18,%19,%20,%21,%22,%23,%24,%25,%26,%27,%28,%29,%30,%31}, {%32,%33,%34,%35}, %36, 1, 1, 1, 0;\n"
      : "+f"(d[0]), "+f"(d[1]), "+f"(d[2]), "+f"(d[3]), "+f"(d[4]), "+f"(d[5]), "+f"(d[6]), "+f"(d[7]), "+f"(d[8]), "+f"(d[9]), "+f"(d[10]), "+f"(d[11]), "+f"(d[12]), "+f"(d[13]), "+f"(d[14]), "+f"(d[15]), "+f"(d[16]), "+f"(d[17]), "+f"(d[18]), "+f"(d[19]), "+f"(d[20]), "+f"(d[21]), "+f"(d[22]), "+f"(d[23]), "+f"(d[24]), "+f"(d[25]), "+f"(d[26]), "+f"(d[27]), "+f"(d[28]), "+f"(d[29]), "+f"(d[30]), "+f"(d[31])
      : "r"(a[0]), "r"(a[1]), "r"(a[2]), "r"(a[3]), "l"(descB));
}

__device__ __forceinline__ void wgmma_pv(float* d, uint32_t a0, uint32_t a1, uint32_t a2, uint32_t a3, uint64_t descB) {
    asm volatile("wgmma.mma_async.sync.aligned.m64n24k16.f32.bf16.bf16 {%0,%1,%2,%3,%4,%5,%6,%7,%8,%9,%10,%11}, {%12,%13,%14,%15}, %16, 1, 1, 1, 1;\n"
                 : "+f"(d[0]), "+f"(d[1]), "+f"(d[2]), "+f"(d[3]), "+f"(d[4]), "+f"(d[5]), "+f"(d[6]), "+f"(d[7]), "+f"(d[8]), "+f"(d[9]), "+f"(d[10]), "+f"(d[11])
                 : "r"(a0), "r"(a1), "r"(a2), "r"(a3), "l"(descB));
}

__device__ __forceinline__ void k1_panel(int g, int i, int& type, int& col) {
    if (g < 6) {
        int p = g * 5 + i;
        if (p < 8) { type = 0; col = p * 64; } else { type = 1; col = (p - 8) * 64; }
    } else {
        if (i < 3) { type = 1; col = (22 + (g - 6) * 3 + i) * 64; } else { type = 2 + (g - 6); col = 0; }
    }
}

constexpr int K1_STAGES = 4;
constexpr int K1_PANEL_BYTES = 64 * 128;
constexpr int K1_STAGE_BYTES = 16384 + 5 * K1_PANEL_BYTES;
constexpr int K1_SMEM = K1_STAGES * K1_STAGE_BYTES + 128 + 320 * 8;
constexpr float Q_SCALE = 0.25f * 1.4426950408889634f;

__global__ void __launch_bounds__(384, 1)
k1_proj(const __grid_constant__ CUtensorMap tm_x, const __grid_constant__ CUtensorMap tm_wq,
        const __grid_constant__ CUtensorMap tm_wk, const __grid_constant__ CUtensorMap tm_wv,
        const __grid_constant__ CUtensorMap tm_w1, const __grid_constant__ CUtensorMap tm_qo,
        const __grid_constant__ CUtensorMap tm_ho, const __nv_bfloat16* __restrict__ x, const __nv_bfloat16* __restrict__ b1,
        float2* rowstat, float* colpart,
        __nv_bfloat16* __restrict__ kv, float* __restrict__ kvmax) {
    extern __shared__ __align__(1024) uint8_t smem_raw[];
    const uint32_t sbase = smem_u32(smem_raw);
    const uint32_t bar_full = sbase + K1_STAGES * K1_STAGE_BYTES, bar_empty = bar_full + 8 * K1_STAGES, bar_col = bar_empty + 8 * K1_STAGES;
    const uint32_t sCol = bar_full + 128;
    const int tid = threadIdx.x, warp = __shfl_sync(0xffffffffu, tid >> 5, 0), lane = tid & 31;
    const int crank = blockIdx.x & 1, grp = (blockIdx.x >> 1) & 7, rb = (blockIdx.x >> 4) * 2 + crank;
    const int npanels = grp < 6 ? 5 : 4;
    if (tid == 0) DEV_STAMP(0, 0);

    const int hrow0 = (warp - 9) * 6, hnr = warp == 11 ? 4 : 6;
    uint4 v[6][2];
    if (warp >= 9) {
        const uint4* xp = reinterpret_cast<const uint4*>(x + (size_t)(rb * 128 + grp * 16 + hrow0) * D_MODEL);
#pragma unroll
        for (int r = 0; r < 6; r++)
            if (r < hnr) { v[r][0] = __ldg(xp + r * 64 + lane); v[r][1] = __ldg(xp + r * 64 + 32 + lane); }
    }
    const int krot = rb >> 1;
    if (tid == 256) {
        for (int s = 0; s < K1_STAGES; s++) { mbar_init(bar_full + 8 * s, 1); mbar_init(bar_empty + 8 * s, s == 0 ? 18 : 16); }
        mbar_init(bar_col, 96);
        mbar_init_fence();
    }
    cluster_sync_relaxed();
    pdl_launch();

    if (warp >= 8) {
        reg_dealloc<88>();
            if (warp == 8) {
            if (lane == 0) {
                const CUtensorMap* tms[5]; int cols[5];
#pragma unroll
                for (int i = 0; i < 5; i++) {
                    int type, col; k1_panel(grp, i, type, col);
                    tms[i] = type == 0 ? &tm_wq : type == 1 ? &tm_w1 : type == 2 ? &tm_wk : &tm_wv;
                    cols[i] = col;
                }
                for (int ks = 0; ks < 8; ks++) {
                    const int s = ks % K1_STAGES;
                    const uint32_t st = sbase + s * K1_STAGE_BYTES;
                    mbar_wait(bar_empty + 8 * s, ((ks / K1_STAGES) & 1) ^ 1);
                    mbar_expect_tx(bar_full + 8 * s, 16384 + npanels * K1_PANEL_BYTES);
                    const int k0 = ((ks + krot) & 7) * 64;
                    tma_load_2d(st, &tm_x, k0, rb * 128, bar_full + 8 * s);
#pragma unroll
                    for (int i = 0; i < 5; i++)
                        if (i < npanels && ((i + ks + crank) & 1) == 0)
                            tma_load_2d_mc(st + 16384 + i * K1_PANEL_BYTES, tms[i], cols[i], k0, bar_full + 8 * s, (uint16_t)3);
                }
            }
        } else {
            const int ht = tid - 288;
#pragma unroll
            for (int r = 0; r < 6; r++) {
                if (r < hnr) {
                    float f[16];
                    const uint32_t w[8] = {v[r][0].x, v[r][0].y, v[r][0].z, v[r][0].w, v[r][1].x, v[r][1].y, v[r][1].z, v[r][1].w};
#pragma unroll
                    for (int i = 0; i < 8; i++) { f[2 * i] = bf_lo(w[i]); f[2 * i + 1] = bf_hi(w[i]); }
                    float sum = 0.f;
#pragma unroll
                    for (int i = 0; i < 16; i++) sum += f[i];
#pragma unroll
                    for (int o = 16; o > 0; o >>= 1) sum += __shfl_xor_sync(0xffffffffu, sum, o);
                    const float mean = sum * (1.0f / D_MODEL);
                    float sq = 0.f;
#pragma unroll
                    for (int i = 0; i < 16; i++) { const float d = f[i] - mean; sq += d * d; }
#pragma unroll
                    for (int o = 16; o > 0; o >>= 1) sq += __shfl_xor_sync(0xffffffffu, sq, o);
                    const float rstd = rsqrtf(sq * (1.0f / D_MODEL) + 1e-5f);
                    if (lane == 0) rowstat[rb * 128 + grp * 16 + hrow0 + r] = make_float2(xch_enc(rstd), mean * rstd);
                }
            }
            if (ht == 0) DEV_STAMP(0, 5);
            mbar_wait(bar_full, 0);
            {
                const int pc = ht >> 1, half = ht & 1;
                float sacc[8];
#pragma unroll
                for (int c = 0; c < 8; c++) sacc[c] = 0.f;
                if (pc < npanels * 8) {
                    const uint32_t pb = sbase + 16384 + (pc >> 3) * K1_PANEL_BYTES;
#pragma unroll
                    for (int i = 0; i < 16; i++) {
                        const int k = crank * 32 + 2 * i + half;
                        uint4 u;
                        asm volatile("ld.shared.v4.b32 {%0,%1,%2,%3}, [%4];" : "=r"(u.x), "=r"(u.y), "=r"(u.z), "=r"(u.w)
                                     : "r"(pb + k * 128 + (((pc & 7) ^ (k & 7)) << 4)));
                        sacc[0] += bf_lo(u.x); sacc[1] += bf_hi(u.x); sacc[2] += bf_lo(u.y); sacc[3] += bf_hi(u.y);
                        sacc[4] += bf_lo(u.z); sacc[5] += bf_hi(u.z); sacc[6] += bf_lo(u.w); sacc[7] += bf_hi(u.w);
                    }
                }
#pragma unroll
                for (int c = 0; c < 8; c++) sacc[c] += __shfl_xor_sync(0xffffffffu, sacc[c], 1);
                if (pc < npanels * 8) {
                    float4* dst = reinterpret_cast<float4*>(colpart + (grp * 16 + rb) * 320 + pc * 8) + half;
                    *dst = half ? make_float4(xch_enc(sacc[4]), xch_enc(sacc[5]), xch_enc(sacc[6]), xch_enc(sacc[7]))
                                : make_float4(xch_enc(sacc[0]), xch_enc(sacc[1]), xch_enc(sacc[2]), xch_enc(sacc[3]));
                }
                named_bar_sync(4, 96);
                if (ht < 2) mbar_arrive_remote(bar_empty, ht);
            }
            if (ht == 0) DEV_STAMP(0, 6);
            for (int c2 = ht; c2 < npanels * 32; c2 += 96) {
                int type, col; k1_panel(grp, c2 >> 5, type, col);
                uint32_t bb = 0;
                if (type == 1) bb = __ldg(reinterpret_cast<const uint32_t*>(b1 + col) + (c2 & 31));
                uint2 pv[16];
                bool okv = false;
#pragma unroll 1
                for (uint32_t n = 0; n < (1u << 14) && !okv; n++) {
                    okv = true;
#pragma unroll
                    for (int k = 0; k < 16; k++) pv[k] = ld_relaxed_v2(colpart + (grp * 16 + k) * 320 + c2 * 2);
#pragma unroll
                    for (int k = 0; k < 16; k++) okv = okv && pv[k].x != NOT_READY && pv[k].y != NOT_READY;
                    if (!okv) __nanosleep(200);
                }
                float s0 = 0.f, s1 = 0.f;
#pragma unroll
                for (int k = 0; k < 16; k++) { s0 += xch_dec(pv[k].x); s1 += xch_dec(pv[k].y); }
                asm volatile("st.shared.v4.f32 [%0], {%1,%2,%3,%4};" ::"r"(sCol + c2 * 16), "f"(s0), "f"(bf_lo(bb)), "f"(s1), "f"(bf_hi(bb)) : "memory");
            }
            mbar_arrive(bar_col);
            if (ht == 0) DEV_STAMP(0, 7);
        }
    } else {
        reg_alloc<208>();
        const int wg = warp >> 2;
        const int g = lane >> 2, t = lane & 3;
        const int wrow = (warp & 3) * 16;
        float acc[160];
#pragma unroll
        for (int i = 0; i < 160; i++) acc[i] = 0.f;
        float2 rs0, rs1;
        const uint64_t dA0 = make_desc(sbase + wg * 8192, 16, 1024, 1);
        const uint64_t dB0 = make_desc(sbase + 16384, K1_PANEL_BYTES, 1024, 1);
#define K1_MAINLOOP(FIVE)                                                                                          \
        for (int ks = 0; ks < 8; ks++) {                                                                           \
            const int s = ks % K1_STAGES;                                                                          \
            mbar_wait(bar_full + 8 * s, (ks / K1_STAGES) & 1);                                                     \
            if (ks == 0 && tid == 0) DEV_STAMP(0, 1);                                                              \
            wg_fence();                                                                                            \
            _Pragma("unroll") for (int kk = 0; kk < 4; kk++) {                                                     \
                const uint64_t dA = dA0 + (uint64_t)((s * K1_STAGE_BYTES + kk * 32) >> 4);                         \
                const uint64_t dB = dB0 + (uint64_t)((s * K1_STAGE_BYTES + kk * 2048) >> 4);                       \
                wgmma_ss_n256_tb(acc, dA, dB, (ks | kk) != 0);                                                     \
                if (FIVE) wgmma_ss_n64_tb(acc + 128, dA, dB + (uint64_t)((4 * K1_PANEL_BYTES) >> 4), (ks | kk) != 0); \
            }                                                                                                      \
            wg_commit();                                                                                           \
            if (ks == 7) {                                                                                         \
                uint2 r0, r1;                                                                                      \
                uint32_t n = 0;                                                                                    \
                _Pragma("unroll 1") do {                                                                           \
                    r0 = ld_relaxed_v2(rowstat + rb * 128 + wg * 64 + wrow + g);                                   \
                    r1 = ld_relaxed_v2(rowstat + rb * 128 + wg * 64 + wrow + g + 8);                               \
                } while ((r0.x == NOT_READY || r1.x == NOT_READY) && ++n < (1u << 14));                            \
                rs0 = make_float2(xch_dec(r0.x), __uint_as_float(r0.y));                                           \
                rs1 = make_float2(xch_dec(r1.x), __uint_as_float(r1.y));                                           \
                mbar_wait(bar_col, 0);                                                                             \
            }                                                                                                      \
            if (ks > 0 && ks <= 4) {                                                                               \
                wg_wait<1>();                                                                                      \
                if (lane < 2) mbar_arrive_remote(bar_empty + 8 * ((ks - 1) % K1_STAGES), lane);                    \
            }                                                                                                      \
        }                                                                                                          \
        wg_wait<0>();
        if (npanels == 5) { K1_MAINLOOP(true) } else { K1_MAINLOOP(false) }
        fence_regs<160>(acc);
        if (tid == 0) DEV_STAMP(0, 2);
        named_bar_sync(1, 256);
        const int srow = (lane & 7) + ((lane >> 3) & 1) * 8;
#pragma unroll
        for (int p = 0; p < 5; p++) {
            if (p < npanels) {
                int type, col; k1_panel(grp, p, type, col);
                float* a = acc + p * 32;
                const int nj = type <= 1 ? 8 : 2;
                const float sc = type == 0 ? Q_SCALE : 1.0f;
                const float r0x = rs0.x * sc, r0y = -rs0.y * sc, r1x = rs1.x * sc, r1y = -rs1.y * sc;
#pragma unroll
                for (int j = 0; j < 8; j++) {
                    if (j < nj) {
                        float4 c;
                        asm volatile("ld.shared.v4.f32 {%0,%1,%2,%3}, [%4];" : "=f"(c.x), "=f"(c.y), "=f"(c.z), "=f"(c.w)
                                     : "r"(sCol + (p * 64 + j * 8 + 2 * t) * 8));
                        a[4 * j] = fmaf(a[4 * j], r0x, fmaf(r0y, c.x, c.y));
                        a[4 * j + 1] = fmaf(a[4 * j + 1], r0x, fmaf(r0y, c.z, c.w));
                        a[4 * j + 2] = fmaf(a[4 * j + 2], r1x, fmaf(r1y, c.x, c.y));
                        a[4 * j + 3] = fmaf(a[4 * j + 3], r1x, fmaf(r1y, c.z, c.w));
                    }
                }
                if (type <= 1) {
                    const uint32_t stg = sbase + (p * 8 + warp) * 2048;
                    uint32_t pk[16];
                    if (type == 0) {
#pragma unroll
                        for (int j = 0; j < 8; j++) {
                            pk[2 * j] = pack_bf16(a[4 * j], a[4 * j + 1]);
                            pk[2 * j + 1] = pack_bf16(a[4 * j + 2], a[4 * j + 3]);
                        }
                    } else {
#pragma unroll
                        for (int j = 0; j < 8; j++) {
                            const uint32_t h0 = pack_bf16_relu(a[4 * j], a[4 * j + 1]), h1 = pack_bf16_relu(a[4 * j + 2], a[4 * j + 3]);
                            pk[2 * j] = mul_bf16x2(h0, h0);
                            pk[2 * j + 1] = mul_bf16x2(h1, h1);
                        }
                    }
#pragma unroll
                    for (int j = 0; j < 8; j += 2) {
                        const int c16 = j + (lane >> 4);
                        stmatrix_x4(stg + srow * 128 + ((c16 ^ (srow & 7)) << 4), pk[2 * j], pk[2 * j + 1], pk[2 * j + 2], pk[2 * j + 3]);
                    }
                    fence_proxy_async();
                    __syncwarp();
                    if (lane == 0) {
                        tma_store_2d(type == 0 ? &tm_qo : &tm_ho, stg, col, rb * 128 + warp * 16);
                        tma_store_commit();
                    }
                } else if (type == 3) {
                    const int r = wg * 64 + wrow + g;
                    const int pos0 = (r >> 2) * 64 + rb * 4 + (r & 3), pos1 = pos0 + 128;
                    uint32_t* dst = reinterpret_cast<uint32_t*>(kv);
                    const uint32_t r00 = pack_bf16(a[0], a[1]), r01 = pack_bf16(a[4], a[5]);
                    const uint32_t r10 = pack_bf16(a[2], a[3]), r11 = pack_bf16(a[6], a[7]);
                    dst[(pos0 >> 4) * 128 + (pos0 & 15) * 4 + t] = r00;
                    dst[16384 + pos0 * 4 + t] = r01;
                    dst[(pos1 >> 4) * 128 + (pos1 & 15) * 4 + t] = r10;
                    dst[16384 + pos1 * 4 + t] = r11;
                    float m = fmaxf(fmaxf(fmaxf(fabsf(bf_lo(r00)), fabsf(bf_hi(r00))), fmaxf(fabsf(bf_lo(r01)), fabsf(bf_hi(r01)))),
                                    fmaxf(fmaxf(fabsf(bf_lo(r10)), fabsf(bf_hi(r10))), fmaxf(fabsf(bf_lo(r11)), fabsf(bf_hi(r11)))));
#pragma unroll
                    for (int o = 16; o > 0; o >>= 1) m = fmaxf(m, __shfl_xor_sync(0xffffffffu, m, o));
                    if (lane == 0) kvmax[128 + rb * 8 + warp] = m;
                } else {
                    float* kf = reinterpret_cast<float*>(smem_raw + 96 * 1024);
                    const int r = wg * 64 + wrow + g;
                    const int pos0 = (r >> 2) * 64 + rb * 4 + (r & 3), pos1 = pos0 + 128;
                    uint32_t* dst = reinterpret_cast<uint32_t*>(kv) + 32768;
                    dst[(pos0 >> 3) * 64 + (pos0 & 7) * 4 + t] = pack_bf16(a[0], a[1]);
                    dst[(pos0 >> 3) * 64 + 32 + (pos0 & 7) * 4 + t] = pack_bf16(a[4], a[5]);
                    dst[(pos1 >> 3) * 64 + (pos1 & 7) * 4 + t] = pack_bf16(a[2], a[3]);
                    dst[(pos1 >> 3) * 64 + 32 + (pos1 & 7) * 4 + t] = pack_bf16(a[6], a[7]);
                    kf[r * 17 + 2 * t] = a[0]; kf[r * 17 + 2 * t + 1] = a[1];
                    kf[r * 17 + 8 + 2 * t] = a[4]; kf[r * 17 + 8 + 2 * t + 1] = a[5];
                    kf[(r + 8) * 17 + 2 * t] = a[2]; kf[(r + 8) * 17 + 2 * t + 1] = a[3];
                    kf[(r + 8) * 17 + 8 + 2 * t] = a[6]; kf[(r + 8) * 17 + 8 + 2 * t + 1] = a[7];
                    named_bar_sync(1, 256);
                    if (tid < 64) {
                        const int i = tid >> 4, dim = tid & 15;
                        const int c = rb * 4 + i;
                        const int inner = (dim >> 3) * 64 + (c & 7) * 8 + (dim & 7);
                        float kt = 0.f;
#pragma unroll 8
                        for (int j = 0; j < 32; j++) {
                            const __nv_bfloat16 d = __float2bfloat16_rn(kf[(j * 4 + i) * 17 + dim] - kt);
                            kt += __bfloat162float(d);
                            kf[(j * 4 + i) * 17 + dim] = kt;
                            const int grp8 = j * 8 + (c >> 3);
                            kv[(grp8 < 128 ? grp8 * 256 + 128 : 49152 + (grp8 - 128) * 128) + inner] = d;
                        }
                    }
                    named_bar_sync(1, 256);
                    if (tid < 128) {
                        float n = 0.f;
#pragma unroll
                        for (int d = 0; d < 16; d++) { const float v = kf[tid * 17 + d]; n += v * v; }
                        if (!(n == n)) n = __int_as_float(0x7f800000);
#pragma unroll
                        for (int o = 8; o > 0; o >>= 1) n = fmaxf(n, __shfl_xor_sync(0xffffffffu, n, o));
                        if ((lane & 15) == 0) kvmax[rb * 8 + (tid >> 4)] = n;
                    }
                }
            }
        }
        if (tid == 0) DEV_STAMP(0, 3);
        if (lane == 0) tma_store_wait();
        if (tid == 0) DEV_STAMP(0, 4);
    }
}

constexpr int AT_KT = 64;
constexpr int AT_NCHUNK = 8;
constexpr int AT_NSTEP = S_LEN / AT_KT;
constexpr int AT_SPC = AT_NSTEP / AT_NCHUNK;
constexpr int AT_ONES = 131072;
constexpr int F2_STAGES = 4;
constexpr int F2_STAGE_BYTES = 8192 + 16384;
constexpr int F2_BASE = 132096;
constexpr int F2_NK = F_DIM / 64;
constexpr int AT_BAR = F2_BASE + F2_STAGES * F2_STAGE_BYTES;
constexpr int AT_SMEM = AT_BAR + 256;
#define AT_SWMASK_V 0xB6DB
constexpr uint32_t AT_SWMASK = AT_SWMASK_V;

#define AT_MAGIC (383.0f + 0.00390625f - 0.5849625f)
__device__ __forceinline__ uint32_t exp2_pair_alu(float t0, float t1) {
    uint32_t y;
    asm("prmt.b32 %0, %1, %2, 0x6521;" : "=r"(y) : "f"(t0), "f"(t1));
    const uint32_t e = y & 0x7F807F80u;
    uint32_t uh, p;
    asm("lop3.b32 %0, %1, %2, 0x3F003F00, 0xBE;" : "=r"(uh) : "r"(y), "r"(e));
    asm("fma.rn.bf16x2 %0, %1, %2, %3;" : "=r"(p) : "r"(uh), "r"(y), "r"(e));
    return p;
}

__device__ __forceinline__ void at_load_chunk(uint32_t sbase, const __nv_bfloat16* KV, uint32_t bar0, int c) {
    const uint8_t* src = reinterpret_cast<const uint8_t*>(KV);
    const uint32_t off = c < 4 ? c * 16384 : 98304 + (c - 4) * 8192, bytes = c < 4 ? 16384 : 8192;
    mbar_expect_tx(bar0 + 8 * c, bytes + 4096);
    bulk_g2s(sbase + off, src + off, bytes, bar0 + 8 * c);
    bulk_g2s(sbase + 65536 + c * 4096, src + 65536 + c * 4096, 4096, bar0 + 8 * c);
}

__device__ __forceinline__ void at_store(const float* o, __nv_bfloat16* O, int row, int lane) {
    const float l0 = __shfl_sync(0xffffffffu, o[8], lane & ~3);
    const float l1 = __shfl_sync(0xffffffffu, o[10], lane & ~3);
    const float r0 = __fdividef(1.0f, l0), r1 = __fdividef(1.0f, l1);
    const int t = lane & 3;
    uint32_t* op = reinterpret_cast<uint32_t*>(O + (size_t)(row + (lane >> 2)) * 16);
    op[t] = pack_bf16(o[0] * r0, o[1] * r0);
    op[t + 4] = pack_bf16(o[4] * r0, o[5] * r0);
    op[64 + t] = pack_bf16(o[2] * r1, o[3] * r1);
    op[64 + t + 4] = pack_bf16(o[6] * r1, o[7] * r1);
}

__device__ __forceinline__ void mma16816(float* c, const uint32_t* a, uint32_t b0, uint32_t b1) {
    asm volatile("mma.sync.aligned.m16n8k16.row.col.f32.bf16.bf16.f32 {%0,%1,%2,%3}, {%4,%5,%6,%7}, {%8,%9}, {%0,%1,%2,%3};"
                 : "+f"(c[0]), "+f"(c[1]), "+f"(c[2]), "+f"(c[3]) : "r"(a[0]), "r"(a[1]), "r"(a[2]), "r"(a[3]), "r"(b0), "r"(b1));
}
__device__ __forceinline__ void attn_fallback(const __nv_bfloat16* Q, const __nv_bfloat16* KV, __nv_bfloat16* O, uint32_t sbase) {
    const int tid = threadIdx.x;
    const int lane = tid & 31, g = lane >> 2, t = lane & 3;
    const uint32_t* Kg = reinterpret_cast<const uint32_t*>(KV + 65536);
#pragma unroll 1
    for (int mt = 0; mt < 2; mt++) {
        const int row = blockIdx.x * 512 + (tid >> 7) * 128 + mt * 64 + ((tid >> 5) & 3) * 16;
        const uint32_t* qp = reinterpret_cast<const uint32_t*>(Q + (size_t)(row + g) * 16);
        const uint32_t q[4] = {qp[t], qp[64 + t], qp[t + 4], qp[64 + t + 4]};
        float o[12];
#pragma unroll
        for (int i = 0; i < 12; i++) o[i] = 0.f;
        float m0 = -INFINITY, m1 = -INFINITY;
#pragma unroll 1
        for (int kt = 0; kt < S_LEN / 16; kt++) {
            float s[8];
#pragma unroll
            for (int i = 0; i < 8; i++) s[i] = 0.f;
#pragma unroll
            for (int h = 0; h < 2; h++) {
                const uint32_t* kp = Kg + (kt * 2 + h) * 64 + g * 4 + t;
                mma16816(s + 4 * h, q, kp[0], kp[32]);
            }
            float x0 = fmaxf(fmaxf(s[0], s[1]), fmaxf(s[4], s[5])), x1 = fmaxf(fmaxf(s[2], s[3]), fmaxf(s[6], s[7]));
            x0 = fmaxf(x0, __shfl_xor_sync(0xffffffffu, x0, 1)); x0 = fmaxf(x0, __shfl_xor_sync(0xffffffffu, x0, 2));
            x1 = fmaxf(x1, __shfl_xor_sync(0xffffffffu, x1, 1)); x1 = fmaxf(x1, __shfl_xor_sync(0xffffffffu, x1, 2));
            x0 = fmaxf(x0, m0); x1 = fmaxf(x1, m1);
            const float f0 = ex2(m0 - x0), f1 = ex2(m1 - x1);
            m0 = x0; m1 = x1;
#pragma unroll
            for (int j = 0; j < 3; j++) { o[4 * j] *= f0; o[4 * j + 1] *= f0; o[4 * j + 2] *= f1; o[4 * j + 3] *= f1; }
            const uint32_t p[4] = {pack_bf16(ex2(s[0] - m0), ex2(s[1] - m0)), pack_bf16(ex2(s[2] - m1), ex2(s[3] - m1)),
                                   pack_bf16(ex2(s[4] - m0), ex2(s[5] - m0)), pack_bf16(ex2(s[6] - m1), ex2(s[7] - m1))};
#pragma unroll
            for (int j = 0; j < 3; j++) {
                const uint32_t base = sbase + (j == 0 ? kt * 512 : j == 1 ? 65536 + kt * 256 : AT_ONES) + (lane & 15) * 16;
                uint32_t b0, b1;
                asm volatile("ldmatrix.sync.aligned.m8n8.x2.trans.shared.b16 {%0,%1}, [%2];" : "=r"(b0), "=r"(b1) : "r"(base));
                mma16816(o + 4 * j, p, b0, b1);
            }
        }
        at_store(o, O, row, lane);
    }
}

__global__ void __launch_bounds__(640, 1)
k2_attn(const __grid_constant__ CUtensorMap tm_h, const __grid_constant__ CUtensorMap tm_w2,
        const __nv_bfloat16* __restrict__ Q, const __nv_bfloat16* __restrict__ KV, const float* __restrict__ kvmax,
        const __nv_bfloat16* __restrict__ b2, __nv_bfloat16* __restrict__ O, __nv_bfloat16* __restrict__ G,
        uint2* __restrict__ rowstat, uint2* __restrict__ colpart) {
    extern __shared__ __align__(1024) uint8_t smem_raw[];
    const uint32_t sbase = smem_u32(smem_raw);
    const uint32_t bar0 = sbase + AT_BAR, f2_full = bar0 + 64, f2_empty = f2_full + 64;
    const int tid = threadIdx.x;
    const int wg = __shfl_sync(0xffffffffu, tid >> 7, 0);
    const int warp = (tid >> 5) & 3, lane = tid & 31;
    const int g = lane >> 2, t = lane & 3;
    if (tid == 0) DEV_STAMP(1, 0);
    if (tid == 0) {
        for (int i = 0; i < AT_NCHUNK; i++) mbar_init(bar0 + 8 * i, 1);
        for (int i = 0; i < F2_STAGES; i++) { mbar_init(f2_full + 8 * i, 1); mbar_init(f2_empty + 8 * i, 4); }
        mbar_init_fence();
    }
    if (tid < 16) asm volatile("st.shared.v4.b32 [%0], {%1,%2,%2,%2};" ::"r"(sbase + AT_ONES + tid * 16), "r"(0x00003F80u), "r"(0u) : "memory");
    fence_proxy_async();
    __syncthreads();

    if (wg == 4) {
        const int rb = blockIdx.x >> 2, cb = blockIdx.x & 3;
        const uint32_t fb = sbase + F2_BASE;
        const bool leader = tid == 512;
        if (leader) {
#pragma unroll
            for (int s = 0; s < F2_STAGES; s++) {
                mbar_expect_tx(f2_full + 8 * s, F2_STAGE_BYTES);
                tma_load_2d(fb + s * F2_STAGE_BYTES + 8192, &tm_w2, cb * 128, s * 64, f2_full + 8 * s);
                tma_load_2d(fb + s * F2_STAGE_BYTES + 16384, &tm_w2, cb * 128 + 64, s * 64, f2_full + 8 * s);
            }
            pdl_wait();
#pragma unroll
            for (int s = 0; s < F2_STAGES; s++) tma_load_2d(fb + s * F2_STAGE_BYTES, &tm_h, s * 64, rb * 64, f2_full + 8 * s);
        }
        __syncwarp();
        const uint64_t dA0 = make_desc(fb, 16, 1024, 1);
        const uint64_t dB0 = make_desc(fb + 8192, 8192, 1024, 1);
        float acc[64];
#pragma unroll
        for (int i = 0; i < 64; i++) asm volatile("mov.f32 %0, 0f00000000;" : "=f"(acc[i]));
#pragma unroll 1
        for (int ks = 0; ks < F2_NK; ks++) {
            const int s = ks % F2_STAGES;
            mbar_wait(f2_full + 8 * s, (ks / F2_STAGES) & 1);
            wg_fence();
#pragma unroll
            for (int kk = 0; kk < 4; kk++)
                wgmma_ss_n128_tb(acc, dA0 + (uint64_t)((s * F2_STAGE_BYTES + kk * 32) >> 4),
                                 dB0 + (uint64_t)((s * F2_STAGE_BYTES + kk * 2048) >> 4), 1);
            wg_commit();
            wg_wait<1>();
            if (ks > 0 && ks - 1 + F2_STAGES < F2_NK) {
                const int ps = (ks - 1) % F2_STAGES, k0 = (ks - 1 + F2_STAGES) * 64;
                if (lane == 0) mbar_arrive(f2_empty + 8 * ps);
                if (leader) {
                    mbar_wait(f2_empty + 8 * ps, ((ks - 1) / F2_STAGES) & 1);
                    mbar_expect_tx(f2_full + 8 * ps, F2_STAGE_BYTES);
                    tma_load_2d(fb + ps * F2_STAGE_BYTES, &tm_h, k0, rb * 64, f2_full + 8 * ps);
                    tma_load_2d(fb + ps * F2_STAGE_BYTES + 8192, &tm_w2, cb * 128, k0, f2_full + 8 * ps);
                    tma_load_2d(fb + ps * F2_STAGE_BYTES + 16384, &tm_w2, cb * 128 + 64, k0, f2_full + 8 * ps);
                }
                __syncwarp();
            }
        }
        wg_wait<0>();
        fence_regs<64>(acc);
        uint32_t* gp = reinterpret_cast<uint32_t*>(G + (size_t)(rb * 64 + warp * 16 + g) * D_MODEL + cb * 128) + t;
#pragma unroll
        for (int j = 0; j < 16; j++) {
            const uint32_t bb = __ldg(reinterpret_cast<const uint32_t*>(b2 + cb * 128 + j * 8) + t);
            const float b0 = bf_lo(bb), b1v = bf_hi(bb);
            const float z0 = acc[4 * j] + b0, z1 = acc[4 * j + 1] + b1v, z2 = acc[4 * j + 2] + b0, z3 = acc[4 * j + 3] + b1v;
            gp[j * 4] = pack_bf16(__fdividef(z0, 1.0f + __expf(-z0)), __fdividef(z1, 1.0f + __expf(-z1)));
            gp[j * 4 + 8 * (D_MODEL / 2)] = pack_bf16(__fdividef(z2, 1.0f + __expf(-z2)), __fdividef(z3, 1.0f + __expf(-z3)));
        }
        if (leader) DEV_STAMP(1, 5);
        return;
    }

    pdl_wait();
    pdl_launch();
    if (tid == 0) DEV_STAMP(1, 1);
    if (tid == 0) { at_load_chunk(sbase, KV, bar0, 0); at_load_chunk(sbase, KV, bar0, 1); at_load_chunk(sbase, KV, bar0, 2); }
    if (tid >= 128 && tid < 288) colpart[blockIdx.x * 160 + tid - 128] = make_uint2(NOT_READY, NOT_READY);
    if (tid >= 288 && tid < 304) rowstat[blockIdx.x * 16 + tid - 288] = make_uint2(NOT_READY, NOT_READY);
    const int rowA = blockIdx.x * 512 + wg * 128 + warp * 16;
    const uint32_t* qp = reinterpret_cast<const uint32_t*>(Q + (size_t)(rowA + g) * 16);
    const uint32_t lo0 = ((sbase & 0x3FFFF) >> 4) | (8u << 16);

#define AT_EXP(P) _Pragma("unroll") for (int i = 0; i < AT_KT / 4; i++) {                       \
                if ((AT_SWMASK >> (i & 15)) & 1) P[i] = exp2_pair_alu(s[2 * i], s[2 * i + 1]);  \
                else P[i] = pack_bf16(ex2(s[2 * i]), ex2(s[2 * i + 1])); }
#define AT_PV(P, st) _Pragma("unroll") for (int j = 0; j < AT_KT / 16; j++)                     \
                wgmma_pv(o, P[4 * j], P[4 * j + 1], P[4 * j + 2], P[4 * j + 3],                 \
                         desc64(vlo + ((st) * 4 + j) * 32, vhi - ((st) * 4 + j) * 16));
#define AT_PIPE 0
#define AT_STEP(st, PC, PN, klo, khi) {                                                         \
                wg_wait<0>();                                                                   \
                fence_regs<AT_KT / 2>(s);                                                       \
                AT_EXP(p0);                                                                     \
                if (st == AT_SPC - 1 && mt == 0) mbar_wait(bar0 + 8 * (c + 1), 0);              \
                wg_fence();                                                                     \
                wgmma_qk_acc_n64(s, q, desc64(klo, khi));                                       \
                AT_PV(p0, st);                                                                  \
                wg_commit(); }

#pragma unroll 1
    for (int mt = 0; mt < 2; mt++) {
        uint32_t q[4];
        q[0] = qp[mt * 512 + t]; q[2] = qp[mt * 512 + t + 4]; q[1] = qp[mt * 512 + 64 + t]; q[3] = qp[mt * 512 + 64 + t + 4];
        float o[12];
#pragma unroll
        for (int i = 0; i < 12; i++) asm volatile("mov.f32 %0, 0f00000000;" : "=f"(o[i]));
        float s[AT_KT / 2];
        uint32_t p0[AT_KT / 4], p1[AT_KT / 4];
        (void)p1;
#pragma unroll
        for (int i = 0; i < AT_KT / 2; i++) {
            if ((AT_SWMASK >> ((i >> 1) & 15)) & 1) asm volatile("mov.f32 %0, %1;" : "=f"(s[i]) : "f"(AT_MAGIC));
            else asm volatile("mov.f32 %0, 0f00000000;" : "=f"(s[i]));
        }
        if (mt == 0) mbar_wait(bar0, 0);
        if (tid == 0) DEV_STAMP(1, 2 + mt);
        uint32_t klo = lo0 + 16, vlo = lo0, vhi = 4096;
        wg_fence();
        wgmma_qk_acc_n64(s, q, desc64(klo, 32));
        wg_commit();
        uint32_t kst = 256, khi = 32;
#pragma unroll 1
        for (int c = 0; c < AT_NCHUNK - 1; c++) {
            if (tid == 0 && mt == 0 && c + 3 < AT_NCHUNK) at_load_chunk(sbase, KV, bar0, c + 3);
            AT_STEP(0, p0, p1, klo + kst, khi); AT_STEP(1, p1, p0, klo + 2 * kst, khi); AT_STEP(2, p0, p1, klo + 3 * kst, khi);
            if (c == 3) { klo = lo0 + (98304 >> 4); kst = 128; khi = 16; } else klo += 4 * kst;
            AT_STEP(3, p1, p0, klo, khi);
            vlo += 512; vhi -= 256;
        }
        {
            const int c = 0; (void)c;
            AT_STEP(0, p0, p1, klo + 128, 16); AT_STEP(1, p1, p0, klo + 256, 16); AT_STEP(2, p0, p1, klo + 384, 16);
            wg_wait<0>();
            fence_regs<AT_KT / 2>(s);
            AT_EXP(p0);
            wg_fence();
            AT_PV(p0, 3);
            wg_commit();
            wg_wait<0>();
            fence_regs<12>(o);
        }
        at_store(o, O, rowA + mt * 64, lane);
    }
    if (tid == 0) DEV_STAMP(1, 4);

    bool unsafe;
    {
        float km = fmaxf(fmaxf(kvmax[lane], kvmax[lane + 32]), fmaxf(kvmax[lane + 64], kvmax[lane + 96]));
        float vm = fmaxf(fmaxf(kvmax[128 + lane], kvmax[160 + lane]), fmaxf(kvmax[192 + lane], kvmax[224 + lane]));
#pragma unroll
        for (int o = 16; o > 0; o >>= 1) { km = fmaxf(km, __shfl_xor_sync(0xffffffffu, km, o)); vm = fmaxf(vm, __shfl_xor_sync(0xffffffffu, vm, o)); }
        const uint4* qr = reinterpret_cast<const uint4*>(Q + (size_t)(rowA + (lane >> 4) * 64 + (lane & 15)) * 16);
        const uint4 qa = qr[0], qb = qr[1];
        const uint32_t qw[8] = {qa.x, qa.y, qa.z, qa.w, qb.x, qb.y, qb.z, qb.w};
        float qn = 0.f;
#pragma unroll
        for (int i = 0; i < 8; i++) qn += bf_lo(qw[i]) * bf_lo(qw[i]) + bf_hi(qw[i]) * bf_hi(qw[i]);
        const bool ok = (qn * km <= 3600.0f) && (vm <= 1.0e12f);
        unsafe = __any_sync(0xffffffffu, !ok);
    }
    if (!unsafe) return;

    attn_fallback(Q, KV, O, sbase);
}

constexpr int K3_STAGE_BYTES = 16384 + 8192;
constexpr int K3_X = 8 * K3_STAGE_BYTES;
constexpr int K3_G = K3_X + 16384;
constexpr int K3_SMEM = K3_G + 16384 + 256;

__global__ void __launch_bounds__(256, 1)
k3_out(const __grid_constant__ CUtensorMap tm_o, const __grid_constant__ CUtensorMap tm_wo,
       const __grid_constant__ CUtensorMap tm_x, const __grid_constant__ CUtensorMap tm_g,
       const __grid_constant__ CUtensorMap tm_out) {
    extern __shared__ __align__(1024) uint8_t smem_raw[];
    const uint32_t sbase = smem_u32(smem_raw);
    const uint32_t sX = sbase + K3_X, sG = sbase + K3_G;
    const uint32_t bar_full = sG + 16384, bar_x = bar_full + 64;
    const int tid = threadIdx.x, warp = __shfl_sync(0xffffffffu, tid >> 5, 0), lane = tid & 31;
    const int rb = blockIdx.x >> 3, cb = blockIdx.x & 7;
    if (tid == 0) {
        DEV_STAMP(2, 0);
        for (int s = 0; s < 8; s++) mbar_init(bar_full + 8 * s, 1);
        mbar_init(bar_x, 1);
        mbar_init_fence();
        for (int s = 0; s < 8; s++) {
            mbar_expect_tx(bar_full + 8 * s, K3_STAGE_BYTES);
            tma_load_2d(sbase + s * K3_STAGE_BYTES + 16384, &tm_wo, cb * 64, s * 64, bar_full + 8 * s);
        }
        mbar_expect_tx(bar_x, 32768);
        tma_load_2d(sX, &tm_x, cb * 64, rb * 128, bar_x);
        pdl_wait();
        DEV_STAMP(2, 1);
        for (int s = 0; s < 8; s++) tma_load_2d(sbase + s * K3_STAGE_BYTES, &tm_o, s * 64, rb * 128, bar_full + 8 * s);
        tma_load_2d(sG, &tm_g, cb * 64, rb * 128, bar_x);
    }
    __syncthreads();
    const int wg = warp >> 2;
    float acc[32];
#pragma unroll
    for (int i = 0; i < 32; i++) asm volatile("mov.f32 %0, 0f00000000;" : "=f"(acc[i]));
    const uint64_t dA0 = make_desc(sbase + wg * 8192, 16, 1024, 1);
    const uint64_t dB0 = make_desc(sbase + 16384, 8192, 1024, 1);
#pragma unroll 1
    for (int ks = 0; ks < 8; ks++) {
        mbar_wait(bar_full + 8 * ks, 0);
        wg_fence();
#pragma unroll
        for (int kk = 0; kk < 4; kk++)
            wgmma_ss_n64_tb(acc, dA0 + (uint64_t)((ks * K3_STAGE_BYTES + kk * 32) >> 4),
                            dB0 + (uint64_t)((ks * K3_STAGE_BYTES + kk * 2048) >> 4), 1);
        wg_commit();
    }
    wg_wait<0>();
    fence_regs<32>(acc);
    if (tid == 0) DEV_STAMP(2, 2);
    mbar_wait(bar_x, 0);
    const int g = lane >> 2, t = lane & 3;
    const int row0 = warp * 16 + g;
#pragma unroll
    for (int j = 0; j < 8; j++) {
#pragma unroll
        for (int h = 0; h < 2; h++) {
            const int row = row0 + h * 8;
            const uint32_t off = row * 128 + ((j ^ (row & 7)) << 4) + t * 4;
            uint32_t xv, gv;
            asm volatile("ld.shared.b32 %0, [%1];" : "=r"(xv) : "r"(sX + off) : "memory");
            asm volatile("ld.shared.b32 %0, [%1];" : "=r"(gv) : "r"(sG + off) : "memory");
            const uint32_t ov = pack_bf16(fmaf(acc[4 * j + 2 * h], bf_lo(gv), bf_lo(xv)), fmaf(acc[4 * j + 2 * h + 1], bf_hi(gv), bf_hi(xv)));
            asm volatile("st.shared.b32 [%0], %1;" ::"r"(sX + off), "r"(ov) : "memory");
        }
    }
    fence_proxy_async();
    __syncwarp();
    if (lane == 0) {
        tma_store_2d(&tm_out, sX + warp * 2048, cb * 64, rb * 128 + warp * 16);
        tma_store_commit();
        if (tid == 0) DEV_STAMP(2, 3);
        tma_store_wait();
        if (tid == 0) DEV_STAMP(2, 4);
    }
}

typedef CUresult (*EncodeFn)(CUtensorMap*, CUtensorMapDataType, cuuint32_t, void*, const cuuint64_t*, const cuuint64_t*,
                             const cuuint32_t*, const cuuint32_t*, CUtensorMapInterleave, CUtensorMapSwizzle,
                             CUtensorMapL2promotion, CUtensorMapFloatOOBfill);

struct HostState {
    bool ready;
    const void* key[11];
    CUtensorMap wq, wk, wv, w1, qo, ho, hi, oi, w2, wo, xi, gi, out;
    void *pQ, *pKV, *pH, *pO, *pMax, *pRow, *pCol, *pFlag, *pG;
};
HostState g_hs;

void make_map(EncodeFn fn, CUtensorMap* m, const void* ptr, uint64_t inner, uint64_t outer, uint32_t box_in, uint32_t box_out) {
    cuuint64_t dims[2] = {inner, outer};
    cuuint64_t strides[1] = {inner * 2};
    cuuint32_t box[2] = {box_in, box_out};
    cuuint32_t es[2] = {1, 1};
    fn(m, CU_TENSOR_MAP_DATA_TYPE_BFLOAT16, 2, const_cast<void*>(ptr), dims, strides, box, es, CU_TENSOR_MAP_INTERLEAVE_NONE,
       CU_TENSOR_MAP_SWIZZLE_128B, CU_TENSOR_MAP_L2_PROMOTION_L2_256B, CU_TENSOR_MAP_FLOAT_OOB_FILL_NONE);
}

template <typename... KArgs, typename... Args>
void launch(void (*kern)(KArgs...), int grid, int block, int smem, bool pdl, int cluster, Args... args) {
    cudaLaunchConfig_t cfg = {};
    cfg.gridDim = dim3(grid); cfg.blockDim = dim3(block); cfg.dynamicSmemBytes = smem; cfg.stream = cudaStreamPerThread;
    cudaLaunchAttribute at[2];
    int n = 0;
    if (pdl) { at[n].id = cudaLaunchAttributeProgrammaticStreamSerialization; at[n].val.programmaticStreamSerializationAllowed = 1; n++; }
    if (cluster > 1) { at[n].id = cudaLaunchAttributeClusterDimension; at[n].val.clusterDim.x = cluster; at[n].val.clusterDim.y = 1; at[n].val.clusterDim.z = 1; n++; }
    cfg.attrs = at; cfg.numAttrs = n;
    cudaLaunchKernelEx(&cfg, kern, KArgs(args)...);
}

}

extern "C" void kernel_launch(void* const* d_in, const int* in_sizes, int n_in, void* d_out, int out_size) {
    (void)in_sizes; (void)n_in; (void)out_size;
    HostState& hs = g_hs;
    bool same = hs.ready;
    for (int i = 0; i < 10 && same; i++) same = hs.key[i] == d_in[i];
    same = same && hs.key[10] == d_out;
    if (!same) {
        void* fp = nullptr;
        cudaDriverEntryPointQueryResult qr;
        cudaGetDriverEntryPoint("cuTensorMapEncodeTiled", &fp, cudaEnableDefault, &qr);
        EncodeFn fn = (EncodeFn)fp;
        cudaGetSymbolAddress(&hs.pQ, g_Q); cudaGetSymbolAddress(&hs.pKV, g_KV); cudaGetSymbolAddress(&hs.pH, g_H);
        cudaGetSymbolAddress(&hs.pO, g_O); cudaGetSymbolAddress(&hs.pMax, g_kvmax);
        cudaGetSymbolAddress(&hs.pRow, g_rowstat); cudaGetSymbolAddress(&hs.pCol, g_colpart); cudaGetSymbolAddress(&hs.pG, g_G);
        make_map(fn, &hs.wq, d_in[1], 512, 512, 64, 64);
        make_map(fn, &hs.wk, d_in[2], 16, 512, 64, 64);
        make_map(fn, &hs.wv, d_in[3], 16, 512, 64, 64);
        make_map(fn, &hs.w1, d_in[6], F_DIM, 512, 64, 64);
        make_map(fn, &hs.qo, hs.pQ, 512, S_LEN, 64, 16);
        make_map(fn, &hs.ho, hs.pH, F_DIM, S_LEN, 64, 16);
        make_map(fn, &hs.hi, hs.pH, F_DIM, S_LEN, 64, 64);
        make_map(fn, &hs.gi, hs.pG, 512, S_LEN, 64, 128);
        make_map(fn, &hs.oi, hs.pO, 512, S_LEN, 64, 128);
        make_map(fn, &hs.w2, d_in[8], 512, F_DIM, 64, 64);
        make_map(fn, &hs.wo, d_in[4], 512, 512, 64, 64);
        make_map(fn, &hs.xi, d_in[0], 512, S_LEN, 64, 128);
        make_map(fn, &hs.out, d_out, 512, S_LEN, 64, 16);
        cudaFuncSetAttribute(k1_proj, cudaFuncAttributeMaxDynamicSharedMemorySize, K1_SMEM);
        cudaFuncSetAttribute(k2_attn, cudaFuncAttributeMaxDynamicSharedMemorySize, AT_SMEM);
        cudaFuncSetAttribute(k3_out, cudaFuncAttributeMaxDynamicSharedMemorySize, K3_SMEM);
        for (int i = 0; i < 10; i++) hs.key[i] = d_in[i];
        hs.key[10] = d_out;
        hs.ready = true;
    }
    launch(k1_proj, 128, 384, K1_SMEM, false, 2, hs.xi, hs.wq, hs.wk, hs.wv, hs.w1, hs.qo, hs.ho, (const __nv_bfloat16*)d_in[0],
           (const __nv_bfloat16*)d_in[7], (float2*)hs.pRow, (float*)hs.pCol, (__nv_bfloat16*)hs.pKV, (float*)hs.pMax);
    launch(k2_attn, 128, 640, AT_SMEM, true, 1, hs.hi, hs.w2, (const __nv_bfloat16*)hs.pQ, (const __nv_bfloat16*)hs.pKV,
           (const float*)hs.pMax, (const __nv_bfloat16*)d_in[9], (__nv_bfloat16*)hs.pO, (__nv_bfloat16*)hs.pG, (uint2*)hs.pRow, (uint2*)hs.pCol);
    launch(k3_out, 128, 256, K3_SMEM, true, 1, hs.oi, hs.wo, hs.xi, hs.gi, hs.out);
}
```

```cpp
#include <cuda_runtime.h>
#include <cuda_bf16.h>
#include <cuda.h>
#include <stdint.h>

namespace {

constexpr int S_LEN = 2048, D_MODEL = 512, F_DIM = 1792;

__device__ __align__(1024) __nv_bfloat16 g_Q[S_LEN * D_MODEL];
__device__ __align__(1024) __nv_bfloat16 g_KV[6 * S_LEN * 8];
__device__ __align__(1024) __nv_bfloat16 g_G[S_LEN * D_MODEL];
__device__ __align__(1024) __nv_bfloat16 g_H[S_LEN * F_DIM];
__device__ __align__(1024) __nv_bfloat16 g_O[S_LEN * D_MODEL];
__device__ __align__(1024) float g_kvmax[256];
__device__ __align__(1024) float2 g_rowstat[S_LEN];
__device__ __align__(1024) float g_colpart[8 * 16 * 320];

__device__ __align__(1024) int g_sync[512];

#define DEV_STAMP(k, e) do {} while (0)
__device__ __forceinline__ uint32_t smem_u32(const void* p) { return (uint32_t)__cvta_generic_to_shared(p); }
__device__ __forceinline__ void wg_fence() { asm volatile("wgmma.fence.sync.aligned;" ::: "memory"); }
__device__ __forceinline__ void wg_commit() { asm volatile("wgmma.commit_group.sync.aligned;" ::: "memory"); }
template <int N> __device__ __forceinline__ void wg_wait() { asm volatile("wgmma.wait_group.sync.aligned %0;" ::"n"(N) : "memory"); }
template <int N> __device__ __forceinline__ void fence_regs(float* r) {
#pragma unroll
    for (int i = 0; i < N; i++) asm volatile("" : "+f"(r[i])::"memory");
}
__device__ __forceinline__ void fence_proxy_async() { asm volatile("fence.proxy.async.shared::cta;" ::: "memory"); }
__device__ __forceinline__ void mbar_init(uint32_t bar, int cnt) { asm volatile("mbarrier.init.shared::cta.b64 [%0], %1;" ::"r"(bar), "r"(cnt) : "memory"); }
__device__ __forceinline__ void mbar_init_fence() { asm volatile("fence.mbarrier_init.release.cluster;" ::: "memory"); }
__device__ __forceinline__ void mbar_expect_tx(uint32_t bar, uint32_t bytes) {
    asm volatile("mbarrier.arrive.expect_tx.shared::cta.b64 _, [%0], %1;" ::"r"(bar), "r"(bytes) : "memory");
}
__device__ __forceinline__ void mbar_arrive(uint32_t bar) { asm volatile("mbarrier.arrive.shared::cta.b64 _, [%0];" ::"r"(bar) : "memory"); }
__device__ __forceinline__ bool mbar_try(uint32_t bar, uint32_t parity) {
    uint32_t ok;
    asm volatile("{\n.reg .pred p;\nmbarrier.try_wait.parity.shared::cta.b64 p, [%1], %2;\nselp.u32 %0, 1, 0, p;\n}\n"
                 : "=r"(ok) : "r"(bar), "r"(parity) : "memory");
    return ok != 0;
}
__device__ __forceinline__ void mbar_wait(uint32_t bar, uint32_t parity) {
    if (mbar_try(bar, parity)) return;
    const long long t0 = clock64();
#pragma unroll 1
    while (!mbar_try(bar, parity)) {
        if (clock64() - t0 > 20000000ll) {
            break;
        }
    }
}
__device__ __forceinline__ void bulk_g2s(uint32_t dst, const void* src, uint32_t bytes, uint32_t bar) {
    asm volatile("cp.async.bulk.shared::cluster.global.mbarrier::complete_tx::bytes [%0], [%1], %2, [%3];"
                 ::"r"(dst), "l"(src), "r"(bytes), "r"(bar) : "memory");
}
__device__ __forceinline__ void tma_load_2d(uint32_t dst, const CUtensorMap* tm, int c0, int c1, uint32_t bar) {
    asm volatile("cp.async.bulk.tensor.2d.shared::cluster.global.mbarrier::complete_tx::bytes [%0], [%1, {%3, %4}], [%2];"
                 ::"r"(dst), "l"((uint64_t)tm), "r"(bar), "r"(c0), "r"(c1) : "memory");
}
__device__ __forceinline__ void tma_load_2d_mc(uint32_t dst, const CUtensorMap* tm, int c0, int c1, uint32_t bar, uint16_t mask) {
    asm volatile("cp.async.bulk.tensor.2d.shared::cluster.global.mbarrier::complete_tx::bytes.multicast::cluster [%0], [%1, {%3, %4}], [%2], %5;"
                 ::"r"(dst), "l"((uint64_t)tm), "r"(bar), "r"(c0), "r"(c1), "h"(mask) : "memory");
}
__device__ __forceinline__ void mbar_arrive_remote(uint32_t bar, uint32_t cta) {
    asm volatile("{\n.reg .b32 ra;\nmapa.shared::cluster.u32 ra, %0, %1;\nmbarrier.arrive.shared::cluster.b64 _, [ra];\n}\n"
                 ::"r"(bar), "r"(cta) : "memory");
}
__device__ __forceinline__ void cluster_sync_relaxed() {
    asm volatile("barrier.cluster.arrive.relaxed;\nbarrier.cluster.wait;" ::: "memory");
}
__device__ __forceinline__ uint2 ld_relaxed_v2(const void* p) {
    uint2 v; asm volatile("ld.relaxed.gpu.global.v2.b32 {%0,%1}, [%2];" : "=r"(v.x), "=r"(v.y) : "l"(p) : "memory"); return v;
}
__device__ __forceinline__ void signal_add(int* p) {
    asm volatile("fence.proxy.async;\nfence.acq_rel.gpu;\nred.relaxed.gpu.global.add.s32 [%0], 1;" ::"l"(p) : "memory");
}
__device__ __forceinline__ void wait_count(const int* p, int target) {
    int v = -1;
#pragma unroll 1
    for (uint32_t n = 0; n < (1u << 20) && v < target; n++)
        asm volatile("ld.acquire.gpu.global.s32 %0, [%1];" : "=r"(v) : "l"(p) : "memory");
    asm volatile("fence.proxy.async;" ::: "memory");
}
constexpr uint32_t NOT_READY = 0u;
__device__ __forceinline__ float xch_enc(float v) { return __uint_as_float((v == 0.f ? 0u : __float_as_uint(v)) ^ 0x80000000u); }
__device__ __forceinline__ float xch_dec(uint32_t u) { return __uint_as_float(u ^ 0x80000000u); }
__device__ __forceinline__ void tma_store_2d(const CUtensorMap* tm, uint32_t src, int c0, int c1) {
    asm volatile("cp.async.bulk.tensor.2d.global.shared::cta.bulk_group [%0, {%2, %3}], [%1];"
                 ::"l"((uint64_t)tm), "r"(src), "r"(c0), "r"(c1) : "memory");
}
__device__ __forceinline__ void tma_store_commit() { asm volatile("cp.async.bulk.commit_group;" ::: "memory"); }
__device__ __forceinline__ void tma_store_wait() { asm volatile("cp.async.bulk.wait_group 0;" ::: "memory"); }
__device__ __forceinline__ void tma_prefetch_desc(const CUtensorMap* tm) { asm volatile("prefetch.tensormap [%0];" ::"l"((uint64_t)tm) : "memory"); }
__device__ __forceinline__ void named_bar_sync(int id, int n) { asm volatile("bar.sync %0, %1;" ::"r"(id), "r"(n) : "memory"); }
__device__ __forceinline__ void pdl_wait() { asm volatile("griddepcontrol.wait;" ::: "memory"); }
__device__ __forceinline__ void pdl_launch() { asm volatile("griddepcontrol.launch_dependents;" ::: "memory"); }
template <int N> __device__ __forceinline__ void reg_alloc() { asm volatile("setmaxnreg.inc.sync.aligned.u32 %0;" ::"n"(N)); }
template <int N> __device__ __forceinline__ void reg_dealloc() { asm volatile("setmaxnreg.dec.sync.aligned.u32 %0;" ::"n"(N)); }
__device__ __forceinline__ float ex2(float x) { float y; asm("ex2.approx.ftz.f32 %0, %1;" : "=f"(y) : "f"(x)); return y; }
__device__ __forceinline__ uint32_t pack_bf16(float lo, float hi) {
    uint32_t r; asm("cvt.rn.bf16x2.f32 %0, %1, %2;" : "=r"(r) : "f"(hi), "f"(lo)); return r;
}
__device__ __forceinline__ uint32_t pack_bf16_relu(float lo, float hi) {
    uint32_t r; asm("cvt.rn.relu.bf16x2.f32 %0, %1, %2;" : "=r"(r) : "f"(hi), "f"(lo)); return r;
}
__device__ __forceinline__ uint32_t mul_bf16x2(uint32_t a, uint32_t b) {
    uint32_t r; asm("mul.rn.bf16x2 %0, %1, %2;" : "=r"(r) : "r"(a), "r"(b)); return r;
}
__device__ __forceinline__ float bf_lo(uint32_t v) { return __uint_as_float(v << 16); }
__device__ __forceinline__ float bf_hi(uint32_t v) { return __uint_as_float(v & 0xFFFF0000u); }
__device__ __forceinline__ void stmatrix_x4(uint32_t addr, uint32_t r0, uint32_t r1, uint32_t r2, uint32_t r3) {
    asm volatile("stmatrix.sync.aligned.m8n8.x4.shared.b16 [%0], {%1,%2,%3,%4};" ::"r"(addr), "r"(r0), "r"(r1), "r"(r2), "r"(r3) : "memory");
}
__device__ __forceinline__ uint64_t make_desc(uint32_t addr, uint32_t lbo, uint32_t sbo, uint32_t swz) {
    return (uint64_t)((addr & 0x3FFFF) >> 4) | ((uint64_t)(lbo >> 4) << 16) | ((uint64_t)(sbo >> 4) << 32) | ((uint64_t)swz << 62);
}

__device__ __forceinline__ uint64_t desc64(uint32_t lo, uint32_t hi) {
    uint64_t d; asm("mov.b64 %0, {%1, %2};" : "=l"(d) : "r"(lo), "r"(hi)); return d;
}

__device__ __forceinline__ void wgmma_ss_n256_tb(float* d, uint64_t descA, uint64_t descB, int scaleD) {
    asm volatile("{\n.reg .pred p;\nsetp.ne.b32 p, %130, 0;\n"
      "wgmma.mma_async.sync.aligned.m64n256k16.f32.bf16.bf16 {%0,%1,%2,%3,%4,%5,%6,%7,%8,%9,%10,%11,%12,%13,%14,%15,%16,%17,%18,%19,%20,%21,%22,%23,%24,%25,%26,%27,%28,%29,%30,%31,%32,%33,%34,%35,%36,%37,%38,%39,%40,%41,%42,%43,%44,%45,%46,%47,%48,%49,%50,%51,%52,%53,%54,%55,%56,%57,%58,%59,%60,%61,%62,%63,%64,%65,%66,%67,%68,%69,%70,%71,%72,%73,%74,%75,%76,%77,%78,%79,%80,%81,%82,%83,%84,%85,%86,%87,%88,%89,%90,%91,%92,%93,%94,%95,%96,%97,%98,%99,%100,%101,%102,%103,%104,%105,%106,%107,%108,%109,%110,%111,%112,%113,%114,%115,%116,%117,%118,%119,%120,%121,%122,%123,%124,%125,%126,%127}, %128, %129, p, 1, 1, 0, 1;\n}\n"
      : "+f"(d[0]), "+f"(d[1]), "+f"(d[2]), "+f"(d[3]), "+f"(d[4]), "+f"(d[5]), "+f"(d[6]), "+f"(d[7]), "+f"(d[8]), "+f"(d[9]), "+f"(d[10]), "+f"(d[11]), "+f"(d[12]), "+f"(d[13]), "+f"(d[14]), "+f"(d[15]), "+f"(d[16]), "+f"(d[17]), "+f"(d[18]), "+f"(d[19]), "+f"(d[20]), "+f"(d[21]), "+f"(d[22]), "+f"(d[23]), "+f"(d[24]), "+f"(d[25]), "+f"(d[26]), "+f"(d[27]), "+f"(d[28]), "+f"(d[29]), "+f"(d[30]), "+f"(d[31]), "+f"(d[32]), "+f"(d[33]), "+f"(d[34]), "+f"(d[35]), "+f"(d[36]), "+f"(d[37]), "+f"(d[38]), "+f"(d[39]), "+f"(d[40]), "+f"(d[41]), "+f"(d[42]), "+f"(d[43]), "+f"(d[44]), "+f"(d[45]), "+f"(d[46]), "+f"(d[47]), "+f"(d[48]), "+f"(d[49]), "+f"(d[50]), "+f"(d[51]), "+f"(d[52]), "+f"(d[53]), "+f"(d[54]), "+f"(d[55]), "+f"(d[56]), "+f"(d[57]), "+f"(d[58]), "+f"(d[59]), "+f"(d[60]), "+f"(d[61]), "+f"(d[62]), "+f"(d[63]), "+f"(d[64]), "+f"(d[65]), "+f"(d[66]), "+f"(d[67]), "+f"(d[68]), "+f"(d[69]), "+f"(d[70]), "+f"(d[71]), "+f"(d[72]), "+f"(d[73]), "+f"(d[74]), "+f"(d[75]), "+f"(d[76]), "+f"(d[77]), "+f"(d[78]), "+f"(d[79]), "+f"(d[80]), "+f"(d[81]), "+f"(d[82]), "+f"(d[83]), "+f"(d[84]), "+f"(d[85]), "+f"(d[86]), "+f"(d[87]), "+f"(d[88]), "+f"(d[89]), "+f"(d[90]), "+f"(d[91]), "+f"(d[92]), "+f"(d[93]), "+f"(d[94]), "+f"(d[95]), "+f"(d[96]), "+f"(d[97]), "+f"(d[98]), "+f"(d[99]), "+f"(d[100]), "+f"(d[101]), "+f"(d[102]), "+f"(d[103]), "+f"(d[104]), "+f"(d[105]), "+f"(d[106]), "+f"(d[107]), "+f"(d[108]), "+f"(d[109]), "+f"(d[110]), "+f"(d[111]), "+f"(d[112]), "+f"(d[113]), "+f"(d[114]), "+f"(d[115]), "+f"(d[116]), "+f"(d[117]), "+f"(d[118]), "+f"(d[119]), "+f"(d[120]), "+f"(d[121]), "+f"(d[122]), "+f"(d[123]), "+f"(d[124]), "+f"(d[125]), "+f"(d[126]), "+f"(d[127])
      : "l"(descA), "l"(descB), "r"(scaleD));
}
__device__ __forceinline__ void wgmma_ss_n128_tb(float* d, uint64_t descA, uint64_t descB, int scaleD) {
    asm volatile("{\n.reg .pred p;\nsetp.ne.b32 p, %66, 0;\n"
      "wgmma.mma_async.sync.aligned.m64n128k16.f32.bf16.bf16 {%0,%1,%2,%3,%4,%5,%6,%7,%8,%9,%10,%11,%12,%13,%14,%15,%16,%17,%18,%19,%20,%21,%22,%23,%24,%25,%26,%27,%28,%29,%30,%31,%32,%33,%34,%35,%36,%37,%38,%39,%40,%41,%42,%43,%44,%45,%46,%47,%48,%49,%50,%51,%52,%53,%54,%55,%56,%57,%58,%59,%60,%61,%62,%63}, %64, %65, p, 1, 1, 0, 1;\n}\n"
      : "+f"(d[0]), "+f"(d[1]), "+f"(d[2]), "+f"(d[3]), "+f"(d[4]), "+f"(d[5]), "+f"(d[6]), "+f"(d[7]), "+f"(d[8]), "+f"(d[9]), "+f"(d[10]), "+f"(d[11]), "+f"(d[12]), "+f"(d[13]), "+f"(d[14]), "+f"(d[15]), "+f"(d[16]), "+f"(d[17]), "+f"(d[18]), "+f"(d[19]), "+f"(d[20]), "+f"(d[21]), "+f"(d[22]), "+f"(d[23]), "+f"(d[24]), "+f"(d[25]), "+f"(d[26]), "+f"(d[27]), "+f"(d[28]), "+f"(d[29]), "+f"(d[30]), "+f"(d[31]), "+f"(d[32]), "+f"(d[33]), "+f"(d[34]), "+f"(d[35]), "+f"(d[36]), "+f"(d[37]), "+f"(d[38]), "+f"(d[39]), "+f"(d[40]), "+f"(d[41]), "+f"(d[42]), "+f"(d[43]), "+f"(d[44]), "+f"(d[45]), "+f"(d[46]), "+f"(d[47]), "+f"(d[48]), "+f"(d[49]), "+f"(d[50]), "+f"(d[51]), "+f"(d[52]), "+f"(d[53]), "+f"(d[54]), "+f"(d[55]), "+f"(d[56]), "+f"(d[57]), "+f"(d[58]), "+f"(d[59]), "+f"(d[60]), "+f"(d[61]), "+f"(d[62]), "+f"(d[63])
      : "l"(descA), "l"(descB), "r"(scaleD));
}
__device__ __forceinline__ void wgmma_ss_n64_tb(float* d, uint64_t descA, uint64_t descB, int scaleD) {
    asm volatile("{\n.reg .pred p;\nsetp.ne.b32 p, %34, 0;\n"
      "wgmma.mma_async.sync.aligned.m64n64k16.f32.bf16.bf16 {%0,%1,%2,%3,%4,%5,%6,%7,%8,%9,%10,%11,%12,%13,%14,%15,%16,%17,%18,%19,%20,%21,%22,%23,%24,%25,%26,%27,%28,%29,%30,%31}, %32, %33, p, 1, 1, 0, 1;\n}\n"
      : "+f"(d[0]), "+f"(d[1]), "+f"(d[2]), "+f"(d[3]), "+f"(d[4]), "+f"(d[5]), "+f"(d[6]), "+f"(d[7]), "+f"(d[8]), "+f"(d[9]), "+f"(d[10]), "+f"(d[11]), "+f"(d[12]), "+f"(d[13]), "+f"(d[14]), "+f"(d[15]), "+f"(d[16]), "+f"(d[17]), "+f"(d[18]), "+f"(d[19]), "+f"(d[20]), "+f"(d[21]), "+f"(d[22]), "+f"(d[23]), "+f"(d[24]), "+f"(d[25]), "+f"(d[26]), "+f"(d[27]), "+f"(d[28]), "+f"(d[29]), "+f"(d[30]), "+f"(d[31])
      : "l"(descA), "l"(descB), "r"(scaleD));
}
__device__ __forceinline__ void wgmma_qk_acc_n64(float* d, const uint32_t* a, uint64_t descB) {
    asm volatile("wgmma.mma_async.sync.aligned.m64n64k16.f32.bf16.bf16 {%0,%1,%2,%3,%4,%5,%6,%7,%8,%9,%10,%11,%12,%13,%14,%15,%16,%17,%18,%19,%20,%21,%22,%23,%24,%25,%26,%27,%28,%29,%30,%31}, {%32,%33,%34,%35}, %36, 1, 1, 1, 0;\n"
      : "+f"(d[0]), "+f"(d[1]), "+f"(d[2]), "+f"(d[3]), "+f"(d[4]), "+f"(d[5]), "+f"(d[6]), "+f"(d[7]), "+f"(d[8]), "+f"(d[9]), "+f"(d[10]), "+f"(d[11]), "+f"(d[12]), "+f"(d[13]), "+f"(d[14]), "+f"(d[15]), "+f"(d[16]), "+f"(d[17]), "+f"(d[18]), "+f"(d[19]), "+f"(d[20]), "+f"(d[21]), "+f"(d[22]), "+f"(d[23]), "+f"(d[24]), "+f"(d[25]), "+f"(d[26]), "+f"(d[27]), "+f"(d[28]), "+f"(d[29]), "+f"(d[30]), "+f"(d[31])
      : "r"(a[0]), "r"(a[1]), "r"(a[2]), "r"(a[3]), "l"(descB));
}

__device__ __forceinline__ void wgmma_pv(float* d, uint32_t a0, uint32_t a1, uint32_t a2, uint32_t a3, uint64_t descB) {
    asm volatile("wgmma.mma_async.sync.aligned.m64n24k16.f32.bf16.bf16 {%0,%1,%2,%3,%4,%5,%6,%7,%8,%9,%10,%11}, {%12,%13,%14,%15}, %16, 1, 1, 1, 1;\n"
                 : "+f"(d[0]), "+f"(d[1]), "+f"(d[2]), "+f"(d[3]), "+f"(d[4]), "+f"(d[5]), "+f"(d[6]), "+f"(d[7]), "+f"(d[8]), "+f"(d[9]), "+f"(d[10]), "+f"(d[11])
                 : "r"(a0), "r"(a1), "r"(a2), "r"(a3), "l"(descB));
}

__device__ __forceinline__ void k1_panel(int g, int i, int& type, int& col) {
    if (g < 6) {
        int p = g * 5 + i;
        if (p < 8) { type = 0; col = p * 64; } else { type = 1; col = (p - 8) * 64; }
    } else {
        if (i < 3) { type = 1; col = (22 + (g - 6) * 3 + i) * 64; } else { type = 2 + (g - 6); col = 0; }
    }
}

constexpr int K1_STAGES = 4;
constexpr int K1_PANEL_BYTES = 64 * 128;
constexpr int K1_STAGE_BYTES = 16384 + 5 * K1_PANEL_BYTES;
constexpr int K1_SMEM = K1_STAGES * K1_STAGE_BYTES + 128 + 320 * 8;
constexpr float Q_SCALE = 0.25f * 1.4426950408889634f;

__global__ void __launch_bounds__(384, 1)
k1_proj(const __grid_constant__ CUtensorMap tm_x, const __grid_constant__ CUtensorMap tm_wq,
        const __grid_constant__ CUtensorMap tm_wk, const __grid_constant__ CUtensorMap tm_wv,
        const __grid_constant__ CUtensorMap tm_w1, const __grid_constant__ CUtensorMap tm_qo,
        const __grid_constant__ CUtensorMap tm_ho, const __nv_bfloat16* __restrict__ x, const __nv_bfloat16* __restrict__ b1,
        float2* rowstat, float* colpart, int* sync,
        __nv_bfloat16* __restrict__ kv, float* __restrict__ kvmax) {
    extern __shared__ __align__(1024) uint8_t smem_raw[];
    const uint32_t sbase = smem_u32(smem_raw);
    const uint32_t bar_full = sbase + K1_STAGES * K1_STAGE_BYTES, bar_empty = bar_full + 8 * K1_STAGES, bar_col = bar_empty + 8 * K1_STAGES;
    const uint32_t sCol = bar_full + 128;
    const int tid = threadIdx.x, warp = __shfl_sync(0xffffffffu, tid >> 5, 0), lane = tid & 31;
    const int crank = blockIdx.x & 1, grp = (blockIdx.x >> 1) & 7, rb = (blockIdx.x >> 4) * 2 + crank;
    const int npanels = grp < 6 ? 5 : 4;
    if (tid == 0) DEV_STAMP(0, 0);

    uint4 v[2][2];
    if (warp < 8) {
        const uint4* xp = reinterpret_cast<const uint4*>(x + (size_t)(rb * 128 + grp * 16 + warp * 2) * D_MODEL);
#pragma unroll
        for (int r = 0; r < 2; r++) { v[r][0] = __ldg(xp + r * 64 + lane); v[r][1] = __ldg(xp + r * 64 + 32 + lane); }
    }
    const int krot = rb & 8 ? 4 : 0, cstage = (rb >> 1) & 3;
    if (tid == 256) {
        for (int s = 0; s < K1_STAGES; s++) { mbar_init(bar_full + 8 * s, 1); mbar_init(bar_empty + 8 * s, s == cstage ? 18 : 16); }
        mbar_init(bar_col, 96);
        mbar_init_fence();
    }
    if (tid >= 128 && tid < 130) sync[256 + (tid - 128) * 128 + blockIdx.x] = 0;
    cluster_sync_relaxed();
    pdl_launch();

    if (warp >= 8) {
        reg_dealloc<88>();
            if (warp == 8) {
            if (lane == 0) {
                const CUtensorMap* tms[5]; int cols[5];
#pragma unroll
                for (int i = 0; i < 5; i++) {
                    int type, col; k1_panel(grp, i, type, col);
                    tms[i] = type == 0 ? &tm_wq : type == 1 ? &tm_w1 : type == 2 ? &tm_wk : &tm_wv;
                    cols[i] = col;
                }
                for (int ks = 0; ks < 8; ks++) {
                    const int s = ks % K1_STAGES;
                    const uint32_t st = sbase + s * K1_STAGE_BYTES;
                    mbar_wait(bar_empty + 8 * s, ((ks / K1_STAGES) & 1) ^ 1);
                    mbar_expect_tx(bar_full + 8 * s, 16384 + npanels * K1_PANEL_BYTES);
                    const int k0 = ((ks + krot) & 7) * 64;
                    tma_load_2d(st, &tm_x, k0, rb * 128, bar_full + 8 * s);
#pragma unroll
                    for (int i = 0; i < 5; i++)
                        if (i < npanels && ((i + ks + crank) & 1) == 0)
                            tma_load_2d_mc(st + 16384 + i * K1_PANEL_BYTES, tms[i], cols[i], k0, bar_full + 8 * s, (uint16_t)3);
                }
            }
        } else {
            const int ht = tid - 288;
            mbar_wait(bar_full + 8 * cstage, 0);
            {
                const int pc = ht >> 1, half = ht & 1;
                float sacc[8];
#pragma unroll
                for (int c = 0; c < 8; c++) sacc[c] = 0.f;
                if (pc < npanels * 8) {
                    const uint32_t pb = sbase + cstage * K1_STAGE_BYTES + 16384 + (pc >> 3) * K1_PANEL_BYTES;
#pragma unroll
                    for (int i = 0; i < 16; i++) {
                        const int k = crank * 32 + 2 * i + half;
                        uint4 u;
                        asm volatile("ld.shared.v4.b32 {%0,%1,%2,%3}, [%4];" : "=r"(u.x), "=r"(u.y), "=r"(u.z), "=r"(u.w)
                                     : "r"(pb + k * 128 + (((pc & 7) ^ (k & 7)) << 4)));
                        sacc[0] += bf_lo(u.x); sacc[1] += bf_hi(u.x); sacc[2] += bf_lo(u.y); sacc[3] += bf_hi(u.y);
                        sacc[4] += bf_lo(u.z); sacc[5] += bf_hi(u.z); sacc[6] += bf_lo(u.w); sacc[7] += bf_hi(u.w);
                    }
                }
#pragma unroll
                for (int c = 0; c < 8; c++) sacc[c] += __shfl_xor_sync(0xffffffffu, sacc[c], 1);
                if (pc < npanels * 8) {
                    float4* dst = reinterpret_cast<float4*>(colpart + (grp * 16 + rb) * 320 + pc * 8) + half;
                    *dst = half ? make_float4(xch_enc(sacc[4]), xch_enc(sacc[5]), xch_enc(sacc[6]), xch_enc(sacc[7]))
                                : make_float4(xch_enc(sacc[0]), xch_enc(sacc[1]), xch_enc(sacc[2]), xch_enc(sacc[3]));
                }
                named_bar_sync(4, 96);
                if (ht < 2) mbar_arrive_remote(bar_empty + 8 * cstage, ht);
            }
            if (ht == 0) DEV_STAMP(0, 6);
            for (int c2 = ht; c2 < npanels * 32; c2 += 96) {
                int type, col; k1_panel(grp, c2 >> 5, type, col);
                uint32_t bb = 0;
                if (type == 1) bb = __ldg(reinterpret_cast<const uint32_t*>(b1 + col) + (c2 & 31));
                uint2 pv[16];
                bool okv = false;
#pragma unroll 1
                for (uint32_t n = 0; n < (1u << 14) && !okv; n++) {
                    okv = true;
#pragma unroll
                    for (int k = 0; k < 16; k++) pv[k] = ld_relaxed_v2(colpart + (grp * 16 + k) * 320 + c2 * 2);
#pragma unroll
                    for (int k = 0; k < 16; k++) okv = okv && pv[k].x != NOT_READY && pv[k].y != NOT_READY;
                }
                float s0 = 0.f, s1 = 0.f;
#pragma unroll
                for (int k = 0; k < 16; k++) { s0 += xch_dec(pv[k].x); s1 += xch_dec(pv[k].y); }
                asm volatile("st.shared.v4.f32 [%0], {%1,%2,%3,%4};" ::"r"(sCol + c2 * 16), "f"(s0), "f"(bf_lo(bb)), "f"(s1), "f"(bf_hi(bb)) : "memory");
            }
            mbar_arrive(bar_col);
            if (ht == 0) DEV_STAMP(0, 7);
        }
    } else {
        reg_alloc<208>();
        const int wg = warp >> 2;
        const int g = lane >> 2, t = lane & 3;
        const int wrow = (warp & 3) * 16;
        {
            float f[2][16], sum[2], sq[2];
#pragma unroll
            for (int r = 0; r < 2; r++) {
                const uint32_t w[8] = {v[r][0].x, v[r][0].y, v[r][0].z, v[r][0].w, v[r][1].x, v[r][1].y, v[r][1].z, v[r][1].w};
#pragma unroll
                for (int i = 0; i < 8; i++) { f[r][2 * i] = bf_lo(w[i]); f[r][2 * i + 1] = bf_hi(w[i]); }
                sum[r] = 0.f;
#pragma unroll
                for (int i = 0; i < 16; i++) sum[r] += f[r][i];
            }
#pragma unroll
            for (int o = 16; o > 0; o >>= 1) { sum[0] += __shfl_xor_sync(0xffffffffu, sum[0], o); sum[1] += __shfl_xor_sync(0xffffffffu, sum[1], o); }
#pragma unroll
            for (int r = 0; r < 2; r++) {
                sum[r] *= (1.0f / D_MODEL);
                sq[r] = 0.f;
#pragma unroll
                for (int i = 0; i < 16; i++) { const float d = f[r][i] - sum[r]; sq[r] += d * d; }
            }
#pragma unroll
            for (int o = 16; o > 0; o >>= 1) { sq[0] += __shfl_xor_sync(0xffffffffu, sq[0], o); sq[1] += __shfl_xor_sync(0xffffffffu, sq[1], o); }
            if (lane < 2) {
                const float rstd = rsqrtf((lane ? sq[1] : sq[0]) * (1.0f / D_MODEL) + 1e-5f);
                rowstat[rb * 128 + grp * 16 + warp * 2 + lane] = make_float2(xch_enc(rstd), (lane ? sum[1] : sum[0]) * rstd);
            }
            if (tid == 0) DEV_STAMP(0, 5);
        }
        float acc[160];
#pragma unroll
        for (int i = 0; i < 160; i++) acc[i] = 0.f;
        float2 rs0, rs1;
        const uint64_t dA0 = make_desc(sbase + wg * 8192, 16, 1024, 1);
        const uint64_t dB0 = make_desc(sbase + 16384, K1_PANEL_BYTES, 1024, 1);
#define K1_MAINLOOP(FIVE)                                                                                          \
        for (int ks = 0; ks < 8; ks++) {                                                                           \
            const int s = ks % K1_STAGES;                                                                          \
            mbar_wait(bar_full + 8 * s, (ks / K1_STAGES) & 1);                                                     \
            if (ks == 0 && tid == 0) DEV_STAMP(0, 1);                                                              \
            wg_fence();                                                                                            \
            _Pragma("unroll") for (int kk = 0; kk < 4; kk++) {                                                     \
                const uint64_t dA = dA0 + (uint64_t)((s * K1_STAGE_BYTES + kk * 32) >> 4);                         \
                const uint64_t dB = dB0 + (uint64_t)((s * K1_STAGE_BYTES + kk * 2048) >> 4);                       \
                wgmma_ss_n256_tb(acc, dA, dB, (ks | kk) != 0);                                                     \
                if (FIVE) wgmma_ss_n64_tb(acc + 128, dA, dB + (uint64_t)((4 * K1_PANEL_BYTES) >> 4), (ks | kk) != 0); \
            }                                                                                                      \
            wg_commit();                                                                                           \
            if (ks == 7) {                                                                                         \
                uint2 r0, r1;                                                                                      \
                uint32_t n = 0;                                                                                    \
                _Pragma("unroll 1") do {                                                                           \
                    r0 = ld_relaxed_v2(rowstat + rb * 128 + wg * 64 + wrow + g);                                   \
                    r1 = ld_relaxed_v2(rowstat + rb * 128 + wg * 64 + wrow + g + 8);                               \
                } while ((r0.x == NOT_READY || r1.x == NOT_READY) && ++n < (1u << 14));                            \
                rs0 = make_float2(xch_dec(r0.x), __uint_as_float(r0.y));                                           \
                rs1 = make_float2(xch_dec(r1.x), __uint_as_float(r1.y));                                           \
                mbar_wait(bar_col, 0);                                                                             \
            }                                                                                                      \
            if (ks > 0 && ks <= 4) {                                                                               \
                wg_wait<1>();                                                                                      \
                if (lane < 2) mbar_arrive_remote(bar_empty + 8 * ((ks - 1) % K1_STAGES), lane);                    \
            }                                                                                                      \
        }                                                                                                          \
        wg_wait<0>();
        if (npanels == 5) { K1_MAINLOOP(true) } else { K1_MAINLOOP(false) }
        fence_regs<160>(acc);
        if (tid == 0) DEV_STAMP(0, 2);
        named_bar_sync(1, 256);
        const int srow = (lane & 7) + ((lane >> 3) & 1) * 8;
#pragma unroll
        for (int p = 0; p < 5; p++) {
            if (p < npanels) {
                int type, col; k1_panel(grp, p, type, col);
                float* a = acc + p * 32;
                const int nj = type <= 1 ? 8 : 2;
                const float sc = type == 0 ? Q_SCALE : 1.0f;
                const float r0x = rs0.x * sc, r0y = -rs0.y * sc, r1x = rs1.x * sc, r1y = -rs1.y * sc;
#pragma unroll
                for (int j = 0; j < 8; j++) {
                    if (j < nj) {
                        float4 c;
                        asm volatile("ld.shared.v4.f32 {%0,%1,%2,%3}, [%4];" : "=f"(c.x), "=f"(c.y), "=f"(c.z), "=f"(c.w)
                                     : "r"(sCol + (p * 64 + j * 8 + 2 * t) * 8));
                        a[4 * j] = fmaf(a[4 * j], r0x, fmaf(r0y, c.x, c.y));
                        a[4 * j + 1] = fmaf(a[4 * j + 1], r0x, fmaf(r0y, c.z, c.w));
                        a[4 * j + 2] = fmaf(a[4 * j + 2], r1x, fmaf(r1y, c.x, c.y));
                        a[4 * j + 3] = fmaf(a[4 * j + 3], r1x, fmaf(r1y, c.z, c.w));
                    }
                }
                if (type <= 1) {
                    const uint32_t stg = sbase + (p * 8 + warp) * 2048;
                    uint32_t pk[16];
                    if (type == 0) {
#pragma unroll
                        for (int j = 0; j < 8; j++) {
                            pk[2 * j] = pack_bf16(a[4 * j], a[4 * j + 1]);
                            pk[2 * j + 1] = pack_bf16(a[4 * j + 2], a[4 * j + 3]);
                        }
                    } else {
#pragma unroll
                        for (int j = 0; j < 8; j++) {
                            const uint32_t h0 = pack_bf16_relu(a[4 * j], a[4 * j + 1]), h1 = pack_bf16_relu(a[4 * j + 2], a[4 * j + 3]);
                            pk[2 * j] = mul_bf16x2(h0, h0);
                            pk[2 * j + 1] = mul_bf16x2(h1, h1);
                        }
                    }
#pragma unroll
                    for (int j = 0; j < 8; j += 2) {
                        const int c16 = j + (lane >> 4);
                        stmatrix_x4(stg + srow * 128 + ((c16 ^ (srow & 7)) << 4), pk[2 * j], pk[2 * j + 1], pk[2 * j + 2], pk[2 * j + 3]);
                    }
                    if (p == 2 || p == 4) {
                        fence_proxy_async();
                        __syncwarp();
                        if (lane == 0) {
                            const int pfirst = p == 2 ? 0 : 3;
#pragma unroll 1
                            for (int p2 = pfirst; p2 <= p; p2++) {
                                const int gp = grp < 6 ? grp * 5 + p2 : 30 + (grp - 6) * 3 + p2;
                                if (gp < 8) tma_store_2d(&tm_qo, sbase + (p2 * 8 + warp) * 2048, gp * 64, rb * 128 + warp * 16);
                                else tma_store_2d(&tm_ho, sbase + (p2 * 8 + warp) * 2048, (gp - 8) * 64, rb * 128 + warp * 16);
                            }
                            tma_store_commit();
                        }
                    }
                } else if (type == 3) {
                    const int r = wg * 64 + wrow + g;
                    const int pos0 = (r >> 2) * 64 + rb * 4 + (r & 3), pos1 = pos0 + 128;
                    uint32_t* dst = reinterpret_cast<uint32_t*>(kv);
                    const uint32_t r00 = pack_bf16(a[0], a[1]), r01 = pack_bf16(a[4], a[5]);
                    const uint32_t r10 = pack_bf16(a[2], a[3]), r11 = pack_bf16(a[6], a[7]);
                    dst[(pos0 >> 4) * 128 + (pos0 & 15) * 4 + t] = r00;
                    dst[16384 + pos0 * 4 + t] = r01;
                    dst[(pos1 >> 4) * 128 + (pos1 & 15) * 4 + t] = r10;
                    dst[16384 + pos1 * 4 + t] = r11;
                    float m = fmaxf(fmaxf(fmaxf(fabsf(bf_lo(r00)), fabsf(bf_hi(r00))), fmaxf(fabsf(bf_lo(r01)), fabsf(bf_hi(r01)))),
                                    fmaxf(fmaxf(fabsf(bf_lo(r10)), fabsf(bf_hi(r10))), fmaxf(fabsf(bf_lo(r11)), fabsf(bf_hi(r11)))));
#pragma unroll
                    for (int o = 16; o > 0; o >>= 1) m = fmaxf(m, __shfl_xor_sync(0xffffffffu, m, o));
                    if (lane == 0) kvmax[128 + rb * 8 + warp] = m;
                    named_bar_sync(1, 256);
                    if (tid == 0) signal_add(sync);
                } else {
                    float* kf = reinterpret_cast<float*>(smem_raw + 96 * 1024);
                    const int r = wg * 64 + wrow + g;
                    const int pos0 = (r >> 2) * 64 + rb * 4 + (r & 3), pos1 = pos0 + 128;
                    uint32_t* dst = reinterpret_cast<uint32_t*>(kv) + 32768;
                    dst[(pos0 >> 3) * 64 + (pos0 & 7) * 4 + t] = pack_bf16(a[0], a[1]);
                    dst[(pos0 >> 3) * 64 + 32 + (pos0 & 7) * 4 + t] = pack_bf16(a[4], a[5]);
                    dst[(pos1 >> 3) * 64 + (pos1 & 7) * 4 + t] = pack_bf16(a[2], a[3]);
                    dst[(pos1 >> 3) * 64 + 32 + (pos1 & 7) * 4 + t] = pack_bf16(a[6], a[7]);
                    kf[r * 17 + 2 * t] = a[0]; kf[r * 17 + 2 * t + 1] = a[1];
                    kf[r * 17 + 8 + 2 * t] = a[4]; kf[r * 17 + 8 + 2 * t + 1] = a[5];
                    kf[(r + 8) * 17 + 2 * t] = a[2]; kf[(r + 8) * 17 + 2 * t + 1] = a[3];
                    kf[(r + 8) * 17 + 8 + 2 * t] = a[6]; kf[(r + 8) * 17 + 8 + 2 * t + 1] = a[7];
                    named_bar_sync(1, 256);
                    if (tid < 64) {
                        const int i = tid >> 4, dim = tid & 15;
                        const int c = rb * 4 + i;
                        const int inner = (dim >> 3) * 64 + (c & 7) * 8 + (dim & 7);
                        float kt = 0.f;
#pragma unroll 8
                        for (int j = 0; j < 32; j++) {
                            const __nv_bfloat16 d = __float2bfloat16_rn(kf[(j * 4 + i) * 17 + dim] - kt);
                            kt += __bfloat162float(d);
                            kf[(j * 4 + i) * 17 + dim] = kt;
                            const int grp8 = j * 8 + (c >> 3);
                            kv[(grp8 < 128 ? grp8 * 256 + 128 : 49152 + (grp8 - 128) * 128) + inner] = d;
                        }
                    }
                    named_bar_sync(1, 256);
                    if (tid < 128) {
                        float n = 0.f;
#pragma unroll
                        for (int d = 0; d < 16; d++) { const float v = kf[tid * 17 + d]; n += v * v; }
                        if (!(n == n)) n = __int_as_float(0x7f800000);
#pragma unroll
                        for (int o = 8; o > 0; o >>= 1) n = fmaxf(n, __shfl_xor_sync(0xffffffffu, n, o));
                        if ((lane & 15) == 0) kvmax[rb * 8 + (tid >> 4)] = n;
                    }
                    named_bar_sync(1, 256);
                    if (tid == 0) signal_add(sync);
                }
            }
        }
        if (tid == 0) DEV_STAMP(0, 3);
        if (lane == 0) {
            tma_store_wait();
            if (grp < 2) signal_add(sync + 128 + rb * 8 + warp);
        }
        if (tid == 0) DEV_STAMP(0, 4);
    }
}

constexpr int AT_KT = 64;
constexpr int AT_NCHUNK = 8;
constexpr int AT_NSTEP = S_LEN / AT_KT;
constexpr int AT_SPC = AT_NSTEP / AT_NCHUNK;
constexpr int AT_ONES = 131072;
constexpr int F2_STAGES = 4;
constexpr int F2_STAGE_BYTES = 8192 + 16384;
constexpr int F2_BASE = 132096;
constexpr int F2_NK = F_DIM / 64;
constexpr int AT_BAR = F2_BASE + F2_STAGES * F2_STAGE_BYTES;
constexpr int AT_SMEM = AT_BAR + 256;
#define AT_SWMASK_V 0xB6DB
constexpr uint32_t AT_SWMASK = AT_SWMASK_V;

#define AT_MAGIC (383.0f + 0.00390625f - 0.5849625f)
__device__ __forceinline__ uint32_t exp2_pair_alu(float t0, float t1) {
    uint32_t y;
    asm("prmt.b32 %0, %1, %2, 0x6521;" : "=r"(y) : "f"(t0), "f"(t1));
    const uint32_t e = y & 0x7F807F80u;
    uint32_t uh, p;
    asm("lop3.b32 %0, %1, %2, 0x3F003F00, 0xBE;" : "=r"(uh) : "r"(y), "r"(e));
    asm("fma.rn.bf16x2 %0, %1, %2, %3;" : "=r"(p) : "r"(uh), "r"(y), "r"(e));
    return p;
}

__device__ __forceinline__ void at_load_chunk(uint32_t sbase, const __nv_bfloat16* KV, uint32_t bar0, int c) {
    const uint8_t* src = reinterpret_cast<const uint8_t*>(KV);
    const uint32_t off = c < 4 ? c * 16384 : 98304 + (c - 4) * 8192, bytes = c < 4 ? 16384 : 8192;
    mbar_expect_tx(bar0 + 8 * c, bytes + 4096);
    bulk_g2s(sbase + off, src + off, bytes, bar0 + 8 * c);
    bulk_g2s(sbase + 65536 + c * 4096, src + 65536 + c * 4096, 4096, bar0 + 8 * c);
}

__device__ __forceinline__ void at_store(const float* o, __nv_bfloat16* O, int row, int lane) {
    const float l0 = __shfl_sync(0xffffffffu, o[8], lane & ~3);
    const float l1 = __shfl_sync(0xffffffffu, o[10], lane & ~3);
    const float r0 = __fdividef(1.0f, l0), r1 = __fdividef(1.0f, l1);
    const int t = lane & 3;
    uint32_t* op = reinterpret_cast<uint32_t*>(O + (size_t)(row + (lane >> 2)) * 16);
    op[t] = pack_bf16(o[0] * r0, o[1] * r0);
    op[t + 4] = pack_bf16(o[4] * r0, o[5] * r0);
    op[64 + t] = pack_bf16(o[2] * r1, o[3] * r1);
    op[64 + t + 4] = pack_bf16(o[6] * r1, o[7] * r1);
}

__device__ __forceinline__ void mma16816(float* c, const uint32_t* a, uint32_t b0, uint32_t b1) {
    asm volatile("mma.sync.aligned.m16n8k16.row.col.f32.bf16.bf16.f32 {%0,%1,%2,%3}, {%4,%5,%6,%7}, {%8,%9}, {%0,%1,%2,%3};"
                 : "+f"(c[0]), "+f"(c[1]), "+f"(c[2]), "+f"(c[3]) : "r"(a[0]), "r"(a[1]), "r"(a[2]), "r"(a[3]), "r"(b0), "r"(b1));
}
__device__ __forceinline__ void attn_fallback(const __nv_bfloat16* Q, const __nv_bfloat16* KV, __nv_bfloat16* O, uint32_t sbase) {
    const int tid = threadIdx.x;
    const int lane = tid & 31, g = lane >> 2, t = lane & 3;
    const uint32_t* Kg = reinterpret_cast<const uint32_t*>(KV + 65536);
#pragma unroll 1
    for (int mt = 0; mt < 2; mt++) {
        const int row = blockIdx.x * 512 + (tid >> 7) * 128 + mt * 64 + ((tid >> 5) & 3) * 16;
        const uint32_t* qp = reinterpret_cast<const uint32_t*>(Q + (size_t)(row + g) * 16);
        const uint32_t q[4] = {__ldcg(qp + t), __ldcg(qp + 64 + t), __ldcg(qp + t + 4), __ldcg(qp + 64 + t + 4)};
        float o[12];
#pragma unroll
        for (int i = 0; i < 12; i++) o[i] = 0.f;
        float m0 = -INFINITY, m1 = -INFINITY;
#pragma unroll 1
        for (int kt = 0; kt < S_LEN / 16; kt++) {
            float s[8];
#pragma unroll
            for (int i = 0; i < 8; i++) s[i] = 0.f;
#pragma unroll
            for (int h = 0; h < 2; h++) {
                const uint32_t* kp = Kg + (kt * 2 + h) * 64 + g * 4 + t;
                mma16816(s + 4 * h, q, __ldcg(kp), __ldcg(kp + 32));
            }
            float x0 = fmaxf(fmaxf(s[0], s[1]), fmaxf(s[4], s[5])), x1 = fmaxf(fmaxf(s[2], s[3]), fmaxf(s[6], s[7]));
            x0 = fmaxf(x0, __shfl_xor_sync(0xffffffffu, x0, 1)); x0 = fmaxf(x0, __shfl_xor_sync(0xffffffffu, x0, 2));
            x1 = fmaxf(x1, __shfl_xor_sync(0xffffffffu, x1, 1)); x1 = fmaxf(x1, __shfl_xor_sync(0xffffffffu, x1, 2));
            x0 = fmaxf(x0, m0); x1 = fmaxf(x1, m1);
            const float f0 = ex2(m0 - x0), f1 = ex2(m1 - x1);
            m0 = x0; m1 = x1;
#pragma unroll
            for (int j = 0; j < 3; j++) { o[4 * j] *= f0; o[4 * j + 1] *= f0; o[4 * j + 2] *= f1; o[4 * j + 3] *= f1; }
            const uint32_t p[4] = {pack_bf16(ex2(s[0] - m0), ex2(s[1] - m0)), pack_bf16(ex2(s[2] - m1), ex2(s[3] - m1)),
                                   pack_bf16(ex2(s[4] - m0), ex2(s[5] - m0)), pack_bf16(ex2(s[6] - m1), ex2(s[7] - m1))};
#pragma unroll
            for (int j = 0; j < 3; j++) {
                const uint32_t base = sbase + (j == 0 ? kt * 512 : j == 1 ? 65536 + kt * 256 : AT_ONES) + (lane & 15) * 16;
                uint32_t b0, b1;
                asm volatile("ldmatrix.sync.aligned.m8n8.x2.trans.shared.b16 {%0,%1}, [%2];" : "=r"(b0), "=r"(b1) : "r"(base));
                mma16816(o + 4 * j, p, b0, b1);
            }
        }
        at_store(o, O, row, lane);
    }
}

__global__ void __launch_bounds__(640, 1)
k2_attn(const __grid_constant__ CUtensorMap tm_h, const __grid_constant__ CUtensorMap tm_w2,
        const __nv_bfloat16* __restrict__ Q, const __nv_bfloat16* __restrict__ KV, const float* __restrict__ kvmax,
        const __nv_bfloat16* __restrict__ b2, __nv_bfloat16* __restrict__ O, __nv_bfloat16* __restrict__ G,
        uint2* __restrict__ rowstat, uint2* __restrict__ colpart, int* sync) {
    extern __shared__ __align__(1024) uint8_t smem_raw[];
    const uint32_t sbase = smem_u32(smem_raw);
    const uint32_t bar0 = sbase + AT_BAR, f2_full = bar0 + 64, f2_empty = f2_full + 64;
    const int tid = threadIdx.x;
    const int wg = __shfl_sync(0xffffffffu, tid >> 7, 0);
    const int warp = (tid >> 5) & 3, lane = tid & 31;
    const int g = lane >> 2, t = lane & 3;
    if (tid == 0) DEV_STAMP(1, 0);
    if (tid == 0) {
        for (int i = 0; i < AT_NCHUNK; i++) mbar_init(bar0 + 8 * i, 1);
        for (int i = 0; i < F2_STAGES; i++) { mbar_init(f2_full + 8 * i, 1); mbar_init(f2_empty + 8 * i, 4); }
        mbar_init_fence();
    }
    if (tid < 16) asm volatile("st.shared.v4.b32 [%0], {%1,%2,%2,%2};" ::"r"(sbase + AT_ONES + tid * 16), "r"(0x00003F80u), "r"(0u) : "memory");
    fence_proxy_async();
    __syncthreads();

    if (wg == 4) {
        const int rb = blockIdx.x >> 2, cb = blockIdx.x & 3;
        const uint32_t fb = sbase + F2_BASE;
        const bool leader = tid == 512;
        if (leader) {
#pragma unroll
            for (int s = 0; s < F2_STAGES; s++) {
                mbar_expect_tx(f2_full + 8 * s, F2_STAGE_BYTES);
                tma_load_2d(fb + s * F2_STAGE_BYTES + 8192, &tm_w2, cb * 128, s * 64, f2_full + 8 * s);
                tma_load_2d(fb + s * F2_STAGE_BYTES + 16384, &tm_w2, cb * 128 + 64, s * 64, f2_full + 8 * s);
            }
        }
        pdl_wait();
        pdl_launch();
        if (leader) {
#pragma unroll
            for (int s = 0; s < F2_STAGES; s++) tma_load_2d(fb + s * F2_STAGE_BYTES, &tm_h, s * 64, rb * 64, f2_full + 8 * s);
        }
        colpart[blockIdx.x * 160 + tid - 512] = make_uint2(NOT_READY, NOT_READY);
        if (tid < 544) colpart[blockIdx.x * 160 + 128 + tid - 512] = make_uint2(NOT_READY, NOT_READY);
        if (tid >= 544 && tid < 560) rowstat[blockIdx.x * 16 + tid - 544] = make_uint2(NOT_READY, NOT_READY);
        __syncwarp();
        const uint64_t dA0 = make_desc(fb, 16, 1024, 1);
        const uint64_t dB0 = make_desc(fb + 8192, 8192, 1024, 1);
        float acc[64];
#pragma unroll
        for (int i = 0; i < 64; i++) asm volatile("mov.f32 %0, 0f00000000;" : "=f"(acc[i]));
#pragma unroll 1
        for (int ks = 0; ks < F2_NK; ks++) {
            const int s = ks % F2_STAGES;
            mbar_wait(f2_full + 8 * s, (ks / F2_STAGES) & 1);
            wg_fence();
#pragma unroll
            for (int kk = 0; kk < 4; kk++)
                wgmma_ss_n128_tb(acc, dA0 + (uint64_t)((s * F2_STAGE_BYTES + kk * 32) >> 4),
                                 dB0 + (uint64_t)((s * F2_STAGE_BYTES + kk * 2048) >> 4), 1);
            wg_commit();
            wg_wait<1>();
            if (ks > 0 && ks - 1 + F2_STAGES < F2_NK) {
                const int ps = (ks - 1) % F2_STAGES, k0 = (ks - 1 + F2_STAGES) * 64;
                if (lane == 0) mbar_arrive(f2_empty + 8 * ps);
                if (leader) {
                    mbar_wait(f2_empty + 8 * ps, ((ks - 1) / F2_STAGES) & 1);
                    mbar_expect_tx(f2_full + 8 * ps, F2_STAGE_BYTES);
                    tma_load_2d(fb + ps * F2_STAGE_BYTES, &tm_h, k0, rb * 64, f2_full + 8 * ps);
                    tma_load_2d(fb + ps * F2_STAGE_BYTES + 8192, &tm_w2, cb * 128, k0, f2_full + 8 * ps);
                    tma_load_2d(fb + ps * F2_STAGE_BYTES + 16384, &tm_w2, cb * 128 + 64, k0, f2_full + 8 * ps);
                }
                __syncwarp();
            }
        }
        wg_wait<0>();
        fence_regs<64>(acc);
        uint32_t* gp = reinterpret_cast<uint32_t*>(G + (size_t)(rb * 64 + warp * 16 + g) * D_MODEL + cb * 128) + t;
#pragma unroll
        for (int j = 0; j < 16; j++) {
            const uint32_t bb = __ldg(reinterpret_cast<const uint32_t*>(b2 + cb * 128 + j * 8) + t);
            const float b0 = bf_lo(bb), b1v = bf_hi(bb);
            const float z0 = acc[4 * j] + b0, z1 = acc[4 * j + 1] + b1v, z2 = acc[4 * j + 2] + b0, z3 = acc[4 * j + 3] + b1v;
            gp[j * 4] = pack_bf16(__fdividef(z0, 1.0f + __expf(-z0)), __fdividef(z1, 1.0f + __expf(-z1)));
            gp[j * 4 + 8 * (D_MODEL / 2)] = pack_bf16(__fdividef(z2, 1.0f + __expf(-z2)), __fdividef(z3, 1.0f + __expf(-z3)));
        }
        __syncwarp();
        if (lane == 0) signal_add(sync + 384 + blockIdx.x);
        if (leader) DEV_STAMP(1, 5);
        return;
    }

    if (tid == 0) {
        wait_count(sync, 32);
        DEV_STAMP(1, 1);
        at_load_chunk(sbase, KV, bar0, 0); at_load_chunk(sbase, KV, bar0, 1); at_load_chunk(sbase, KV, bar0, 2);
    }
    if (lane == 0) wait_count(sync + 128 + blockIdx.x, 2);
    __syncwarp();
    const int rowA = blockIdx.x * 512 + wg * 128 + warp * 16;
    const uint32_t* qp = reinterpret_cast<const uint32_t*>(Q + (size_t)(rowA + g) * 16);
    const uint32_t lo0 = ((sbase & 0x3FFFF) >> 4) | (8u << 16);

#define AT_EXP(P) _Pragma("unroll") for (int i = 0; i < AT_KT / 4; i++) {                       \
                if ((AT_SWMASK >> (i & 15)) & 1) P[i] = exp2_pair_alu(s[2 * i], s[2 * i + 1]);  \
                else P[i] = pack_bf16(ex2(s[2 * i]), ex2(s[2 * i + 1])); }
#define AT_PV(P, st) _Pragma("unroll") for (int j = 0; j < AT_KT / 16; j++)                     \
                wgmma_pv(o, P[4 * j], P[4 * j + 1], P[4 * j + 2], P[4 * j + 3],                 \
                         desc64(vlo + ((st) * 4 + j) * 32, vhi - ((st) * 4 + j) * 16));
#define AT_PIPE 0
#define AT_STEP(st, PC, PN, klo, khi) {                                                         \
                wg_wait<0>();                                                                   \
                fence_regs<AT_KT / 2>(s);                                                       \
                AT_EXP(p0);                                                                     \
                if (st == AT_SPC - 1 && mt == 0) mbar_wait(bar0 + 8 * (c + 1), 0);              \
                wg_fence();                                                                     \
                wgmma_qk_acc_n64(s, q, desc64(klo, khi));                                       \
                AT_PV(p0, st);                                                                  \
                wg_commit(); }

#pragma unroll 1
    for (int mt = 0; mt < 2; mt++) {
        uint32_t q[4];
        q[0] = __ldcg(qp + mt * 512 + t); q[2] = __ldcg(qp + mt * 512 + t + 4);
        q[1] = __ldcg(qp + mt * 512 + 64 + t); q[3] = __ldcg(qp + mt * 512 + 64 + t + 4);
        float o[12];
#pragma unroll
        for (int i = 0; i < 12; i++) asm volatile("mov.f32 %0, 0f00000000;" : "=f"(o[i]));
        float s[AT_KT / 2];
        uint32_t p0[AT_KT / 4], p1[AT_KT / 4];
        (void)p1;
#pragma unroll
        for (int i = 0; i < AT_KT / 2; i++) {
            if ((AT_SWMASK >> ((i >> 1) & 15)) & 1) asm volatile("mov.f32 %0, %1;" : "=f"(s[i]) : "f"(AT_MAGIC));
            else asm volatile("mov.f32 %0, 0f00000000;" : "=f"(s[i]));
        }
        if (mt == 0) mbar_wait(bar0, 0);
        if (tid == 0) DEV_STAMP(1, 2 + mt);
        uint32_t klo = lo0 + 16, vlo = lo0, vhi = 4096;
        wg_fence();
        wgmma_qk_acc_n64(s, q, desc64(klo, 32));
        wg_commit();
        uint32_t kst = 256, khi = 32;
#pragma unroll 1
        for (int c = 0; c < AT_NCHUNK - 1; c++) {
            if (tid == 0 && mt == 0 && c + 3 < AT_NCHUNK) at_load_chunk(sbase, KV, bar0, c + 3);
            AT_STEP(0, p0, p1, klo + kst, khi); AT_STEP(1, p1, p0, klo + 2 * kst, khi); AT_STEP(2, p0, p1, klo + 3 * kst, khi);
            if (c == 3) { klo = lo0 + (98304 >> 4); kst = 128; khi = 16; } else klo += 4 * kst;
            AT_STEP(3, p1, p0, klo, khi);
            vlo += 512; vhi -= 256;
        }
        {
            const int c = 0; (void)c;
            AT_STEP(0, p0, p1, klo + 128, 16); AT_STEP(1, p1, p0, klo + 256, 16); AT_STEP(2, p0, p1, klo + 384, 16);
            wg_wait<0>();
            fence_regs<AT_KT / 2>(s);
            AT_EXP(p0);
            wg_fence();
            AT_PV(p0, 3);
            wg_commit();
            wg_wait<0>();
            fence_regs<12>(o);
        }
        at_store(o, O, rowA + mt * 64, lane);
    }
    if (tid == 0) DEV_STAMP(1, 4);

    bool unsafe;
    {
        float km = fmaxf(fmaxf(__ldcg(kvmax + lane), __ldcg(kvmax + lane + 32)), fmaxf(__ldcg(kvmax + lane + 64), __ldcg(kvmax + lane + 96)));
        float vm = fmaxf(fmaxf(__ldcg(kvmax + 128 + lane), __ldcg(kvmax + 160 + lane)), fmaxf(__ldcg(kvmax + 192 + lane), __ldcg(kvmax + 224 + lane)));
#pragma unroll
        for (int o = 16; o > 0; o >>= 1) { km = fmaxf(km, __shfl_xor_sync(0xffffffffu, km, o)); vm = fmaxf(vm, __shfl_xor_sync(0xffffffffu, vm, o)); }
        const uint4* qr = reinterpret_cast<const uint4*>(Q + (size_t)(rowA + (lane >> 4) * 64 + (lane & 15)) * 16);
        const uint4 qa = __ldcg(qr), qb = __ldcg(qr + 1);
        const uint32_t qw[8] = {qa.x, qa.y, qa.z, qa.w, qb.x, qb.y, qb.z, qb.w};
        float qn = 0.f;
#pragma unroll
        for (int i = 0; i < 8; i++) qn += bf_lo(qw[i]) * bf_lo(qw[i]) + bf_hi(qw[i]) * bf_hi(qw[i]);
        const bool ok = (qn * km <= 3600.0f) && (vm <= 1.0e12f);
        unsafe = __any_sync(0xffffffffu, !ok);
    }
    if (unsafe) attn_fallback(Q, KV, O, sbase);
    __syncwarp();
    if (lane == 0) signal_add(sync + 256 + (blockIdx.x >> 3));
}

constexpr int K3_STAGE_BYTES = 16384 + 8192;
constexpr int K3_X = 8 * K3_STAGE_BYTES;
constexpr int K3_G = K3_X + 16384;
constexpr int K3_SMEM = K3_G + 16384 + 256;

__global__ void __launch_bounds__(256, 1)
k3_out(const __grid_constant__ CUtensorMap tm_o, const __grid_constant__ CUtensorMap tm_wo,
       const __grid_constant__ CUtensorMap tm_x, const __grid_constant__ CUtensorMap tm_g,
       const __grid_constant__ CUtensorMap tm_out, int* sync) {
    extern __shared__ __align__(1024) uint8_t smem_raw[];
    const uint32_t sbase = smem_u32(smem_raw);
    const uint32_t sX = sbase + K3_X, sG = sbase + K3_G;
    const uint32_t bar_full = sG + 16384, bar_x = bar_full + 64;
    const int tid = threadIdx.x, warp = __shfl_sync(0xffffffffu, tid >> 5, 0), lane = tid & 31;
    const int rb = blockIdx.x >> 3, cb = blockIdx.x & 7;
    if (tid == 0) {
        DEV_STAMP(2, 0);
        for (int s = 0; s < 8; s++) mbar_init(bar_full + 8 * s, 1);
        mbar_init(bar_x, 1);
        mbar_init_fence();
        for (int s = 0; s < 8; s++) {
            mbar_expect_tx(bar_full + 8 * s, K3_STAGE_BYTES);
            tma_load_2d(sbase + s * K3_STAGE_BYTES + 16384, &tm_wo, cb * 64, s * 64, bar_full + 8 * s);
        }
        mbar_expect_tx(bar_x, 32768);
        tma_load_2d(sX, &tm_x, cb * 64, rb * 128, bar_x);
    }
    __syncthreads();
    if (lane == 0) {
        wait_count(sync + 256 + rb, 128);
        if (tid == 0) DEV_STAMP(2, 1);
        tma_load_2d(sbase + warp * K3_STAGE_BYTES, &tm_o, warp * 64, rb * 128, bar_full + 8 * warp);
        if (warp == 7) {
            wait_count(sync + 384 + rb * 8 + (cb >> 1), 4);
            wait_count(sync + 384 + rb * 8 + 4 + (cb >> 1), 4);
            tma_load_2d(sG, &tm_g, cb * 64, rb * 128, bar_x);
        }
    }
    __syncwarp();
    const int wg = warp >> 2;
    float acc[32];
#pragma unroll
    for (int i = 0; i < 32; i++) asm volatile("mov.f32 %0, 0f00000000;" : "=f"(acc[i]));
    const uint64_t dA0 = make_desc(sbase + wg * 8192, 16, 1024, 1);
    const uint64_t dB0 = make_desc(sbase + 16384, 8192, 1024, 1);
#pragma unroll 1
    for (int ks = 0; ks < 8; ks++) {
        mbar_wait(bar_full + 8 * ks, 0);
        wg_fence();
#pragma unroll
        for (int kk = 0; kk < 4; kk++)
            wgmma_ss_n64_tb(acc, dA0 + (uint64_t)((ks * K3_STAGE_BYTES + kk * 32) >> 4),
                            dB0 + (uint64_t)((ks * K3_STAGE_BYTES + kk * 2048) >> 4), 1);
        wg_commit();
    }
    wg_wait<0>();
    fence_regs<32>(acc);
    if (tid == 0) DEV_STAMP(2, 2);
    mbar_wait(bar_x, 0);
    const int g = lane >> 2, t = lane & 3;
    const int row0 = warp * 16 + g;
#pragma unroll
    for (int j = 0; j < 8; j++) {
#pragma unroll
        for (int h = 0; h < 2; h++) {
            const int row = row0 + h * 8;
            const uint32_t off = row * 128 + ((j ^ (row & 7)) << 4) + t * 4;
            uint32_t xv, gv;
            asm volatile("ld.shared.b32 %0, [%1];" : "=r"(xv) : "r"(sX + off) : "memory");
            asm volatile("ld.shared.b32 %0, [%1];" : "=r"(gv) : "r"(sG + off) : "memory");
            const uint32_t ov = pack_bf16(fmaf(acc[4 * j + 2 * h], bf_lo(gv), bf_lo(xv)), fmaf(acc[4 * j + 2 * h + 1], bf_hi(gv), bf_hi(xv)));
            asm volatile("st.shared.b32 [%0], %1;" ::"r"(sX + off), "r"(ov) : "memory");
        }
    }
    fence_proxy_async();
    __syncwarp();
    if (lane == 0) {
        tma_store_2d(&tm_out, sX + warp * 2048, cb * 64, rb * 128 + warp * 16);
        tma_store_commit();
        if (tid == 0) DEV_STAMP(2, 3);
        if (warp == 0) {
            pdl_wait();
            sync[128 + blockIdx.x] = 0;
            if (blockIdx.x == 0) sync[0] = 0;
        }
        tma_store_wait();
        if (tid == 0) DEV_STAMP(2, 4);
    }
}

typedef CUresult (*EncodeFn)(CUtensorMap*, CUtensorMapDataType, cuuint32_t, void*, const cuuint64_t*, const cuuint64_t*,
                             const cuuint32_t*, const cuuint32_t*, CUtensorMapInterleave, CUtensorMapSwizzle,
                             CUtensorMapL2promotion, CUtensorMapFloatOOBfill);

struct HostState {
    bool ready;
    const void* key[11];
    CUtensorMap wq, wk, wv, w1, qo, ho, hi, oi, w2, wo, xi, gi, out;
    void *pQ, *pKV, *pH, *pO, *pMax, *pRow, *pCol, *pFlag, *pG;
};
HostState g_hs;

void make_map(EncodeFn fn, CUtensorMap* m, const void* ptr, uint64_t inner, uint64_t outer, uint32_t box_in, uint32_t box_out) {
    cuuint64_t dims[2] = {inner, outer};
    cuuint64_t strides[1] = {inner * 2};
    cuuint32_t box[2] = {box_in, box_out};
    cuuint32_t es[2] = {1, 1};
    fn(m, CU_TENSOR_MAP_DATA_TYPE_BFLOAT16, 2, const_cast<void*>(ptr), dims, strides, box, es, CU_TENSOR_MAP_INTERLEAVE_NONE,
       CU_TENSOR_MAP_SWIZZLE_128B, CU_TENSOR_MAP_L2_PROMOTION_L2_256B, CU_TENSOR_MAP_FLOAT_OOB_FILL_NONE);
}

template <typename... KArgs, typename... Args>
void launch(void (*kern)(KArgs...), int grid, int block, int smem, bool pdl, int cluster, Args... args) {
    cudaLaunchConfig_t cfg = {};
    cfg.gridDim = dim3(grid); cfg.blockDim = dim3(block); cfg.dynamicSmemBytes = smem; cfg.stream = cudaStreamPerThread;
    cudaLaunchAttribute at[2];
    int n = 0;
    if (pdl) { at[n].id = cudaLaunchAttributeProgrammaticStreamSerialization; at[n].val.programmaticStreamSerializationAllowed = 1; n++; }
    if (cluster > 1) { at[n].id = cudaLaunchAttributeClusterDimension; at[n].val.clusterDim.x = cluster; at[n].val.clusterDim.y = 1; at[n].val.clusterDim.z = 1; n++; }
    cfg.attrs = at; cfg.numAttrs = n;
    cudaLaunchKernelEx(&cfg, kern, KArgs(args)...);
}

}

extern "C" void kernel_launch(void* const* d_in, const int* in_sizes, int n_in, void* d_out, int out_size) {
    (void)in_sizes; (void)n_in; (void)out_size;
    HostState& hs = g_hs;
    bool same = hs.ready;
    for (int i = 0; i < 10 && same; i++) same = hs.key[i] == d_in[i];
    same = same && hs.key[10] == d_out;
    if (!same) {
        void* fp = nullptr;
        cudaDriverEntryPointQueryResult qr;
        cudaGetDriverEntryPoint("cuTensorMapEncodeTiled", &fp, cudaEnableDefault, &qr);
        EncodeFn fn = (EncodeFn)fp;
        cudaGetSymbolAddress(&hs.pQ, g_Q); cudaGetSymbolAddress(&hs.pKV, g_KV); cudaGetSymbolAddress(&hs.pH, g_H);
        cudaGetSymbolAddress(&hs.pO, g_O); cudaGetSymbolAddress(&hs.pMax, g_kvmax);
        cudaGetSymbolAddress(&hs.pRow, g_rowstat); cudaGetSymbolAddress(&hs.pCol, g_colpart); cudaGetSymbolAddress(&hs.pG, g_G); cudaGetSymbolAddress(&hs.pFlag, g_sync);
        make_map(fn, &hs.wq, d_in[1], 512, 512, 64, 64);
        make_map(fn, &hs.wk, d_in[2], 16, 512, 64, 64);
        make_map(fn, &hs.wv, d_in[3], 16, 512, 64, 64);
        make_map(fn, &hs.w1, d_in[6], F_DIM, 512, 64, 64);
        make_map(fn, &hs.qo, hs.pQ, 512, S_LEN, 64, 16);
        make_map(fn, &hs.ho, hs.pH, F_DIM, S_LEN, 64, 16);
        make_map(fn, &hs.hi, hs.pH, F_DIM, S_LEN, 64, 64);
        make_map(fn, &hs.gi, hs.pG, 512, S_LEN, 64, 128);
        make_map(fn, &hs.oi, hs.pO, 512, S_LEN, 64, 128);
        make_map(fn, &hs.w2, d_in[8], 512, F_DIM, 64, 64);
        make_map(fn, &hs.wo, d_in[4], 512, 512, 64, 64);
        make_map(fn, &hs.xi, d_in[0], 512, S_LEN, 64, 128);
        make_map(fn, &hs.out, d_out, 512, S_LEN, 64, 16);
        cudaFuncSetAttribute(k1_proj, cudaFuncAttributeMaxDynamicSharedMemorySize, K1_SMEM);
        cudaFuncSetAttribute(k2_attn, cudaFuncAttributeMaxDynamicSharedMemorySize, AT_SMEM);
        cudaFuncSetAttribute(k3_out, cudaFuncAttributeMaxDynamicSharedMemorySize, K3_SMEM);
        for (int i = 0; i < 10; i++) hs.key[i] = d_in[i];
        hs.key[10] = d_out;
        hs.ready = true;
    }
    launch(k1_proj, 128, 384, K1_SMEM, false, 2, hs.xi, hs.wq, hs.wk, hs.wv, hs.w1, hs.qo, hs.ho, (const __nv_bfloat16*)d_in[0],
           (const __nv_bfloat16*)d_in[7], (float2*)hs.pRow, (float*)hs.pCol, (int*)hs.pFlag, (__nv_bfloat16*)hs.pKV, (float*)hs.pMax);
    launch(k2_attn, 128, 640, AT_SMEM, true, 1, hs.hi, hs.w2, (const __nv_bfloat16*)hs.pQ, (const __nv_bfloat16*)hs.pKV,
           (const float*)hs.pMax, (const __nv_bfloat16*)d_in[9], (__nv_bfloat16*)hs.pO, (__nv_bfloat16*)hs.pG, (uint2*)hs.pRow, (uint2*)hs.pCol, (int*)hs.pFlag);
    launch(k3_out, 128, 256, K3_SMEM, true, 1, hs.oi, hs.wo, hs.xi, hs.gi, hs.out, (int*)hs.pFlag);
}
```

```cpp
#include <cuda_runtime.h>
#include <cuda_bf16.h>
#include <cuda.h>
#include <stdint.h>

namespace {

constexpr int S_LEN = 2048, D_MODEL = 512, F_DIM = 1792;

__device__ __align__(1024) __nv_bfloat16 g_Q[S_LEN * D_MODEL];
__device__ __align__(1024) __nv_bfloat16 g_KV[6 * S_LEN * 8];
__device__ __align__(1024) __nv_bfloat16 g_G[S_LEN * D_MODEL];
__device__ __align__(1024) __nv_bfloat16 g_H[S_LEN * F_DIM];
__device__ __align__(1024) __nv_bfloat16 g_O[S_LEN * D_MODEL];
__device__ __align__(1024) float g_kvmax[256];
__device__ __align__(1024) float2 g_rowstat[S_LEN];
__device__ __align__(1024) float g_colpart[8 * 16 * 320];

#define DEV_STAMP(k, e) do {} while (0)
__device__ __forceinline__ uint32_t smem_u32(const void* p) { return (uint32_t)__cvta_generic_to_shared(p); }
__device__ __forceinline__ void wg_fence() { asm volatile("wgmma.fence.sync.aligned;" ::: "memory"); }
__device__ __forceinline__ void wg_commit() { asm volatile("wgmma.commit_group.sync.aligned;" ::: "memory"); }
template <int N> __device__ __forceinline__ void wg_wait() { asm volatile("wgmma.wait_group.sync.aligned %0;" ::"n"(N) : "memory"); }
template <int N> __device__ __forceinline__ void fence_regs(float* r) {
#pragma unroll
    for (int i = 0; i < N; i++) asm volatile("" : "+f"(r[i])::"memory");
}
__device__ __forceinline__ void fence_proxy_async() { asm volatile("fence.proxy.async.shared::cta;" ::: "memory"); }
__device__ __forceinline__ void mbar_init(uint32_t bar, int cnt) { asm volatile("mbarrier.init.shared::cta.b64 [%0], %1;" ::"r"(bar), "r"(cnt) : "memory"); }
__device__ __forceinline__ void mbar_init_fence() { asm volatile("fence.mbarrier_init.release.cluster;" ::: "memory"); }
__device__ __forceinline__ void mbar_expect_tx(uint32_t bar, uint32_t bytes) {
    asm volatile("mbarrier.arrive.expect_tx.shared::cta.b64 _, [%0], %1;" ::"r"(bar), "r"(bytes) : "memory");
}
__device__ __forceinline__ void mbar_arrive(uint32_t bar) { asm volatile("mbarrier.arrive.shared::cta.b64 _, [%0];" ::"r"(bar) : "memory"); }
__device__ __forceinline__ bool mbar_try(uint32_t bar, uint32_t parity) {
    uint32_t ok;
    asm volatile("{\n.reg .pred p;\nmbarrier.try_wait.parity.shared::cta.b64 p, [%1], %2;\nselp.u32 %0, 1, 0, p;\n}\n"
                 : "=r"(ok) : "r"(bar), "r"(parity) : "memory");
    return ok != 0;
}
__device__ __forceinline__ void mbar_wait(uint32_t bar, uint32_t parity) {
    if (mbar_try(bar, parity)) return;
    const long long t0 = clock64();
#pragma unroll 1
    while (!mbar_try(bar, parity)) {
        if (clock64() - t0 > 20000000ll) {
            break;
        }
    }
}
__device__ __forceinline__ void bulk_g2s(uint32_t dst, const void* src, uint32_t bytes, uint32_t bar) {
    asm volatile("cp.async.bulk.shared::cluster.global.mbarrier::complete_tx::bytes [%0], [%1], %2, [%3];"
                 ::"r"(dst), "l"(src), "r"(bytes), "r"(bar) : "memory");
}
__device__ __forceinline__ void tma_load_2d(uint32_t dst, const CUtensorMap* tm, int c0, int c1, uint32_t bar) {
    asm volatile("cp.async.bulk.tensor.2d.shared::cluster.global.mbarrier::complete_tx::bytes [%0], [%1, {%3, %4}], [%2];"
                 ::"r"(dst), "l"((uint64_t)tm), "r"(bar), "r"(c0), "r"(c1) : "memory");
}
__device__ __forceinline__ void tma_load_2d_mc(uint32_t dst, const CUtensorMap* tm, int c0, int c1, uint32_t bar, uint16_t mask) {
    asm volatile("cp.async.bulk.tensor.2d.shared::cluster.global.mbarrier::complete_tx::bytes.multicast::cluster [%0], [%1, {%3, %4}], [%2], %5;"
                 ::"r"(dst), "l"((uint64_t)tm), "r"(bar), "r"(c0), "r"(c1), "h"(mask) : "memory");
}
__device__ __forceinline__ void mbar_arrive_remote(uint32_t bar, uint32_t cta) {
    asm volatile("{\n.reg .b32 ra;\nmapa.shared::cluster.u32 ra, %0, %1;\nmbarrier.arrive.shared::cluster.b64 _, [ra];\n}\n"
                 ::"r"(bar), "r"(cta) : "memory");
}
__device__ __forceinline__ void cluster_sync_relaxed() {
    asm volatile("barrier.cluster.arrive.relaxed;\nbarrier.cluster.wait;" ::: "memory");
}
__device__ __forceinline__ uint2 ld_relaxed_v2(const void* p) {
    uint2 v; asm volatile("ld.relaxed.gpu.global.v2.b32 {%0,%1}, [%2];" : "=r"(v.x), "=r"(v.y) : "l"(p) : "memory"); return v;
}
constexpr uint32_t NOT_READY = 0u;
__device__ __forceinline__ float xch_enc(float v) { return __uint_as_float((v == 0.f ? 0u : __float_as_uint(v)) ^ 0x80000000u); }
__device__ __forceinline__ float xch_dec(uint32_t u) { return __uint_as_float(u ^ 0x80000000u); }
__device__ __forceinline__ void tma_store_2d(const CUtensorMap* tm, uint32_t src, int c0, int c1) {
    asm volatile("cp.async.bulk.tensor.2d.global.shared::cta.bulk_group [%0, {%2, %3}], [%1];"
                 ::"l"((uint64_t)tm), "r"(src), "r"(c0), "r"(c1) : "memory");
}
__device__ __forceinline__ void tma_store_commit() { asm volatile("cp.async.bulk.commit_group;" ::: "memory"); }
__device__ __forceinline__ void tma_store_wait() { asm volatile("cp.async.bulk.wait_group 0;" ::: "memory"); }
__device__ __forceinline__ void tma_prefetch_desc(const CUtensorMap* tm) { asm volatile("prefetch.tensormap [%0];" ::"l"((uint64_t)tm) : "memory"); }
__device__ __forceinline__ void named_bar_sync(int id, int n) { asm volatile("bar.sync %0, %1;" ::"r"(id), "r"(n) : "memory"); }
__device__ __forceinline__ void pdl_wait() { asm volatile("griddepcontrol.wait;" ::: "memory"); }
__device__ __forceinline__ void pdl_launch() { asm volatile("griddepcontrol.launch_dependents;" ::: "memory"); }
template <int N> __device__ __forceinline__ void reg_alloc() { asm volatile("setmaxnreg.inc.sync.aligned.u32 %0;" ::"n"(N)); }
template <int N> __device__ __forceinline__ void reg_dealloc() { asm volatile("setmaxnreg.dec.sync.aligned.u32 %0;" ::"n"(N)); }
__device__ __forceinline__ float ex2(float x) { float y; asm("ex2.approx.ftz.f32 %0, %1;" : "=f"(y) : "f"(x)); return y; }
__device__ __forceinline__ uint32_t pack_bf16(float lo, float hi) {
    uint32_t r; asm("cvt.rn.bf16x2.f32 %0, %1, %2;" : "=r"(r) : "f"(hi), "f"(lo)); return r;
}
__device__ __forceinline__ uint32_t pack_bf16_relu(float lo, float hi) {
    uint32_t r; asm("cvt.rn.relu.bf16x2.f32 %0, %1, %2;" : "=r"(r) : "f"(hi), "f"(lo)); return r;
}
__device__ __forceinline__ uint32_t mul_bf16x2(uint32_t a, uint32_t b) {
    uint32_t r; asm("mul.rn.bf16x2 %0, %1, %2;" : "=r"(r) : "r"(a), "r"(b)); return r;
}
__device__ __forceinline__ float bf_lo(uint32_t v) { return __uint_as_float(v << 16); }
__device__ __forceinline__ float bf_hi(uint32_t v) { return __uint_as_float(v & 0xFFFF0000u); }
__device__ __forceinline__ void stmatrix_x4(uint32_t addr, uint32_t r0, uint32_t r1, uint32_t r2, uint32_t r3) {
    asm volatile("stmatrix.sync.aligned.m8n8.x4.shared.b16 [%0], {%1,%2,%3,%4};" ::"r"(addr), "r"(r0), "r"(r1), "r"(r2), "r"(r3) : "memory");
}
__device__ __forceinline__ uint64_t make_desc(uint32_t addr, uint32_t lbo, uint32_t sbo, uint32_t swz) {
    return (uint64_t)((addr & 0x3FFFF) >> 4) | ((uint64_t)(lbo >> 4) << 16) | ((uint64_t)(sbo >> 4) << 32) | ((uint64_t)swz << 62);
}

__device__ __forceinline__ uint64_t desc64(uint32_t lo, uint32_t hi) {
    uint64_t d; asm("mov.b64 %0, {%1, %2};" : "=l"(d) : "r"(lo), "r"(hi)); return d;
}

__device__ __forceinline__ void wgmma_ss_n256_tb(float* d, uint64_t descA, uint64_t descB, int scaleD) {
    asm volatile("{\n.reg .pred p;\nsetp.ne.b32 p, %130, 0;\n"
      "wgmma.mma_async.sync.aligned.m64n256k16.f32.bf16.bf16 {%0,%1,%2,%3,%4,%5,%6,%7,%8,%9,%10,%11,%12,%13,%14,%15,%16,%17,%18,%19,%20,%21,%22,%23,%24,%25,%26,%27,%28,%29,%30,%31,%32,%33,%34,%35,%36,%37,%38,%39,%40,%41,%42,%43,%44,%45,%46,%47,%48,%49,%50,%51,%52,%53,%54,%55,%56,%57,%58,%59,%60,%61,%62,%63,%64,%65,%66,%67,%68,%69,%70,%71,%72,%73,%74,%75,%76,%77,%78,%79,%80,%81,%82,%83,%84,%85,%86,%87,%88,%89,%90,%91,%92,%93,%94,%95,%96,%97,%98,%99,%100,%101,%102,%103,%104,%105,%106,%107,%108,%109,%110,%111,%112,%113,%114,%115,%116,%117,%118,%119,%120,%121,%122,%123,%124,%125,%126,%127}, %128, %129, p, 1, 1, 0, 1;\n}\n"
      : "+f"(d[0]), "+f"(d[1]), "+f"(d[2]), "+f"(d[3]), "+f"(d[4]), "+f"(d[5]), "+f"(d[6]), "+f"(d[7]), "+f"(d[8]), "+f"(d[9]), "+f"(d[10]), "+f"(d[11]), "+f"(d[12]), "+f"(d[13]), "+f"(d[14]), "+f"(d[15]), "+f"(d[16]), "+f"(d[17]), "+f"(d[18]), "+f"(d[19]), "+f"(d[20]), "+f"(d[21]), "+f"(d[22]), "+f"(d[23]), "+f"(d[24]), "+f"(d[25]), "+f"(d[26]), "+f"(d[27]), "+f"(d[28]), "+f"(d[29]), "+f"(d[30]), "+f"(d[31]), "+f"(d[32]), "+f"(d[33]), "+f"(d[34]), "+f"(d[35]), "+f"(d[36]), "+f"(d[37]), "+f"(d[38]), "+f"(d[39]), "+f"(d[40]), "+f"(d[41]), "+f"(d[42]), "+f"(d[43]), "+f"(d[44]), "+f"(d[45]), "+f"(d[46]), "+f"(d[47]), "+f"(d[48]), "+f"(d[49]), "+f"(d[50]), "+f"(d[51]), "+f"(d[52]), "+f"(d[53]), "+f"(d[54]), "+f"(d[55]), "+f"(d[56]), "+f"(d[57]), "+f"(d[58]), "+f"(d[59]), "+f"(d[60]), "+f"(d[61]), "+f"(d[62]), "+f"(d[63]), "+f"(d[64]), "+f"(d[65]), "+f"(d[66]), "+f"(d[67]), "+f"(d[68]), "+f"(d[69]), "+f"(d[70]), "+f"(d[71]), "+f"(d[72]), "+f"(d[73]), "+f"(d[74]), "+f"(d[75]), "+f"(d[76]), "+f"(d[77]), "+f"(d[78]), "+f"(d[79]), "+f"(d[80]), "+f"(d[81]), "+f"(d[82]), "+f"(d[83]), "+f"(d[84]), "+f"(d[85]), "+f"(d[86]), "+f"(d[87]), "+f"(d[88]), "+f"(d[89]), "+f"(d[90]), "+f"(d[91]), "+f"(d[92]), "+f"(d[93]), "+f"(d[94]), "+f"(d[95]), "+f"(d[96]), "+f"(d[97]), "+f"(d[98]), "+f"(d[99]), "+f"(d[100]), "+f"(d[101]), "+f"(d[102]), "+f"(d[103]), "+f"(d[104]), "+f"(d[105]), "+f"(d[106]), "+f"(d[107]), "+f"(d[108]), "+f"(d[109]), "+f"(d[110]), "+f"(d[111]), "+f"(d[112]), "+f"(d[113]), "+f"(d[114]), "+f"(d[115]), "+f"(d[116]), "+f"(d[117]), "+f"(d[118]), "+f"(d[119]), "+f"(d[120]), "+f"(d[121]), "+f"(d[122]), "+f"(d[123]), "+f"(d[124]), "+f"(d[125]), "+f"(d[126]), "+f"(d[127])
      : "l"(descA), "l"(descB), "r"(scaleD));
}
__device__ __forceinline__ void wgmma_ss_n128_tb(float* d, uint64_t descA, uint64_t descB, int scaleD) {
    asm volatile("{\n.reg .pred p;\nsetp.ne.b32 p, %66, 0;\n"
      "wgmma.mma_async.sync.aligned.m64n128k16.f32.bf16.bf16 {%0,%1,%2,%3,%4,%5,%6,%7,%8,%9,%10,%11,%12,%13,%14,%15,%16,%17,%18,%19,%20,%21,%22,%23,%24,%25,%26,%27,%28,%29,%30,%31,%32,%33,%34,%35,%36,%37,%38,%39,%40,%41,%42,%43,%44,%45,%46,%47,%48,%49,%50,%51,%52,%53,%54,%55,%56,%57,%58,%59,%60,%61,%62,%63}, %64, %65, p, 1, 1, 0, 1;\n}\n"
      : "+f"(d[0]), "+f"(d[1]), "+f"(d[2]), "+f"(d[3]), "+f"(d[4]), "+f"(d[5]), "+f"(d[6]), "+f"(d[7]), "+f"(d[8]), "+f"(d[9]), "+f"(d[10]), "+f"(d[11]), "+f"(d[12]), "+f"(d[13]), "+f"(d[14]), "+f"(d[15]), "+f"(d[16]), "+f"(d[17]), "+f"(d[18]), "+f"(d[19]), "+f"(d[20]), "+f"(d[21]), "+f"(d[22]), "+f"(d[23]), "+f"(d[24]), "+f"(d[25]), "+f"(d[26]), "+f"(d[27]), "+f"(d[28]), "+f"(d[29]), "+f"(d[30]), "+f"(d[31]), "+f"(d[32]), "+f"(d[33]), "+f"(d[34]), "+f"(d[35]), "+f"(d[36]), "+f"(d[37]), "+f"(d[38]), "+f"(d[39]), "+f"(d[40]), "+f"(d[41]), "+f"(d[42]), "+f"(d[43]), "+f"(d[44]), "+f"(d[45]), "+f"(d[46]), "+f"(d[47]), "+f"(d[48]), "+f"(d[49]), "+f"(d[50]), "+f"(d[51]), "+f"(d[52]), "+f"(d[53]), "+f"(d[54]), "+f"(d[55]), "+f"(d[56]), "+f"(d[57]), "+f"(d[58]), "+f"(d[59]), "+f"(d[60]), "+f"(d[61]), "+f"(d[62]), "+f"(d[63])
      : "l"(descA), "l"(descB), "r"(scaleD));
}
__device__ __forceinline__ void wgmma_ss_n64_tb(float* d, uint64_t descA, uint64_t descB, int scaleD) {
    asm volatile("{\n.reg .pred p;\nsetp.ne.b32 p, %34, 0;\n"
      "wgmma.mma_async.sync.aligned.m64n64k16.f32.bf16.bf16 {%0,%1,%2,%3,%4,%5,%6,%7,%8,%9,%10,%11,%12,%13,%14,%15,%16,%17,%18,%19,%20,%21,%22,%23,%24,%25,%26,%27,%28,%29,%30,%31}, %32, %33, p, 1, 1, 0, 1;\n}\n"
      : "+f"(d[0]), "+f"(d[1]), "+f"(d[2]), "+f"(d[3]), "+f"(d[4]), "+f"(d[5]), "+f"(d[6]), "+f"(d[7]), "+f"(d[8]), "+f"(d[9]), "+f"(d[10]), "+f"(d[11]), "+f"(d[12]), "+f"(d[13]), "+f"(d[14]), "+f"(d[15]), "+f"(d[16]), "+f"(d[17]), "+f"(d[18]), "+f"(d[19]), "+f"(d[20]), "+f"(d[21]), "+f"(d[22]), "+f"(d[23]), "+f"(d[24]), "+f"(d[25]), "+f"(d[26]), "+f"(d[27]), "+f"(d[28]), "+f"(d[29]), "+f"(d[30]), "+f"(d[31])
      : "l"(descA), "l"(descB), "r"(scaleD));
}
__device__ __forceinline__ void wgmma_qk_acc_n64(float* d, const uint32_t* a, uint64_t descB) {
    asm volatile("wgmma.mma_async.sync.aligned.m64n64k16.f32.bf16.bf16 {%0,%1,%2,%3,%4,%5,%6,%7,%8,%9,%10,%11,%12,%13,%14,%15,%16,%17,%18,%19,%20,%21,%22,%23,%24,%25,%26,%27,%28,%29,%30,%31}, {%32,%33,%34,%35}, %36, 1, 1, 1, 0;\n"
      : "+f"(d[0]), "+f"(d[1]), "+f"(d[2]), "+f"(d[3]), "+f"(d[4]), "+f"(d[5]), "+f"(d[6]), "+f"(d[7]), "+f"(d[8]), "+f"(d[9]), "+f"(d[10]), "+f"(d[11]), "+f"(d[12]), "+f"(d[13]), "+f"(d[14]), "+f"(d[15]), "+f"(d[16]), "+f"(d[17]), "+f"(d[18]), "+f"(d[19]), "+f"(d[20]), "+f"(d[21]), "+f"(d[22]), "+f"(d[23]), "+f"(d[24]), "+f"(d[25]), "+f"(d[26]), "+f"(d[27]), "+f"(d[28]), "+f"(d[29]), "+f"(d[30]), "+f"(d[31])
      : "r"(a[0]), "r"(a[1]), "r"(a[2]), "r"(a[3]), "l"(descB));
}

__device__ __forceinline__ void wgmma_pv(float* d, uint32_t a0, uint32_t a1, uint32_t a2, uint32_t a3, uint64_t descB) {
    asm volatile("wgmma.mma_async.sync.aligned.m64n24k16.f32.bf16.bf16 {%0,%1,%2,%3,%4,%5,%6,%7,%8,%9,%10,%11}, {%12,%13,%14,%15}, %16, 1, 1, 1, 1;\n"
                 : "+f"(d[0]), "+f"(d[1]), "+f"(d[2]), "+f"(d[3]), "+f"(d[4]), "+f"(d[5]), "+f"(d[6]), "+f"(d[7]), "+f"(d[8]), "+f"(d[9]), "+f"(d[10]), "+f"(d[11])
                 : "r"(a0), "r"(a1), "r"(a2), "r"(a3), "l"(descB));
}

__device__ __forceinline__ void k1_panel(int g, int i, int& type, int& col) {
    if (g < 6) {
        int p = g * 5 + i;
        if (p < 8) { type = 0; col = p * 64; } else { type = 1; col = (p - 8) * 64; }
    } else {
        if (i < 3) { type = 1; col = (22 + (g - 6) * 3 + i) * 64; } else { type = 2 + (g - 6); col = 0; }
    }
}

constexpr int K1_STAGES = 4;
constexpr int K1_PANEL_BYTES = 64 * 128;
constexpr int K1_STAGE_BYTES = 16384 + 5 * K1_PANEL_BYTES;
constexpr int K1_SMEM = K1_STAGES * K1_STAGE_BYTES + 128 + 320 * 8;
constexpr float Q_SCALE = 0.25f * 1.4426950408889634f;

__global__ void __launch_bounds__(384, 1)
k1_proj(const __grid_constant__ CUtensorMap tm_x, const __grid_constant__ CUtensorMap tm_wq,
        const __grid_constant__ CUtensorMap tm_wk, const __grid_constant__ CUtensorMap tm_wv,
        const __grid_constant__ CUtensorMap tm_w1, const __grid_constant__ CUtensorMap tm_qo,
        const __grid_constant__ CUtensorMap tm_ho, const __nv_bfloat16* __restrict__ x, const __nv_bfloat16* __restrict__ b1,
        float2* rowstat, float* colpart,
        __nv_bfloat16* __restrict__ kv, float* __restrict__ kvmax) {
    extern __shared__ __align__(1024) uint8_t smem_raw[];
    const uint32_t sbase = smem_u32(smem_raw);
    const uint32_t bar_full = sbase + K1_STAGES * K1_STAGE_BYTES, bar_empty = bar_full + 8 * K1_STAGES, bar_col = bar_empty + 8 * K1_STAGES;
    const uint32_t sCol = bar_full + 128;
    const int tid = threadIdx.x, warp = __shfl_sync(0xffffffffu, tid >> 5, 0), lane = tid & 31;
    const int crank = blockIdx.x & 1, grp = (blockIdx.x >> 1) & 7, rb = (blockIdx.x >> 4) * 2 + crank;
    const int npanels = grp < 6 ? 5 : 4;
    if (tid == 0) DEV_STAMP(0, 0);

    uint4 v[2][2];
    if (warp < 8) {
        const uint4* xp = reinterpret_cast<const uint4*>(x + (size_t)(rb * 128 + grp * 16 + warp * 2) * D_MODEL);
#pragma unroll
        for (int r = 0; r < 2; r++) { v[r][0] = __ldg(xp + r * 64 + lane); v[r][1] = __ldg(xp + r * 64 + 32 + lane); }
    }
    const int krot = rb & 8 ? 4 : 0, cstage = (rb >> 1) & 3;
    if (tid == 256) {
        for (int s = 0; s < K1_STAGES; s++) { mbar_init(bar_full + 8 * s, 1); mbar_init(bar_empty + 8 * s, s == cstage ? 18 : 16); }
        mbar_init(bar_col, 96);
        mbar_init_fence();
    }
    cluster_sync_relaxed();
    pdl_launch();

    if (warp >= 8) {
        reg_dealloc<88>();
            if (warp == 8) {
            if (lane == 0) {
                const CUtensorMap* tms[5]; int cols[5];
#pragma unroll
                for (int i = 0; i < 5; i++) {
                    int type, col; k1_panel(grp, i, type, col);
                    tms[i] = type == 0 ? &tm_wq : type == 1 ? &tm_w1 : type == 2 ? &tm_wk : &tm_wv;
                    cols[i] = col;
                }
                for (int ks = 0; ks < 8; ks++) {
                    const int s = ks % K1_STAGES;
                    const uint32_t st = sbase + s * K1_STAGE_BYTES;
                    mbar_wait(bar_empty + 8 * s, ((ks / K1_STAGES) & 1) ^ 1);
                    mbar_expect_tx(bar_full + 8 * s, 16384 + npanels * K1_PANEL_BYTES);
                    const int k0 = ((ks + krot) & 7) * 64;
                    tma_load_2d(st, &tm_x, k0, rb * 128, bar_full + 8 * s);
#pragma unroll
                    for (int i = 0; i < 5; i++)
                        if (i < npanels && ((i + ks + crank) & 1) == 0)
                            tma_load_2d_mc(st + 16384 + i * K1_PANEL_BYTES, tms[i], cols[i], k0, bar_full + 8 * s, (uint16_t)3);
                }
            }
        } else {
            const int ht = tid - 288;
            mbar_wait(bar_full + 8 * cstage, 0);
            {
                const int pc = ht >> 1, half = ht & 1;
                float sacc[8];
#pragma unroll
                for (int c = 0; c < 8; c++) sacc[c] = 0.f;
                if (pc < npanels * 8) {
                    const uint32_t pb = sbase + cstage * K1_STAGE_BYTES + 16384 + (pc >> 3) * K1_PANEL_BYTES;
#pragma unroll
                    for (int i = 0; i < 16; i++) {
                        const int k = crank * 32 + 2 * i + half;
                        uint4 u;
                        asm volatile("ld.shared.v4.b32 {%0,%1,%2,%3}, [%4];" : "=r"(u.x), "=r"(u.y), "=r"(u.z), "=r"(u.w)
                                     : "r"(pb + k * 128 + (((pc & 7) ^ (k & 7)) << 4)));
                        sacc[0] += bf_lo(u.x); sacc[1] += bf_hi(u.x); sacc[2] += bf_lo(u.y); sacc[3] += bf_hi(u.y);
                        sacc[4] += bf_lo(u.z); sacc[5] += bf_hi(u.z); sacc[6] += bf_lo(u.w); sacc[7] += bf_hi(u.w);
                    }
                }
#pragma unroll
                for (int c = 0; c < 8; c++) sacc[c] += __shfl_xor_sync(0xffffffffu, sacc[c], 1);
                if (pc < npanels * 8) {
                    float4* dst = reinterpret_cast<float4*>(colpart + (grp * 16 + rb) * 320 + pc * 8) + half;
                    *dst = half ? make_float4(xch_enc(sacc[4]), xch_enc(sacc[5]), xch_enc(sacc[6]), xch_enc(sacc[7]))
                                : make_float4(xch_enc(sacc[0]), xch_enc(sacc[1]), xch_enc(sacc[2]), xch_enc(sacc[3]));
                }
                named_bar_sync(4, 96);
                if (ht < 2) mbar_arrive_remote(bar_empty + 8 * cstage, ht);
            }
            if (ht == 0) DEV_STAMP(0, 6);
            for (int c2 = ht; c2 < npanels * 32; c2 += 96) {
                int type, col; k1_panel(grp, c2 >> 5, type, col);
                uint32_t bb = 0;
                if (type == 1) bb = __ldg(reinterpret_cast<const uint32_t*>(b1 + col) + (c2 & 31));
                uint2 pv[16];
                bool okv = false;
#pragma unroll 1
                for (uint32_t n = 0; n < (1u << 14) && !okv; n++) {
                    okv = true;
#pragma unroll
                    for (int k = 0; k < 16; k++) pv[k] = ld_relaxed_v2(colpart + (grp * 16 + k) * 320 + c2 * 2);
#pragma unroll
                    for (int k = 0; k < 16; k++) okv = okv && pv[k].x != NOT_READY && pv[k].y != NOT_READY;
                }
                float s0 = 0.f, s1 = 0.f;
#pragma unroll
                for (int k = 0; k < 16; k++) { s0 += xch_dec(pv[k].x); s1 += xch_dec(pv[k].y); }
                asm volatile("st.shared.v4.f32 [%0], {%1,%2,%3,%4};" ::"r"(sCol + c2 * 16), "f"(s0), "f"(bf_lo(bb)), "f"(s1), "f"(bf_hi(bb)) : "memory");
            }
            mbar_arrive(bar_col);
            if (ht == 0) DEV_STAMP(0, 7);
        }
    } else {
        reg_alloc<208>();
        const int wg = warp >> 2;
        const int g = lane >> 2, t = lane & 3;
        const int wrow = (warp & 3) * 16;
        {
            float f[2][16], sum[2], sq[2];
#pragma unroll
            for (int r = 0; r < 2; r++) {
                const uint32_t w[8] = {v[r][0].x, v[r][0].y, v[r][0].z, v[r][0].w, v[r][1].x, v[r][1].y, v[r][1].z, v[r][1].w};
#pragma unroll
                for (int i = 0; i < 8; i++) { f[r][2 * i] = bf_lo(w[i]); f[r][2 * i + 1] = bf_hi(w[i]); }
                sum[r] = 0.f;
#pragma unroll
                for (int i = 0; i < 16; i++) sum[r] += f[r][i];
            }
#pragma unroll
            for (int o = 16; o > 0; o >>= 1) { sum[0] += __shfl_xor_sync(0xffffffffu, sum[0], o); sum[1] += __shfl_xor_sync(0xffffffffu, sum[1], o); }
#pragma unroll
            for (int r = 0; r < 2; r++) {
                sum[r] *= (1.0f / D_MODEL);
                sq[r] = 0.f;
#pragma unroll
                for (int i = 0; i < 16; i++) { const float d = f[r][i] - sum[r]; sq[r] += d * d; }
            }
#pragma unroll
            for (int o = 16; o > 0; o >>= 1) { sq[0] += __shfl_xor_sync(0xffffffffu, sq[0], o); sq[1] += __shfl_xor_sync(0xffffffffu, sq[1], o); }
            if (lane < 2) {
                const float rstd = rsqrtf((lane ? sq[1] : sq[0]) * (1.0f / D_MODEL) + 1e-5f);
                rowstat[rb * 128 + grp * 16 + warp * 2 + lane] = make_float2(xch_enc(rstd), (lane ? sum[1] : sum[0]) * rstd);
            }
            if (tid == 0) DEV_STAMP(0, 5);
        }
        float acc[160];
#pragma unroll
        for (int i = 0; i < 160; i++) acc[i] = 0.f;
        float2 rs0, rs1;
        const uint64_t dA0 = make_desc(sbase + wg * 8192, 16, 1024, 1);
        const uint64_t dB0 = make_desc(sbase + 16384, K1_PANEL_BYTES, 1024, 1);
#define K1_MAINLOOP(FIVE)                                                                                          \
        for (int ks = 0; ks < 8; ks++) {                                                                           \
            const int s = ks % K1_STAGES;                                                                          \
            mbar_wait(bar_full + 8 * s, (ks / K1_STAGES) & 1);                                                     \
            if (ks == 0 && tid == 0) DEV_STAMP(0, 1);                                                              \
            wg_fence();                                                                                            \
            _Pragma("unroll") for (int kk = 0; kk < 4; kk++) {                                                     \
                const uint64_t dA = dA0 + (uint64_t)((s * K1_STAGE_BYTES + kk * 32) >> 4);                         \
                const uint64_t dB = dB0 + (uint64_t)((s * K1_STAGE_BYTES + kk * 2048) >> 4);                       \
                wgmma_ss_n256_tb(acc, dA, dB, (ks | kk) != 0);                                                     \
                if (FIVE) wgmma_ss_n64_tb(acc + 128, dA, dB + (uint64_t)((4 * K1_PANEL_BYTES) >> 4), (ks | kk) != 0); \
            }                                                                                                      \
            wg_commit();                                                                                           \
            if (ks == 7) {                                                                                         \
                uint2 r0, r1;                                                                                      \
                uint32_t n = 0;                                                                                    \
                _Pragma("unroll 1") do {                                                                           \
                    r0 = ld_relaxed_v2(rowstat + rb * 128 + wg * 64 + wrow + g);                                   \
                    r1 = ld_relaxed_v2(rowstat + rb * 128 + wg * 64 + wrow + g + 8);                               \
                } while ((r0.x == NOT_READY || r1.x == NOT_READY) && ++n < (1u << 14));                            \
                rs0 = make_float2(xch_dec(r0.x), __uint_as_float(r0.y));                                           \
                rs1 = make_float2(xch_dec(r1.x), __uint_as_float(r1.y));                                           \
                mbar_wait(bar_col, 0);                                                                             \
            }                                                                                                      \
            if (ks > 0 && ks <= 4) {                                                                               \
                wg_wait<1>();                                                                                      \
                if (lane < 2) mbar_arrive_remote(bar_empty + 8 * ((ks - 1) % K1_STAGES), lane);                    \
            }                                                                                                      \
        }                                                                                                          \
        wg_wait<0>();
        if (npanels == 5) { K1_MAINLOOP(true) } else { K1_MAINLOOP(false) }
        fence_regs<160>(acc);
        if (tid == 0) DEV_STAMP(0, 2);
        named_bar_sync(1, 256);
        const int srow = (lane & 7) + ((lane >> 3) & 1) * 8;
#pragma unroll
        for (int p = 0; p < 5; p++) {
            if (p < npanels) {
                int type, col; k1_panel(grp, p, type, col);
                float* a = acc + p * 32;
                const int nj = type <= 1 ? 8 : 2;
                const float sc = type == 0 ? Q_SCALE : 1.0f;
                const float r0x = rs0.x * sc, r0y = -rs0.y * sc, r1x = rs1.x * sc, r1y = -rs1.y * sc;
#pragma unroll
                for (int j = 0; j < 8; j++) {
                    if (j < nj) {
                        float4 c;
                        asm volatile("ld.shared.v4.f32 {%0,%1,%2,%3}, [%4];" : "=f"(c.x), "=f"(c.y), "=f"(c.z), "=f"(c.w)
                                     : "r"(sCol + (p * 64 + j * 8 + 2 * t) * 8));
                        a[4 * j] = fmaf(a[4 * j], r0x, fmaf(r0y, c.x, c.y));
                        a[4 * j + 1] = fmaf(a[4 * j + 1], r0x, fmaf(r0y, c.z, c.w));
                        a[4 * j + 2] = fmaf(a[4 * j + 2], r1x, fmaf(r1y, c.x, c.y));
                        a[4 * j + 3] = fmaf(a[4 * j + 3], r1x, fmaf(r1y, c.z, c.w));
                    }
                }
                if (type <= 1) {
                    const uint32_t stg = sbase + (p * 8 + warp) * 2048;
                    uint32_t pk[16];
                    if (type == 0) {
#pragma unroll
                        for (int j = 0; j < 8; j++) {
                            pk[2 * j] = pack_bf16(a[4 * j], a[4 * j + 1]);
                            pk[2 * j + 1] = pack_bf16(a[4 * j + 2], a[4 * j + 3]);
                        }
                    } else {
#pragma unroll
                        for (int j = 0; j < 8; j++) {
                            const uint32_t h0 = pack_bf16_relu(a[4 * j], a[4 * j + 1]), h1 = pack_bf16_relu(a[4 * j + 2], a[4 * j + 3]);
                            pk[2 * j] = mul_bf16x2(h0, h0);
                            pk[2 * j + 1] = mul_bf16x2(h1, h1);
                        }
                    }
#pragma unroll
                    for (int j = 0; j < 8; j += 2) {
                        const int c16 = j + (lane >> 4);
                        stmatrix_x4(stg + srow * 128 + ((c16 ^ (srow & 7)) << 4), pk[2 * j], pk[2 * j + 1], pk[2 * j + 2], pk[2 * j + 3]);
                    }
                    fence_proxy_async();
                    __syncwarp();
                    if (lane == 0) {
                        tma_store_2d(type == 0 ? &tm_qo : &tm_ho, stg, col, rb * 128 + warp * 16);
                        tma_store_commit();
                    }
                } else if (type == 3) {
                    const int r = wg * 64 + wrow + g;
                    const int pos0 = (r >> 2) * 64 + rb * 4 + (r & 3), pos1 = pos0 + 128;
                    uint32_t* dst = reinterpret_cast<uint32_t*>(kv);
                    const uint32_t r00 = pack_bf16(a[0], a[1]), r01 = pack_bf16(a[4], a[5]);
                    const uint32_t r10 = pack_bf16(a[2], a[3]), r11 = pack_bf16(a[6], a[7]);
                    dst[(pos0 >> 4) * 128 + (pos0 & 15) * 4 + t] = r00;
                    dst[16384 + pos0 * 4 + t] = r01;
                    dst[(pos1 >> 4) * 128 + (pos1 & 15) * 4 + t] = r10;
                    dst[16384 + pos1 * 4 + t] = r11;
                    float m = fmaxf(fmaxf(fmaxf(fabsf(bf_lo(r00)), fabsf(bf_hi(r00))), fmaxf(fabsf(bf_lo(r01)), fabsf(bf_hi(r01)))),
                                    fmaxf(fmaxf(fabsf(bf_lo(r10)), fabsf(bf_hi(r10))), fmaxf(fabsf(bf_lo(r11)), fabsf(bf_hi(r11)))));
#pragma unroll
                    for (int o = 16; o > 0; o >>= 1) m = fmaxf(m, __shfl_xor_sync(0xffffffffu, m, o));
                    if (lane == 0) kvmax[128 + rb * 8 + warp] = m;
                } else {
                    float* kf = reinterpret_cast<float*>(smem_raw + 96 * 1024);
                    const int r = wg * 64 + wrow + g;
                    const int pos0 = (r >> 2) * 64 + rb * 4 + (r & 3), pos1 = pos0 + 128;
                    uint32_t* dst = reinterpret_cast<uint32_t*>(kv) + 32768;
                    dst[(pos0 >> 3) * 64 + (pos0 & 7) * 4 + t] = pack_bf16(a[0], a[1]);
                    dst[(pos0 >> 3) * 64 + 32 + (pos0 & 7) * 4 + t] = pack_bf16(a[4], a[5]);
                    dst[(pos1 >> 3) * 64 + (pos1 & 7) * 4 + t] = pack_bf16(a[2], a[3]);
                    dst[(pos1 >> 3) * 64 + 32 + (pos1 & 7) * 4 + t] = pack_bf16(a[6], a[7]);
                    kf[r * 17 + 2 * t] = a[0]; kf[r * 17 + 2 * t + 1] = a[1];
                    kf[r * 17 + 8 + 2 * t] = a[4]; kf[r * 17 + 8 + 2 * t + 1] = a[5];
                    kf[(r + 8) * 17 + 2 * t] = a[2]; kf[(r + 8) * 17 + 2 * t + 1] = a[3];
                    kf[(r + 8) * 17 + 8 + 2 * t] = a[6]; kf[(r + 8) * 17 + 8 + 2 * t + 1] = a[7];
                    named_bar_sync(1, 256);
                    if (tid < 64) {
                        const int i = tid >> 4, dim = tid & 15;
                        const int c = rb * 4 + i;
                        const int inner = (dim >> 3) * 64 + (c & 7) * 8 + (dim & 7);
                        float kt = 0.f;
#pragma unroll 8
                        for (int j = 0; j < 32; j++) {
                            const __nv_bfloat16 d = __float2bfloat16_rn(kf[(j * 4 + i) * 17 + dim] - kt);
                            kt += __bfloat162float(d);
                            kf[(j * 4 + i) * 17 + dim] = kt;
                            const int grp8 = j * 8 + (c >> 3);
                            kv[(grp8 < 128 ? grp8 * 256 + 128 : 49152 + (grp8 - 128) * 128) + inner] = d;
                        }
                    }
                    named_bar_sync(1, 256);
                    if (tid < 128) {
                        float n = 0.f;
#pragma unroll
                        for (int d = 0; d < 16; d++) { const float v = kf[tid * 17 + d]; n += v * v; }
                        if (!(n == n)) n = __int_as_float(0x7f800000);
#pragma unroll
                        for (int o = 8; o > 0; o >>= 1) n = fmaxf(n, __shfl_xor_sync(0xffffffffu, n, o));
                        if ((lane & 15) == 0) kvmax[rb * 8 + (tid >> 4)] = n;
                    }
                }
            }
        }
        if (tid == 0) DEV_STAMP(0, 3);
        if (lane == 0) tma_store_wait();
        if (tid == 0) DEV_STAMP(0, 4);
    }
}

constexpr int AT_KT = 64;
constexpr int AT_NCHUNK = 8;
constexpr int AT_NSTEP = S_LEN / AT_KT;
constexpr int AT_SPC = AT_NSTEP / AT_NCHUNK;
constexpr int AT_ONES = 131072;
constexpr int F2_STAGES = 4;
constexpr int F2_STAGE_BYTES = 8192 + 16384;
constexpr int F2_BASE = 132096;
constexpr int F2_NK = F_DIM / 64;
constexpr int AT_BAR = F2_BASE + F2_STAGES * F2_STAGE_BYTES;
constexpr int AT_SMEM = AT_BAR + 256;
#define AT_SWMASK_V 0xB6DB
constexpr uint32_t AT_SWMASK = AT_SWMASK_V;

#define AT_MAGIC (383.0f + 0.00390625f - 0.5849625f)
__device__ __forceinline__ uint32_t exp2_pair_alu(float t0, float t1) {
    uint32_t y;
    asm("prmt.b32 %0, %1, %2, 0x6521;" : "=r"(y) : "f"(t0), "f"(t1));
    const uint32_t e = y & 0x7F807F80u;
    uint32_t uh, p;
    asm("lop3.b32 %0, %1, %2, 0x3F003F00, 0xBE;" : "=r"(uh) : "r"(y), "r"(e));
    asm("fma.rn.bf16x2 %0, %1, %2, %3;" : "=r"(p) : "r"(uh), "r"(y), "r"(e));
    return p;
}

__device__ __forceinline__ void at_load_chunk(uint32_t sbase, const __nv_bfloat16* KV, uint32_t bar0, int c) {
    const uint8_t* src = reinterpret_cast<const uint8_t*>(KV);
    const uint32_t off = c < 4 ? c * 16384 : 98304 + (c - 4) * 8192, bytes = c < 4 ? 16384 : 8192;
    mbar_expect_tx(bar0 + 8 * c, bytes + 4096);
    bulk_g2s(sbase + off, src + off, bytes, bar0 + 8 * c);
    bulk_g2s(sbase + 65536 + c * 4096, src + 65536 + c * 4096, 4096, bar0 + 8 * c);
}

__device__ __forceinline__ void at_store(const float* o, __nv_bfloat16* O, int row, int lane) {
    const float l0 = __shfl_sync(0xffffffffu, o[8], lane & ~3);
    const float l1 = __shfl_sync(0xffffffffu, o[10], lane & ~3);
    const float r0 = __fdividef(1.0f, l0), r1 = __fdividef(1.0f, l1);
    const int t = lane & 3;
    uint32_t* op = reinterpret_cast<uint32_t*>(O + (size_t)(row + (lane >> 2)) * 16);
    op[t] = pack_bf16(o[0] * r0, o[1] * r0);
    op[t + 4] = pack_bf16(o[4] * r0, o[5] * r0);
    op[64 + t] = pack_bf16(o[2] * r1, o[3] * r1);
    op[64 + t + 4] = pack_bf16(o[6] * r1, o[7] * r1);
}

__device__ __forceinline__ void mma16816(float* c, const uint32_t* a, uint32_t b0, uint32_t b1) {
    asm volatile("mma.sync.aligned.m16n8k16.row.col.f32.bf16.bf16.f32 {%0,%1,%2,%3}, {%4,%5,%6,%7}, {%8,%9}, {%0,%1,%2,%3};"
                 : "+f"(c[0]), "+f"(c[1]), "+f"(c[2]), "+f"(c[3]) : "r"(a[0]), "r"(a[1]), "r"(a[2]), "r"(a[3]), "r"(b0), "r"(b1));
}
__device__ __forceinline__ void attn_fallback(const __nv_bfloat16* Q, const __nv_bfloat16* KV, __nv_bfloat16* O, uint32_t sbase) {
    const int tid = threadIdx.x;
    const int lane = tid & 31, g = lane >> 2, t = lane & 3;
    const uint32_t* Kg = reinterpret_cast<const uint32_t*>(KV + 65536);
#pragma unroll 1
    for (int mt = 0; mt < 2; mt++) {
        const int row = blockIdx.x * 512 + (tid >> 7) * 128 + mt * 64 + ((tid >> 5) & 3) * 16;
        const uint32_t* qp = reinterpret_cast<const uint32_t*>(Q + (size_t)(row + g) * 16);
        const uint32_t q[4] = {qp[t], qp[64 + t], qp[t + 4], qp[64 + t + 4]};
        float o[12];
#pragma unroll
        for (int i = 0; i < 12; i++) o[i] = 0.f;
        float m0 = -INFINITY, m1 = -INFINITY;
#pragma unroll 1
        for (int kt = 0; kt < S_LEN / 16; kt++) {
            float s[8];
#pragma unroll
            for (int i = 0; i < 8; i++) s[i] = 0.f;
#pragma unroll
            for (int h = 0; h < 2; h++) {
                const uint32_t* kp = Kg + (kt * 2 + h) * 64 + g * 4 + t;
                mma16816(s + 4 * h, q, kp[0], kp[32]);
            }
            float x0 = fmaxf(fmaxf(s[0], s[1]), fmaxf(s[4], s[5])), x1 = fmaxf(fmaxf(s[2], s[3]), fmaxf(s[6], s[7]));
            x0 = fmaxf(x0, __shfl_xor_sync(0xffffffffu, x0, 1)); x0 = fmaxf(x0, __shfl_xor_sync(0xffffffffu, x0, 2));
            x1 = fmaxf(x1, __shfl_xor_sync(0xffffffffu, x1, 1)); x1 = fmaxf(x1, __shfl_xor_sync(0xffffffffu, x1, 2));
            x0 = fmaxf(x0, m0); x1 = fmaxf(x1, m1);
            const float f0 = ex2(m0 - x0), f1 = ex2(m1 - x1);
            m0 = x0; m1 = x1;
#pragma unroll
            for (int j = 0; j < 3; j++) { o[4 * j] *= f0; o[4 * j + 1] *= f0; o[4 * j + 2] *= f1; o[4 * j + 3] *= f1; }
            const uint32_t p[4] = {pack_bf16(ex2(s[0] - m0), ex2(s[1] - m0)), pack_bf16(ex2(s[2] - m1), ex2(s[3] - m1)),
                                   pack_bf16(ex2(s[4] - m0), ex2(s[5] - m0)), pack_bf16(ex2(s[6] - m1), ex2(s[7] - m1))};
#pragma unroll
            for (int j = 0; j < 3; j++) {
                const uint32_t base = sbase + (j == 0 ? kt * 512 : j == 1 ? 65536 + kt * 256 : AT_ONES) + (lane & 15) * 16;
                uint32_t b0, b1;
                asm volatile("ldmatrix.sync.aligned.m8n8.x2.trans.shared.b16 {%0,%1}, [%2];" : "=r"(b0), "=r"(b1) : "r"(base));
                mma16816(o + 4 * j, p, b0, b1);
            }
        }
        at_store(o, O, row, lane);
    }
}

__global__ void __launch_bounds__(640, 1)
k2_attn(const __grid_constant__ CUtensorMap tm_h, const __grid_constant__ CUtensorMap tm_w2,
        const __nv_bfloat16* __restrict__ Q, const __nv_bfloat16* __restrict__ KV, const float* __restrict__ kvmax,
        const __nv_bfloat16* __restrict__ b2, __nv_bfloat16* __restrict__ O, __nv_bfloat16* __restrict__ G,
        uint2* __restrict__ rowstat, uint2* __restrict__ colpart) {
    extern __shared__ __align__(1024) uint8_t smem_raw[];
    const uint32_t sbase = smem_u32(smem_raw);
    const uint32_t bar0 = sbase + AT_BAR, f2_full = bar0 + 64, f2_empty = f2_full + 32, bar_guard = f2_empty + 32, sGuard = bar0 + 192;
    const int tid = threadIdx.x;
    const int wg = __shfl_sync(0xffffffffu, tid >> 7, 0);
    const int warp = (tid >> 5) & 3, lane = tid & 31;
    const int g = lane >> 2, t = lane & 3;
    if (tid == 0) DEV_STAMP(1, 0);
    if (tid == 0) {
        for (int i = 0; i < AT_NCHUNK; i++) mbar_init(bar0 + 8 * i, 1);
        for (int i = 0; i < F2_STAGES; i++) { mbar_init(f2_full + 8 * i, 1); mbar_init(f2_empty + 8 * i, 4); }
        mbar_init(bar_guard, 4);
        mbar_init_fence();
    }
    if (tid < 16) asm volatile("st.shared.v4.b32 [%0], {%1,%2,%2,%2};" ::"r"(sbase + AT_ONES + tid * 16), "r"(0x00003F80u), "r"(0u) : "memory");
    fence_proxy_async();
    __syncthreads();

    if (wg == 4) {
        const int rb = blockIdx.x >> 2, cb = blockIdx.x & 3;
        const uint32_t fb = sbase + F2_BASE;
        const bool leader = tid == 512;
        if (leader) {
#pragma unroll
            for (int s = 0; s < F2_STAGES; s++) {
                mbar_expect_tx(f2_full + 8 * s, F2_STAGE_BYTES);
                tma_load_2d(fb + s * F2_STAGE_BYTES + 8192, &tm_w2, cb * 128, s * 64, f2_full + 8 * s);
                tma_load_2d(fb + s * F2_STAGE_BYTES + 16384, &tm_w2, cb * 128 + 64, s * 64, f2_full + 8 * s);
            }
        }
        pdl_wait();
        if (leader) {
#pragma unroll
            for (int s = 0; s < F2_STAGES; s++) tma_load_2d(fb + s * F2_STAGE_BYTES, &tm_h, s * 64, rb * 64, f2_full + 8 * s);
        }
        {
            float km = fmaxf(fmaxf(kvmax[lane], kvmax[lane + 32]), fmaxf(kvmax[lane + 64], kvmax[lane + 96]));
            float vm = fmaxf(fmaxf(kvmax[128 + lane], kvmax[160 + lane]), fmaxf(kvmax[192 + lane], kvmax[224 + lane]));
            uint4 qv[4][2];
#pragma unroll
            for (int i = 0; i < 4; i++) {
                const uint4* qr = reinterpret_cast<const uint4*>(Q + (size_t)(blockIdx.x * 512 + warp * 128 + i * 16 + (lane >> 4) * 64 + (lane & 15)) * 16);
                qv[i][0] = qr[0]; qv[i][1] = qr[1];
            }
#pragma unroll
            for (int o = 16; o > 0; o >>= 1) { km = fmaxf(km, __shfl_xor_sync(0xffffffffu, km, o)); vm = fmaxf(vm, __shfl_xor_sync(0xffffffffu, vm, o)); }
#pragma unroll
            for (int i = 0; i < 4; i++) {
                const uint32_t qw[8] = {qv[i][0].x, qv[i][0].y, qv[i][0].z, qv[i][0].w, qv[i][1].x, qv[i][1].y, qv[i][1].z, qv[i][1].w};
                float qn = 0.f;
#pragma unroll
                for (int j = 0; j < 8; j++) qn += bf_lo(qw[j]) * bf_lo(qw[j]) + bf_hi(qw[j]) * bf_hi(qw[j]);
                const bool ok = (qn * km <= 3600.0f) && (vm <= 1.0e12f);
                const uint32_t bad = __any_sync(0xffffffffu, !ok);
                if (lane == 0) asm volatile("st.shared.u32 [%0], %1;" ::"r"(sGuard + (warp * 4 + i) * 4), "r"(bad) : "memory");
            }
            if (lane == 0) mbar_arrive(bar_guard);
        }
        __syncwarp();
        const uint64_t dA0 = make_desc(fb, 16, 1024, 1);
        const uint64_t dB0 = make_desc(fb + 8192, 8192, 1024, 1);
        float acc[64];
#pragma unroll
        for (int i = 0; i < 64; i++) asm volatile("mov.f32 %0, 0f00000000;" : "=f"(acc[i]));
#pragma unroll 1
        for (int ks = 0; ks < F2_NK; ks++) {
            const int s = ks % F2_STAGES;
            mbar_wait(f2_full + 8 * s, (ks / F2_STAGES) & 1);
            wg_fence();
#pragma unroll
            for (int kk = 0; kk < 4; kk++)
                wgmma_ss_n128_tb(acc, dA0 + (uint64_t)((s * F2_STAGE_BYTES + kk * 32) >> 4),
                                 dB0 + (uint64_t)((s * F2_STAGE_BYTES + kk * 2048) >> 4), 1);
            wg_commit();
            wg_wait<1>();
            if (ks > 0 && ks - 1 + F2_STAGES < F2_NK) {
                const int ps = (ks - 1) % F2_STAGES, k0 = (ks - 1 + F2_STAGES) * 64;
                if (lane == 0) mbar_arrive(f2_empty + 8 * ps);
                if (leader) {
                    mbar_wait(f2_empty + 8 * ps, ((ks - 1) / F2_STAGES) & 1);
                    mbar_expect_tx(f2_full + 8 * ps, F2_STAGE_BYTES);
                    tma_load_2d(fb + ps * F2_STAGE_BYTES, &tm_h, k0, rb * 64, f2_full + 8 * ps);
                    tma_load_2d(fb + ps * F2_STAGE_BYTES + 8192, &tm_w2, cb * 128, k0, f2_full + 8 * ps);
                    tma_load_2d(fb + ps * F2_STAGE_BYTES + 16384, &tm_w2, cb * 128 + 64, k0, f2_full + 8 * ps);
                }
                __syncwarp();
            }
        }
        wg_wait<0>();
        fence_regs<64>(acc);
        uint32_t* gp = reinterpret_cast<uint32_t*>(G + (size_t)(rb * 64 + warp * 16 + g) * D_MODEL + cb * 128) + t;
#pragma unroll
        for (int j = 0; j < 16; j++) {
            const uint32_t bb = __ldg(reinterpret_cast<const uint32_t*>(b2 + cb * 128 + j * 8) + t);
            const float b0 = bf_lo(bb), b1v = bf_hi(bb);
            const float z0 = acc[4 * j] + b0, z1 = acc[4 * j + 1] + b1v, z2 = acc[4 * j + 2] + b0, z3 = acc[4 * j + 3] + b1v;
            gp[j * 4] = pack_bf16(__fdividef(z0, 1.0f + __expf(-z0)), __fdividef(z1, 1.0f + __expf(-z1)));
            gp[j * 4 + 8 * (D_MODEL / 2)] = pack_bf16(__fdividef(z2, 1.0f + __expf(-z2)), __fdividef(z3, 1.0f + __expf(-z3)));
        }
        if (leader) DEV_STAMP(1, 5);
        return;
    }

    pdl_wait();
    pdl_launch();
    if (tid == 0) DEV_STAMP(1, 1);
    if (tid == 0) { at_load_chunk(sbase, KV, bar0, 0); at_load_chunk(sbase, KV, bar0, 1); at_load_chunk(sbase, KV, bar0, 2); }
    if (tid >= 128 && tid < 288) colpart[blockIdx.x * 160 + tid - 128] = make_uint2(NOT_READY, NOT_READY);
    if (tid >= 288 && tid < 304) rowstat[blockIdx.x * 16 + tid - 288] = make_uint2(NOT_READY, NOT_READY);
    const int rowA = blockIdx.x * 512 + wg * 128 + warp * 16;
    const uint32_t* qp = reinterpret_cast<const uint32_t*>(Q + (size_t)(rowA + g) * 16);
    const uint32_t lo0 = ((sbase & 0x3FFFF) >> 4) | (8u << 16);

#define AT_EXP(P) _Pragma("unroll") for (int i = 0; i < AT_KT / 4; i++) {                       \
                if ((AT_SWMASK >> (i & 15)) & 1) P[i] = exp2_pair_alu(s[2 * i], s[2 * i + 1]);  \
                else P[i] = pack_bf16(ex2(s[2 * i]), ex2(s[2 * i + 1])); }
#define AT_PV(P, st) _Pragma("unroll") for (int j = 0; j < AT_KT / 16; j++)                     \
                wgmma_pv(o, P[4 * j], P[4 * j + 1], P[4 * j + 2], P[4 * j + 3],                 \
                         desc64(vlo + ((st) * 4 + j) * 32, vhi - ((st) * 4 + j) * 16));
#define AT_PIPE 2
#define AT_EXPH(P, h) _Pragma("unroll") for (int i = (h) * 8; i < (h) * 8 + 8; i++) {           \
                if ((AT_SWMASK >> (i & 15)) & 1) P[i] = exp2_pair_alu(s[2 * i], s[2 * i + 1]);  \
                else P[i] = pack_bf16(ex2(s[2 * i]), ex2(s[2 * i + 1])); }
#define AT_PVH(P, st, h) _Pragma("unroll") for (int j = (h) * 2; j < (h) * 2 + 2; j++)          \
                wgmma_pv(o, P[4 * j], P[4 * j + 1], P[4 * j + 2], P[4 * j + 3],                 \
                         desc64(vlo + ((st) * 4 + j) * 32, vhi - ((st) * 4 + j) * 16));
#define AT_STEP(st, PC, PN, klo, khi) {                                                         \
                wg_wait<0>();                                                                   \
                fence_regs<AT_KT / 2>(s);                                                       \
                AT_EXPH(p0, 0);                                                                 \
                wg_fence();                                                                     \
                AT_PVH(p0, st, 0);                                                              \
                wg_commit();                                                                    \
                AT_EXPH(p0, 1);                                                                 \
                if (st == AT_SPC - 1 && mt == 0) mbar_wait(bar0 + 8 * (c + 1), 0);              \
                wg_wait<0>();                                                                   \
                wg_fence();                                                                     \
                wgmma_qk_acc_n64(s, q, desc64(klo, khi));                                       \
                AT_PVH(p0, st, 1);                                                              \
                wg_commit(); }

#pragma unroll 1
    for (int mt = 0; mt < 2; mt++) {
        uint32_t q[4];
        q[0] = qp[mt * 512 + t]; q[2] = qp[mt * 512 + t + 4]; q[1] = qp[mt * 512 + 64 + t]; q[3] = qp[mt * 512 + 64 + t + 4];
        float o[12];
#pragma unroll
        for (int i = 0; i < 12; i++) asm volatile("mov.f32 %0, 0f00000000;" : "=f"(o[i]));
        float s[AT_KT / 2];
        uint32_t p0[AT_KT / 4], p1[AT_KT / 4];
        (void)p1;
#pragma unroll
        for (int i = 0; i < AT_KT / 2; i++) {
            if ((AT_SWMASK >> ((i >> 1) & 15)) & 1) asm volatile("mov.f32 %0, %1;" : "=f"(s[i]) : "f"(AT_MAGIC));
            else asm volatile("mov.f32 %0, 0f00000000;" : "=f"(s[i]));
        }
        if (mt == 0) mbar_wait(bar0, 0);
        if (tid == 0) DEV_STAMP(1, 2 + mt);
        uint32_t klo = lo0 + 16, vlo = lo0, vhi = 4096;
        wg_fence();
        wgmma_qk_acc_n64(s, q, desc64(klo, 32));
        wg_commit();
        uint32_t kst = 256, khi = 32;
#pragma unroll 1
        for (int c = 0; c < AT_NCHUNK - 1; c++) {
            if (tid == 0 && mt == 0 && c + 3 < AT_NCHUNK) at_load_chunk(sbase, KV, bar0, c + 3);
            AT_STEP(0, p0, p1, klo + kst, khi); AT_STEP(1, p1, p0, klo + 2 * kst, khi); AT_STEP(2, p0, p1, klo + 3 * kst, khi);
            if (c == 3) { klo = lo0 + (98304 >> 4); kst = 128; khi = 16; } else klo += 4 * kst;
            AT_STEP(3, p1, p0, klo, khi);
            vlo += 512; vhi -= 256;
        }
        {
            const int c = 0; (void)c;
            AT_STEP(0, p0, p1, klo + 128, 16); AT_STEP(1, p1, p0, klo + 256, 16); AT_STEP(2, p0, p1, klo + 384, 16);
            wg_wait<0>();
            fence_regs<AT_KT / 2>(s);
            AT_EXP(p0);
            wg_fence();
            AT_PV(p0, 3);
            wg_commit();
            wg_wait<0>();
            fence_regs<12>(o);
        }
        at_store(o, O, rowA + mt * 64, lane);
    }
    if (tid == 0) DEV_STAMP(1, 4);

    mbar_wait(bar_guard, 0);
    uint32_t bad;
    asm volatile("ld.shared.u32 %0, [%1];" : "=r"(bad) : "r"(sGuard + (tid >> 5) * 4) : "memory");
    if (__any_sync(0xffffffffu, bad != 0) == 0) return;
    attn_fallback(Q, KV, O, sbase);
}

constexpr int K3_STAGE_BYTES = 8192 + 16384;
constexpr int K3_X = 8 * K3_STAGE_BYTES;
constexpr int K3_G = K3_X + 16384;
constexpr int K3_SMEM = K3_G + 16384 + 256;

__global__ void __launch_bounds__(256, 1)
k3_out(const __grid_constant__ CUtensorMap tm_o, const __grid_constant__ CUtensorMap tm_wo,
       const __grid_constant__ CUtensorMap tm_x, const __grid_constant__ CUtensorMap tm_g,
       const __grid_constant__ CUtensorMap tm_out) {
    extern __shared__ __align__(1024) uint8_t smem_raw[];
    const uint32_t sbase = smem_u32(smem_raw);
    const uint32_t bar_full = sbase + K3_G + 16384, bar_x = bar_full + 64;
    const int tid = threadIdx.x, warp = __shfl_sync(0xffffffffu, tid >> 5, 0), lane = tid & 31;
    const int rb = blockIdx.x >> 2, cb = blockIdx.x & 3;
    if (tid == 0) {
        DEV_STAMP(2, 0);
        for (int s = 0; s < 8; s++) mbar_init(bar_full + 8 * s, 1);
        mbar_init(bar_x, 1);
        mbar_init_fence();
        for (int s = 0; s < 8; s++) mbar_expect_tx(bar_full + 8 * s, K3_STAGE_BYTES);
        mbar_expect_tx(bar_x, 32768);
    }
    __syncthreads();
    if (tid == 0) {
        pdl_wait();
        DEV_STAMP(2, 1);
#pragma unroll
        for (int s = 0; s < 8; s++) tma_load_2d(sbase + s * K3_STAGE_BYTES, &tm_o, s * 64, rb * 64, bar_full + 8 * s);
        tma_load_2d(sbase + K3_G, &tm_g, cb * 128, rb * 64, bar_x);
        tma_load_2d(sbase + K3_G + 8192, &tm_g, cb * 128 + 64, rb * 64, bar_x);
    } else if (lane == 0 && warp <= 2) {
        const int h = warp - 1;
#pragma unroll
        for (int s = 0; s < 8; s++) tma_load_2d(sbase + s * K3_STAGE_BYTES + 8192 + h * 8192, &tm_wo, cb * 128 + h * 64, s * 64, bar_full + 8 * s);
        tma_load_2d(sbase + K3_X + h * 8192, &tm_x, cb * 128 + h * 64, rb * 64, bar_x);
    }
    __syncwarp();
    const int wg = warp >> 2;
    float acc[32];
#pragma unroll
    for (int i = 0; i < 32; i++) asm volatile("mov.f32 %0, 0f00000000;" : "=f"(acc[i]));
    const uint64_t dA0 = make_desc(sbase, 16, 1024, 1);
    const uint64_t dB0 = make_desc(sbase + 8192 + wg * 8192, 8192, 1024, 1);
#pragma unroll 1
    for (int ks = 0; ks < 8; ks++) {
        mbar_wait(bar_full + 8 * ks, 0);
        wg_fence();
#pragma unroll
        for (int kk = 0; kk < 4; kk++)
            wgmma_ss_n64_tb(acc, dA0 + (uint64_t)((ks * K3_STAGE_BYTES + kk * 32) >> 4),
                            dB0 + (uint64_t)((ks * K3_STAGE_BYTES + kk * 2048) >> 4), 1);
        wg_commit();
    }
    wg_wait<0>();
    fence_regs<32>(acc);
    if (tid == 0) DEV_STAMP(2, 2);
    mbar_wait(bar_x, 0);
    const int g = lane >> 2, t = lane & 3;
    const int row0 = (warp & 3) * 16 + g;
    const uint32_t sX = sbase + K3_X + wg * 8192, sG = sbase + K3_G + wg * 8192;
#pragma unroll
    for (int j = 0; j < 8; j++) {
#pragma unroll
        for (int h = 0; h < 2; h++) {
            const int row = row0 + h * 8;
            const uint32_t off = row * 128 + ((j ^ (row & 7)) << 4) + t * 4;
            uint32_t xv, gv;
            asm volatile("ld.shared.b32 %0, [%1];" : "=r"(xv) : "r"(sX + off) : "memory");
            asm volatile("ld.shared.b32 %0, [%1];" : "=r"(gv) : "r"(sG + off) : "memory");
            const uint32_t ov = pack_bf16(fmaf(acc[4 * j + 2 * h], bf_lo(gv), bf_lo(xv)), fmaf(acc[4 * j + 2 * h + 1], bf_hi(gv), bf_hi(xv)));
            asm volatile("st.shared.b32 [%0], %1;" ::"r"(sX + off), "r"(ov) : "memory");
        }
    }
    fence_proxy_async();
    __syncwarp();
    if (lane == 0) {
        tma_store_2d(&tm_out, sX + (warp & 3) * 2048, cb * 128 + wg * 64, rb * 64 + (warp & 3) * 16);
        tma_store_commit();
        if (tid == 0) DEV_STAMP(2, 3);
        tma_store_wait();
        if (tid == 0) DEV_STAMP(2, 4);
    }
}

typedef CUresult (*EncodeFn)(CUtensorMap*, CUtensorMapDataType, cuuint32_t, void*, const cuuint64_t*, const cuuint64_t*,
                             const cuuint32_t*, const cuuint32_t*, CUtensorMapInterleave, CUtensorMapSwizzle,
                             CUtensorMapL2promotion, CUtensorMapFloatOOBfill);

struct HostState {
    bool ready;
    const void* key[11];
    CUtensorMap wq, wk, wv, w1, qo, ho, hi, oi, w2, wo, xi, xi64, gi, out;
    void *pQ, *pKV, *pH, *pO, *pMax, *pRow, *pCol, *pFlag, *pG;
};
HostState g_hs;

void make_map(EncodeFn fn, CUtensorMap* m, const void* ptr, uint64_t inner, uint64_t outer, uint32_t box_in, uint32_t box_out) {
    cuuint64_t dims[2] = {inner, outer};
    cuuint64_t strides[1] = {inner * 2};
    cuuint32_t box[2] = {box_in, box_out};
    cuuint32_t es[2] = {1, 1};
    fn(m, CU_TENSOR_MAP_DATA_TYPE_BFLOAT16, 2, const_cast<void*>(ptr), dims, strides, box, es, CU_TENSOR_MAP_INTERLEAVE_NONE,
       CU_TENSOR_MAP_SWIZZLE_128B, CU_TENSOR_MAP_L2_PROMOTION_L2_256B, CU_TENSOR_MAP_FLOAT_OOB_FILL_NONE);
}

template <typename... KArgs, typename... Args>
void launch(void (*kern)(KArgs...), int grid, int block, int smem, bool pdl, int cluster, Args... args) {
    cudaLaunchConfig_t cfg = {};
    cfg.gridDim = dim3(grid); cfg.blockDim = dim3(block); cfg.dynamicSmemBytes = smem; cfg.stream = cudaStreamPerThread;
    cudaLaunchAttribute at[2];
    int n = 0;
    if (pdl) { at[n].id = cudaLaunchAttributeProgrammaticStreamSerialization; at[n].val.programmaticStreamSerializationAllowed = 1; n++; }
    if (cluster > 1) { at[n].id = cudaLaunchAttributeClusterDimension; at[n].val.clusterDim.x = cluster; at[n].val.clusterDim.y = 1; at[n].val.clusterDim.z = 1; n++; }
    cfg.attrs = at; cfg.numAttrs = n;
    cudaLaunchKernelEx(&cfg, kern, KArgs(args)...);
}

}

extern "C" void kernel_launch(void* const* d_in, const int* in_sizes, int n_in, void* d_out, int out_size) {
    (void)in_sizes; (void)n_in; (void)out_size;
    HostState& hs = g_hs;
    bool same = hs.ready;
    for (int i = 0; i < 10 && same; i++) same = hs.key[i] == d_in[i];
    same = same && hs.key[10] == d_out;
    if (!same) {
        void* fp = nullptr;
        cudaDriverEntryPointQueryResult qr;
        cudaGetDriverEntryPoint("cuTensorMapEncodeTiled", &fp, cudaEnableDefault, &qr);
        EncodeFn fn = (EncodeFn)fp;
        cudaGetSymbolAddress(&hs.pQ, g_Q); cudaGetSymbolAddress(&hs.pKV, g_KV); cudaGetSymbolAddress(&hs.pH, g_H);
        cudaGetSymbolAddress(&hs.pO, g_O); cudaGetSymbolAddress(&hs.pMax, g_kvmax);
        cudaGetSymbolAddress(&hs.pRow, g_rowstat); cudaGetSymbolAddress(&hs.pCol, g_colpart); cudaGetSymbolAddress(&hs.pG, g_G);
        make_map(fn, &hs.wq, d_in[1], 512, 512, 64, 64);
        make_map(fn, &hs.wk, d_in[2], 16, 512, 64, 64);
        make_map(fn, &hs.wv, d_in[3], 16, 512, 64, 64);
        make_map(fn, &hs.w1, d_in[6], F_DIM, 512, 64, 64);
        make_map(fn, &hs.qo, hs.pQ, 512, S_LEN, 64, 16);
        make_map(fn, &hs.ho, hs.pH, F_DIM, S_LEN, 64, 16);
        make_map(fn, &hs.hi, hs.pH, F_DIM, S_LEN, 64, 64);
        make_map(fn, &hs.gi, hs.pG, 512, S_LEN, 64, 64);
        make_map(fn, &hs.xi64, d_in[0], 512, S_LEN, 64, 64);
        make_map(fn, &hs.oi, hs.pO, 512, S_LEN, 64, 64);
        make_map(fn, &hs.w2, d_in[8], 512, F_DIM, 64, 64);
        make_map(fn, &hs.wo, d_in[4], 512, 512, 64, 64);
        make_map(fn, &hs.xi, d_in[0], 512, S_LEN, 64, 128);
        make_map(fn, &hs.out, d_out, 512, S_LEN, 64, 16);
        cudaFuncSetAttribute(k1_proj, cudaFuncAttributeMaxDynamicSharedMemorySize, K1_SMEM);
        cudaFuncSetAttribute(k2_attn, cudaFuncAttributeMaxDynamicSharedMemorySize, AT_SMEM);
        cudaFuncSetAttribute(k3_out, cudaFuncAttributeMaxDynamicSharedMemorySize, K3_SMEM);
        for (int i = 0; i < 10; i++) hs.key[i] = d_in[i];
        hs.key[10] = d_out;
        hs.ready = true;
    }
    launch(k1_proj, 128, 384, K1_SMEM, false, 2, hs.xi, hs.wq, hs.wk, hs.wv, hs.w1, hs.qo, hs.ho, (const __nv_bfloat16*)d_in[0],
           (const __nv_bfloat16*)d_in[7], (float2*)hs.pRow, (float*)hs.pCol, (__nv_bfloat16*)hs.pKV, (float*)hs.pMax);
    launch(k2_attn, 128, 640, AT_SMEM, true, 1, hs.hi, hs.w2, (const __nv_bfloat16*)hs.pQ, (const __nv_bfloat16*)hs.pKV,
           (const float*)hs.pMax, (const __nv_bfloat16*)d_in[9], (__nv_bfloat16*)hs.pO, (__nv_bfloat16*)hs.pG, (uint2*)hs.pRow, (uint2*)hs.pCol);
    launch(k3_out, 128, 256, K3_SMEM, true, 1, hs.oi, hs.wo, hs.xi64, hs.gi, hs.out);
}
```

```cpp
#include <cuda_runtime.h>
#include <cuda_bf16.h>
#include <cuda.h>
#include <stdint.h>

namespace {

constexpr int S_LEN = 2048, D_MODEL = 512, F_DIM = 1792;

__device__ __align__(1024) __nv_bfloat16 g_Q[S_LEN * D_MODEL];
__device__ __align__(1024) __nv_bfloat16 g_KV[6 * S_LEN * 8];
__device__ __align__(1024) __nv_bfloat16 g_G[S_LEN * D_MODEL];
__device__ __align__(1024) __nv_bfloat16 g_H[S_LEN * F_DIM];
__device__ __align__(1024) __nv_bfloat16 g_O[S_LEN * D_MODEL];
__device__ __align__(1024) float g_kvmax[256];
__device__ __align__(1024) float2 g_rowstat[S_LEN];
__device__ __align__(1024) float g_colpart[8 * 16 * 320];

#define DEV_STAMP(k, e) do {} while (0)
__device__ __forceinline__ uint32_t smem_u32(const void* p) { return (uint32_t)__cvta_generic_to_shared(p); }
__device__ __forceinline__ void wg_fence() { asm volatile("wgmma.fence.sync.aligned;" ::: "memory"); }
__device__ __forceinline__ void wg_commit() { asm volatile("wgmma.commit_group.sync.aligned;" ::: "memory"); }
template <int N> __device__ __forceinline__ void wg_wait() { asm volatile("wgmma.wait_group.sync.aligned %0;" ::"n"(N) : "memory"); }
template <int N> __device__ __forceinline__ void fence_regs(float* r) {
#pragma unroll
    for (int i = 0; i < N; i++) asm volatile("" : "+f"(r[i])::"memory");
}
__device__ __forceinline__ void fence_proxy_async() { asm volatile("fence.proxy.async.shared::cta;" ::: "memory"); }
__device__ __forceinline__ void mbar_init(uint32_t bar, int cnt) { asm volatile("mbarrier.init.shared::cta.b64 [%0], %1;" ::"r"(bar), "r"(cnt) : "memory"); }
__device__ __forceinline__ void mbar_init_fence() { asm volatile("fence.mbarrier_init.release.cluster;" ::: "memory"); }
__device__ __forceinline__ void mbar_expect_tx(uint32_t bar, uint32_t bytes) {
    asm volatile("mbarrier.arrive.expect_tx.shared::cta.b64 _, [%0], %1;" ::"r"(bar), "r"(bytes) : "memory");
}
__device__ __forceinline__ void mbar_arrive(uint32_t bar) { asm volatile("mbarrier.arrive.shared::cta.b64 _, [%0];" ::"r"(bar) : "memory"); }
__device__ __forceinline__ bool mbar_try(uint32_t bar, uint32_t parity) {
    uint32_t ok;
    asm volatile("{\n.reg .pred p;\nmbarrier.try_wait.parity.shared::cta.b64 p, [%1], %2;\nselp.u32 %0, 1, 0, p;\n}\n"
                 : "=r"(ok) : "r"(bar), "r"(parity) : "memory");
    return ok != 0;
}
__device__ __forceinline__ void mbar_wait(uint32_t bar, uint32_t parity) {
    if (mbar_try(bar, parity)) return;
    const long long t0 = clock64();
#pragma unroll 1
    while (!mbar_try(bar, parity)) {
        if (clock64() - t0 > 20000000ll) {
            break;
        }
    }
}
__device__ __forceinline__ void bulk_g2s(uint32_t dst, const void* src, uint32_t bytes, uint32_t bar) {
    asm volatile("cp.async.bulk.shared::cluster.global.mbarrier::complete_tx::bytes [%0], [%1], %2, [%3];"
                 ::"r"(dst), "l"(src), "r"(bytes), "r"(bar) : "memory");
}
__device__ __forceinline__ void tma_load_2d(uint32_t dst, const CUtensorMap* tm, int c0, int c1, uint32_t bar) {
    asm volatile("cp.async.bulk.tensor.2d.shared::cluster.global.mbarrier::complete_tx::bytes [%0], [%1, {%3, %4}], [%2];"
                 ::"r"(dst), "l"((uint64_t)tm), "r"(bar), "r"(c0), "r"(c1) : "memory");
}
__device__ __forceinline__ void tma_load_2d_mc(uint32_t dst, const CUtensorMap* tm, int c0, int c1, uint32_t bar, uint16_t mask) {
    asm volatile("cp.async.bulk.tensor.2d.shared::cluster.global.mbarrier::complete_tx::bytes.multicast::cluster [%0], [%1, {%3, %4}], [%2], %5;"
                 ::"r"(dst), "l"((uint64_t)tm), "r"(bar), "r"(c0), "r"(c1), "h"(mask) : "memory");
}
__device__ __forceinline__ void mbar_arrive_remote(uint32_t bar, uint32_t cta) {
    asm volatile("{\n.reg .b32 ra;\nmapa.shared::cluster.u32 ra, %0, %1;\nmbarrier.arrive.shared::cluster.b64 _, [ra];\n}\n"
                 ::"r"(bar), "r"(cta) : "memory");
}
__device__ __forceinline__ void cluster_sync_relaxed() {
    asm volatile("barrier.cluster.arrive.relaxed;\nbarrier.cluster.wait;" ::: "memory");
}
__device__ __forceinline__ uint2 ld_relaxed_v2(const void* p) {
    uint2 v; asm volatile("ld.relaxed.gpu.global.v2.b32 {%0,%1}, [%2];" : "=r"(v.x), "=r"(v.y) : "l"(p) : "memory"); return v;
}
constexpr uint32_t NOT_READY = 0u;
__device__ __forceinline__ float xch_enc(float v) { return __uint_as_float((v == 0.f ? 0u : __float_as_uint(v)) ^ 0x80000000u); }
__device__ __forceinline__ float xch_dec(uint32_t u) { return __uint_as_float(u ^ 0x80000000u); }
__device__ __forceinline__ void tma_store_2d(const CUtensorMap* tm, uint32_t src, int c0, int c1) {
    asm volatile("cp.async.bulk.tensor.2d.global.shared::cta.bulk_group [%0, {%2, %3}], [%1];"
                 ::"l"((uint64_t)tm), "r"(src), "r"(c0), "r"(c1) : "memory");
}
__device__ __forceinline__ void tma_store_commit() { asm volatile("cp.async.bulk.commit_group;" ::: "memory"); }
__device__ __forceinline__ void tma_store_wait() { asm volatile("cp.async.bulk.wait_group 0;" ::: "memory"); }
__device__ __forceinline__ void tma_prefetch_desc(const CUtensorMap* tm) { asm volatile("prefetch.tensormap [%0];" ::"l"((uint64_t)tm) : "memory"); }
__device__ __forceinline__ void named_bar_sync(int id, int n) { asm volatile("bar.sync %0, %1;" ::"r"(id), "r"(n) : "memory"); }
__device__ __forceinline__ void pdl_wait() { asm volatile("griddepcontrol.wait;" ::: "memory"); }
__device__ __forceinline__ void pdl_launch() { asm volatile("griddepcontrol.launch_dependents;" ::: "memory"); }
template <int N> __device__ __forceinline__ void reg_alloc() { asm volatile("setmaxnreg.inc.sync.aligned.u32 %0;" ::"n"(N)); }
template <int N> __device__ __forceinline__ void reg_dealloc() { asm volatile("setmaxnreg.dec.sync.aligned.u32 %0;" ::"n"(N)); }
__device__ __forceinline__ float ex2(float x) { float y; asm("ex2.approx.ftz.f32 %0, %1;" : "=f"(y) : "f"(x)); return y; }
__device__ __forceinline__ uint32_t pack_bf16(float lo, float hi) {
    uint32_t r; asm("cvt.rn.bf16x2.f32 %0, %1, %2;" : "=r"(r) : "f"(hi), "f"(lo)); return r;
}
__device__ __forceinline__ uint32_t pack_bf16_relu(float lo, float hi) {
    uint32_t r; asm("cvt.rn.relu.bf16x2.f32 %0, %1, %2;" : "=r"(r) : "f"(hi), "f"(lo)); return r;
}
__device__ __forceinline__ uint32_t mul_bf16x2(uint32_t a, uint32_t b) {
    uint32_t r; asm("mul.rn.bf16x2 %0, %1, %2;" : "=r"(r) : "r"(a), "r"(b)); return r;
}
__device__ __forceinline__ float bf_lo(uint32_t v) { return __uint_as_float(v << 16); }
__device__ __forceinline__ float bf_hi(uint32_t v) { return __uint_as_float(v & 0xFFFF0000u); }
__device__ __forceinline__ void stmatrix_x4(uint32_t addr, uint32_t r0, uint32_t r1, uint32_t r2, uint32_t r3) {
    asm volatile("stmatrix.sync.aligned.m8n8.x4.shared.b16 [%0], {%1,%2,%3,%4};" ::"r"(addr), "r"(r0), "r"(r1), "r"(r2), "r"(r3) : "memory");
}
__device__ __forceinline__ uint64_t make_desc(uint32_t addr, uint32_t lbo, uint32_t sbo, uint32_t swz) {
    return (uint64_t)((addr & 0x3FFFF) >> 4) | ((uint64_t)(lbo >> 4) << 16) | ((uint64_t)(sbo >> 4) << 32) | ((uint64_t)swz << 62);
}

__device__ __forceinline__ uint64_t desc64(uint32_t lo, uint32_t hi) {
    uint64_t d; asm("mov.b64 %0, {%1, %2};" : "=l"(d) : "r"(lo), "r"(hi)); return d;
}

__device__ __forceinline__ void wgmma_ss_n256_tb(float* d, uint64_t descA, uint64_t descB, int scaleD) {
    asm volatile("{\n.reg .pred p;\nsetp.ne.b32 p, %130, 0;\n"
      "wgmma.mma_async.sync.aligned.m64n256k16.f32.bf16.bf16 {%0,%1,%2,%3,%4,%5,%6,%7,%8,%9,%10,%11,%12,%13,%14,%15,%16,%17,%18,%19,%20,%21,%22,%23,%24,%25,%26,%27,%28,%29,%30,%31,%32,%33,%34,%35,%36,%37,%38,%39,%40,%41,%42,%43,%44,%45,%46,%47,%48,%49,%50,%51,%52,%53,%54,%55,%56,%57,%58,%59,%60,%61,%62,%63,%64,%65,%66,%67,%68,%69,%70,%71,%72,%73,%74,%75,%76,%77,%78,%79,%80,%81,%82,%83,%84,%85,%86,%87,%88,%89,%90,%91,%92,%93,%94,%95,%96,%97,%98,%99,%100,%101,%102,%103,%104,%105,%106,%107,%108,%109,%110,%111,%112,%113,%114,%115,%116,%117,%118,%119,%120,%121,%122,%123,%124,%125,%126,%127}, %128, %129, p, 1, 1, 0, 1;\n}\n"
      : "+f"(d[0]), "+f"(d[1]), "+f"(d[2]), "+f"(d[3]), "+f"(d[4]), "+f"(d[5]), "+f"(d[6]), "+f"(d[7]), "+f"(d[8]), "+f"(d[9]), "+f"(d[10]), "+f"(d[11]), "+f"(d[12]), "+f"(d[13]), "+f"(d[14]), "+f"(d[15]), "+f"(d[16]), "+f"(d[17]), "+f"(d[18]), "+f"(d[19]), "+f"(d[20]), "+f"(d[21]), "+f"(d[22]), "+f"(d[23]), "+f"(d[24]), "+f"(d[25]), "+f"(d[26]), "+f"(d[27]), "+f"(d[28]), "+f"(d[29]), "+f"(d[30]), "+f"(d[31]), "+f"(d[32]), "+f"(d[33]), "+f"(d[34]), "+f"(d[35]), "+f"(d[36]), "+f"(d[37]), "+f"(d[38]), "+f"(d[39]), "+f"(d[40]), "+f"(d[41]), "+f"(d[42]), "+f"(d[43]), "+f"(d[44]), "+f"(d[45]), "+f"(d[46]), "+f"(d[47]), "+f"(d[48]), "+f"(d[49]), "+f"(d[50]), "+f"(d[51]), "+f"(d[52]), "+f"(d[53]), "+f"(d[54]), "+f"(d[55]), "+f"(d[56]), "+f"(d[57]), "+f"(d[58]), "+f"(d[59]), "+f"(d[60]), "+f"(d[61]), "+f"(d[62]), "+f"(d[63]), "+f"(d[64]), "+f"(d[65]), "+f"(d[66]), "+f"(d[67]), "+f"(d[68]), "+f"(d[69]), "+f"(d[70]), "+f"(d[71]), "+f"(d[72]), "+f"(d[73]), "+f"(d[74]), "+f"(d[75]), "+f"(d[76]), "+f"(d[77]), "+f"(d[78]), "+f"(d[79]), "+f"(d[80]), "+f"(d[81]), "+f"(d[82]), "+f"(d[83]), "+f"(d[84]), "+f"(d[85]), "+f"(d[86]), "+f"(d[87]), "+f"(d[88]), "+f"(d[89]), "+f"(d[90]), "+f"(d[91]), "+f"(d[92]), "+f"(d[93]), "+f"(d[94]), "+f"(d[95]), "+f"(d[96]), "+f"(d[97]), "+f"(d[98]), "+f"(d[99]), "+f"(d[100]), "+f"(d[101]), "+f"(d[102]), "+f"(d[103]), "+f"(d[104]), "+f"(d[105]), "+f"(d[106]), "+f"(d[107]), "+f"(d[108]), "+f"(d[109]), "+f"(d[110]), "+f"(d[111]), "+f"(d[112]), "+f"(d[113]), "+f"(d[114]), "+f"(d[115]), "+f"(d[116]), "+f"(d[117]), "+f"(d[118]), "+f"(d[119]), "+f"(d[120]), "+f"(d[121]), "+f"(d[122]), "+f"(d[123]), "+f"(d[124]), "+f"(d[125]), "+f"(d[126]), "+f"(d[127])
      : "l"(descA), "l"(descB), "r"(scaleD));
}
__device__ __forceinline__ void wgmma_ss_n128_tb(float* d, uint64_t descA, uint64_t descB, int scaleD) {
    asm volatile("{\n.reg .pred p;\nsetp.ne.b32 p, %66, 0;\n"
      "wgmma.mma_async.sync.aligned.m64n128k16.f32.bf16.bf16 {%0,%1,%2,%3,%4,%5,%6,%7,%8,%9,%10,%11,%12,%13,%14,%15,%16,%17,%18,%19,%20,%21,%22,%23,%24,%25,%26,%27,%28,%29,%30,%31,%32,%33,%34,%35,%36,%37,%38,%39,%40,%41,%42,%43,%44,%45,%46,%47,%48,%49,%50,%51,%52,%53,%54,%55,%56,%57,%58,%59,%60,%61,%62,%63}, %64, %65, p, 1, 1, 0, 1;\n}\n"
      : "+f"(d[0]), "+f"(d[1]), "+f"(d[2]), "+f"(d[3]), "+f"(d[4]), "+f"(d[5]), "+f"(d[6]), "+f"(d[7]), "+f"(d[8]), "+f"(d[9]), "+f"(d[10]), "+f"(d[11]), "+f"(d[12]), "+f"(d[13]), "+f"(d[14]), "+f"(d[15]), "+f"(d[16]), "+f"(d[17]), "+f"(d[18]), "+f"(d[19]), "+f"(d[20]), "+f"(d[21]), "+f"(d[22]), "+f"(d[23]), "+f"(d[24]), "+f"(d[25]), "+f"(d[26]), "+f"(d[27]), "+f"(d[28]), "+f"(d[29]), "+f"(d[30]), "+f"(d[31]), "+f"(d[32]), "+f"(d[33]), "+f"(d[34]), "+f"(d[35]), "+f"(d[36]), "+f"(d[37]), "+f"(d[38]), "+f"(d[39]), "+f"(d[40]), "+f"(d[41]), "+f"(d[42]), "+f"(d[43]), "+f"(d[44]), "+f"(d[45]), "+f"(d[46]), "+f"(d[47]), "+f"(d[48]), "+f"(d[49]), "+f"(d[50]), "+f"(d[51]), "+f"(d[52]), "+f"(d[53]), "+f"(d[54]), "+f"(d[55]), "+f"(d[56]), "+f"(d[57]), "+f"(d[58]), "+f"(d[59]), "+f"(d[60]), "+f"(d[61]), "+f"(d[62]), "+f"(d[63])
      : "l"(descA), "l"(descB), "r"(scaleD));
}
__device__ __forceinline__ void wgmma_ss_n64_tb(float* d, uint64_t descA, uint64_t descB, int scaleD) {
    asm volatile("{\n.reg .pred p;\nsetp.ne.b32 p, %34, 0;\n"
      "wgmma.mma_async.sync.aligned.m64n64k16.f32.bf16.bf16 {%0,%1,%2,%3,%4,%5,%6,%7,%8,%9,%10,%11,%12,%13,%14,%15,%16,%17,%18,%19,%20,%21,%22,%23,%24,%25,%26,%27,%28,%29,%30,%31}, %32, %33, p, 1, 1, 0, 1;\n}\n"
      : "+f"(d[0]), "+f"(d[1]), "+f"(d[2]), "+f"(d[3]), "+f"(d[4]), "+f"(d[5]), "+f"(d[6]), "+f"(d[7]), "+f"(d[8]), "+f"(d[9]), "+f"(d[10]), "+f"(d[11]), "+f"(d[12]), "+f"(d[13]), "+f"(d[14]), "+f"(d[15]), "+f"(d[16]), "+f"(d[17]), "+f"(d[18]), "+f"(d[19]), "+f"(d[20]), "+f"(d[21]), "+f"(d[22]), "+f"(d[23]), "+f"(d[24]), "+f"(d[25]), "+f"(d[26]), "+f"(d[27]), "+f"(d[28]), "+f"(d[29]), "+f"(d[30]), "+f"(d[31])
      : "l"(descA), "l"(descB), "r"(scaleD));
}
__device__ __forceinline__ void wgmma_qk_acc_n64(float* d, const uint32_t* a, uint64_t descB) {
    asm volatile("wgmma.mma_async.sync.aligned.m64n64k16.f32.bf16.bf16 {%0,%1,%2,%3,%4,%5,%6,%7,%8,%9,%10,%11,%12,%13,%14,%15,%16,%17,%18,%19,%20,%21,%22,%23,%24,%25,%26,%27,%28,%29,%30,%31}, {%32,%33,%34,%35}, %36, 1, 1, 1, 0;\n"
      : "+f"(d[0]), "+f"(d[1]), "+f"(d[2]), "+f"(d[3]), "+f"(d[4]), "+f"(d[5]), "+f"(d[6]), "+f"(d[7]), "+f"(d[8]), "+f"(d[9]), "+f"(d[10]), "+f"(d[11]), "+f"(d[12]), "+f"(d[13]), "+f"(d[14]), "+f"(d[15]), "+f"(d[16]), "+f"(d[17]), "+f"(d[18]), "+f"(d[19]), "+f"(d[20]), "+f"(d[21]), "+f"(d[22]), "+f"(d[23]), "+f"(d[24]), "+f"(d[25]), "+f"(d[26]), "+f"(d[27]), "+f"(d[28]), "+f"(d[29]), "+f"(d[30]), "+f"(d[31])
      : "r"(a[0]), "r"(a[1]), "r"(a[2]), "r"(a[3]), "l"(descB));
}

__device__ __forceinline__ void wgmma_pv(float* d, uint32_t a0, uint32_t a1, uint32_t a2, uint32_t a3, uint64_t descB) {
    asm volatile("wgmma.mma_async.sync.aligned.m64n24k16.f32.bf16.bf16 {%0,%1,%2,%3,%4,%5,%6,%7,%8,%9,%10,%11}, {%12,%13,%14,%15}, %16, 1, 1, 1, 1;\n"
                 : "+f"(d[0]), "+f"(d[1]), "+f"(d[2]), "+f"(d[3]), "+f"(d[4]), "+f"(d[5]), "+f"(d[6]), "+f"(d[7]), "+f"(d[8]), "+f"(d[9]), "+f"(d[10]), "+f"(d[11])
                 : "r"(a0), "r"(a1), "r"(a2), "r"(a3), "l"(descB));
}

__device__ __forceinline__ void k1_panel(int g, int i, int& type, int& col) {
    if (g < 6) {
        int p = g * 5 + i;
        if (p < 8) { type = 0; col = p * 64; } else { type = 1; col = (p - 8) * 64; }
    } else {
        if (i < 3) { type = 1; col = (22 + (g - 6) * 3 + i) * 64; } else { type = 2 + (g - 6); col = 0; }
    }
}

constexpr int K1_STAGES = 4;
constexpr int K1_PANEL_BYTES = 64 * 128;
constexpr int K1_STAGE_BYTES = 16384 + 5 * K1_PANEL_BYTES;
constexpr int K1_SMEM = K1_STAGES * K1_STAGE_BYTES + 128 + 320 * 8;
constexpr float Q_SCALE = 0.25f * 1.4426950408889634f;

__global__ void __launch_bounds__(384, 1)
k1_proj(const __grid_constant__ CUtensorMap tm_x, const __grid_constant__ CUtensorMap tm_wq,
        const __grid_constant__ CUtensorMap tm_wk, const __grid_constant__ CUtensorMap tm_wv,
        const __grid_constant__ CUtensorMap tm_w1, const __grid_constant__ CUtensorMap tm_qo,
        const __grid_constant__ CUtensorMap tm_ho, const __nv_bfloat16* __restrict__ x, const __nv_bfloat16* __restrict__ b1,
        float2* rowstat, float* colpart,
        __nv_bfloat16* __restrict__ kv, float* __restrict__ kvmax) {
    extern __shared__ __align__(1024) uint8_t smem_raw[];
    const uint32_t sbase = smem_u32(smem_raw);
    const uint32_t bar_full = sbase + K1_STAGES * K1_STAGE_BYTES, bar_empty = bar_full + 8 * K1_STAGES, bar_col = bar_empty + 8 * K1_STAGES;
    const uint32_t sCol = bar_full + 128;
    const int tid = threadIdx.x, warp = __shfl_sync(0xffffffffu, tid >> 5, 0), lane = tid & 31;
    const int crank = blockIdx.x & 1, grp = (blockIdx.x >> 1) & 7, rb = (blockIdx.x >> 4) * 2 + crank;
    const int npanels = grp < 6 ? 5 : 4;
    if (tid == 0) DEV_STAMP(0, 0);

    if (tid == 288) {
        tma_prefetch_desc(&tm_x); tma_prefetch_desc(&tm_w1); tma_prefetch_desc(grp < 2 ? &tm_wq : grp == 6 ? &tm_wk : &tm_wv);
        tma_prefetch_desc(&tm_ho); tma_prefetch_desc(&tm_qo);
    }
    uint4 v[2][2];
    if (warp < 8) {
        const uint4* xp = reinterpret_cast<const uint4*>(x + (size_t)(rb * 128 + grp * 16 + warp * 2) * D_MODEL);
#pragma unroll
        for (int r = 0; r < 2; r++) { v[r][0] = __ldg(xp + r * 64 + lane); v[r][1] = __ldg(xp + r * 64 + 32 + lane); }
    }
    const int krot = rb & 8 ? 4 : 0, cstage = (rb >> 1) & 3;
    if (tid == 256) {
        for (int s = 0; s < K1_STAGES; s++) { mbar_init(bar_full + 8 * s, 1); mbar_init(bar_empty + 8 * s, s == cstage ? 18 : 16); }
        mbar_init(bar_col, 96);
        mbar_init_fence();
    }
    asm volatile("barrier.cluster.arrive.relaxed;" ::: "memory");
    if (warp != 8) asm volatile("barrier.cluster.wait;" ::: "memory");
    pdl_launch();

    if (warp >= 8) {
        reg_dealloc<88>();
        if (warp == 8) {
            const CUtensorMap* tms[5]; int cols[5];
#pragma unroll
            for (int i = 0; i < 5; i++) {
                int type, col; k1_panel(grp, i, type, col);
                tms[i] = type == 0 ? &tm_wq : type == 1 ? &tm_w1 : type == 2 ? &tm_wk : &tm_wv;
                cols[i] = col;
            }
            if (lane == 0) {
                mbar_expect_tx(bar_full, 16384 + npanels * K1_PANEL_BYTES);
                tma_load_2d(sbase, &tm_x, krot * 64, rb * 128, bar_full);
#pragma unroll
                for (int i = 0; i < 5; i++)
                    if (i < npanels) tma_load_2d(sbase + 16384 + i * K1_PANEL_BYTES, tms[i], cols[i], krot * 64, bar_full);
            }
            __syncwarp();
            asm volatile("barrier.cluster.wait;" ::: "memory");
            constexpr int KS0 = 1;
            if (lane == 0) {
                for (int ks = KS0; ks < 8; ks++) {
                    const int s = ks % K1_STAGES;
                    const uint32_t st = sbase + s * K1_STAGE_BYTES;
                    mbar_wait(bar_empty + 8 * s, ((ks / K1_STAGES) & 1) ^ 1);
                    const int k0 = ((ks + krot) & 7) * 64;
                    mbar_expect_tx(bar_full + 8 * s, 16384 + npanels * K1_PANEL_BYTES);
                    tma_load_2d(st, &tm_x, k0, rb * 128, bar_full + 8 * s);
#pragma unroll
                    for (int i = 0; i < 5; i++)
                        if (i < npanels && ((i + ks + crank) & 1) == 0)
                            tma_load_2d_mc(st + 16384 + i * K1_PANEL_BYTES, tms[i], cols[i], k0, bar_full + 8 * s, (uint16_t)3);
                }
            }
        } else {
            const int ht = tid - 288;
            mbar_wait(bar_full + 8 * cstage, 0);
            {
                const int pc = ht >> 1, half = ht & 1;
                float sacc[8];
#pragma unroll
                for (int c = 0; c < 8; c++) sacc[c] = 0.f;
                if (pc < npanels * 8) {
                    const uint32_t pb = sbase + cstage * K1_STAGE_BYTES + 16384 + (pc >> 3) * K1_PANEL_BYTES;
#pragma unroll
                    for (int i = 0; i < 16; i++) {
                        const int k = crank * 32 + 2 * i + half;
                        uint4 u;
                        asm volatile("ld.shared.v4.b32 {%0,%1,%2,%3}, [%4];" : "=r"(u.x), "=r"(u.y), "=r"(u.z), "=r"(u.w)
                                     : "r"(pb + k * 128 + (((pc & 7) ^ (k & 7)) << 4)));
                        sacc[0] += bf_lo(u.x); sacc[1] += bf_hi(u.x); sacc[2] += bf_lo(u.y); sacc[3] += bf_hi(u.y);
                        sacc[4] += bf_lo(u.z); sacc[5] += bf_hi(u.z); sacc[6] += bf_lo(u.w); sacc[7] += bf_hi(u.w);
                    }
                }
#pragma unroll
                for (int c = 0; c < 8; c++) sacc[c] += __shfl_xor_sync(0xffffffffu, sacc[c], 1);
                if (pc < npanels * 8) {
                    float4* dst = reinterpret_cast<float4*>(colpart + (grp * 16 + rb) * 320 + pc * 8) + half;
                    *dst = half ? make_float4(xch_enc(sacc[4]), xch_enc(sacc[5]), xch_enc(sacc[6]), xch_enc(sacc[7]))
                                : make_float4(xch_enc(sacc[0]), xch_enc(sacc[1]), xch_enc(sacc[2]), xch_enc(sacc[3]));
                }
                named_bar_sync(4, 96);
                if (ht < 2) mbar_arrive_remote(bar_empty + 8 * cstage, ht);
            }
            if (ht == 0) DEV_STAMP(0, 6);
            for (int c2 = ht; c2 < npanels * 32; c2 += 96) {
                int type, col; k1_panel(grp, c2 >> 5, type, col);
                uint32_t bb = 0;
                if (type == 1) bb = __ldg(reinterpret_cast<const uint32_t*>(b1 + col) + (c2 & 31));
                uint2 pv[16];
                bool okv = false;
#pragma unroll 1
                for (uint32_t n = 0; n < (1u << 14) && !okv; n++) {
                    okv = true;
#pragma unroll
                    for (int k = 0; k < 16; k++) pv[k] = ld_relaxed_v2(colpart + (grp * 16 + k) * 320 + c2 * 2);
#pragma unroll
                    for (int k = 0; k < 16; k++) okv = okv && pv[k].x != NOT_READY && pv[k].y != NOT_READY;
                }
                float s0 = 0.f, s1 = 0.f;
#pragma unroll
                for (int k = 0; k < 16; k++) { s0 += xch_dec(pv[k].x); s1 += xch_dec(pv[k].y); }
                asm volatile("st.shared.v4.f32 [%0], {%1,%2,%3,%4};" ::"r"(sCol + c2 * 16), "f"(s0), "f"(bf_lo(bb)), "f"(s1), "f"(bf_hi(bb)) : "memory");
            }
            mbar_arrive(bar_col);
            if (ht == 0) DEV_STAMP(0, 7);
        }
    } else {
        reg_alloc<208>();
        const int wg = warp >> 2;
        const int g = lane >> 2, t = lane & 3;
        const int wrow = (warp & 3) * 16;
        {
            float f[2][16], sum[2], sq[2];
#pragma unroll
            for (int r = 0; r < 2; r++) {
                const uint32_t w[8] = {v[r][0].x, v[r][0].y, v[r][0].z, v[r][0].w, v[r][1].x, v[r][1].y, v[r][1].z, v[r][1].w};
#pragma unroll
                for (int i = 0; i < 8; i++) { f[r][2 * i] = bf_lo(w[i]); f[r][2 * i + 1] = bf_hi(w[i]); }
                sum[r] = 0.f;
#pragma unroll
                for (int i = 0; i < 16; i++) sum[r] += f[r][i];
            }
#pragma unroll
            for (int o = 16; o > 0; o >>= 1) { sum[0] += __shfl_xor_sync(0xffffffffu, sum[0], o); sum[1] += __shfl_xor_sync(0xffffffffu, sum[1], o); }
#pragma unroll
            for (int r = 0; r < 2; r++) {
                sum[r] *= (1.0f / D_MODEL);
                sq[r] = 0.f;
#pragma unroll
                for (int i = 0; i < 16; i++) { const float d = f[r][i] - sum[r]; sq[r] += d * d; }
            }
#pragma unroll
            for (int o = 16; o > 0; o >>= 1) { sq[0] += __shfl_xor_sync(0xffffffffu, sq[0], o); sq[1] += __shfl_xor_sync(0xffffffffu, sq[1], o); }
            if (lane < 2) {
                const float rstd = rsqrtf((lane ? sq[1] : sq[0]) * (1.0f / D_MODEL) + 1e-5f);
                rowstat[rb * 128 + grp * 16 + warp * 2 + lane] = make_float2(xch_enc(rstd), (lane ? sum[1] : sum[0]) * rstd);
            }
            if (tid == 0) DEV_STAMP(0, 5);
        }
        float acc[160];
#pragma unroll
        for (int i = 0; i < 160; i++) acc[i] = 0.f;
        float2 rs0, rs1;
        const uint64_t dA0 = make_desc(sbase + wg * 8192, 16, 1024, 1);
        const uint64_t dB0 = make_desc(sbase + 16384, K1_PANEL_BYTES, 1024, 1);
#define K1_MAINLOOP(FIVE)                                                                                          \
        for (int ks = 0; ks < 8; ks++) {                                                                           \
            const int s = ks % K1_STAGES;                                                                          \
            mbar_wait(bar_full + 8 * s, (ks / K1_STAGES) & 1);                                                     \
            if (ks == 0 && tid == 0) DEV_STAMP(0, 1);                                                              \
            wg_fence();                                                                                            \
            _Pragma("unroll") for (int kk = 0; kk < 4; kk++) {                                                     \
                const uint64_t dA = dA0 + (uint64_t)((s * K1_STAGE_BYTES + kk * 32) >> 4);                         \
                const uint64_t dB = dB0 + (uint64_t)((s * K1_STAGE_BYTES + kk * 2048) >> 4);                       \
                wgmma_ss_n256_tb(acc, dA, dB, (ks | kk) != 0);                                                     \
                if (FIVE) wgmma_ss_n64_tb(acc + 128, dA, dB + (uint64_t)((4 * K1_PANEL_BYTES) >> 4), (ks | kk) != 0); \
            }                                                                                                      \
            wg_commit();                                                                                           \
            if (ks == 7) {                                                                                         \
                uint2 r0, r1;                                                                                      \
                uint32_t n = 0;                                                                                    \
                _Pragma("unroll 1") do {                                                                           \
                    r0 = ld_relaxed_v2(rowstat + rb * 128 + wg * 64 + wrow + g);                                   \
                    r1 = ld_relaxed_v2(rowstat + rb * 128 + wg * 64 + wrow + g + 8);                               \
                } while ((r0.x == NOT_READY || r1.x == NOT_READY) && ++n < (1u << 14));                            \
                rs0 = make_float2(xch_dec(r0.x), __uint_as_float(r0.y));                                           \
                rs1 = make_float2(xch_dec(r1.x), __uint_as_float(r1.y));                                           \
                mbar_wait(bar_col, 0);                                                                             \
            }                                                                                                      \
            if (ks > 0 && ks <= 4) {                                                                               \
                wg_wait<1>();                                                                                      \
                if (lane < 2) mbar_arrive_remote(bar_empty + 8 * ((ks - 1) % K1_STAGES), lane);                    \
            }                                                                                                      \
        }                                                                                                          \
        wg_wait<0>();
        const int srow = (lane & 7) + ((lane >> 3) & 1) * 8;
        if (npanels == 5) { K1_MAINLOOP(true) } else { K1_MAINLOOP(false) }
        fence_regs<160>(acc);
        if (tid == 0) DEV_STAMP(0, 2);
        named_bar_sync(1, 256);
#pragma unroll
        for (int p = 0; p < 5; p++) {
            if (p < npanels) {
                int type, col; k1_panel(grp, p, type, col);
                float* a = acc + p * 32;
                const int nj = type <= 1 ? 8 : 2;
                const float sc = type == 0 ? Q_SCALE : 1.0f;
                const float r0x = rs0.x * sc, r0y = -rs0.y * sc, r1x = rs1.x * sc, r1y = -rs1.y * sc;
#pragma unroll
                for (int j = 0; j < 8; j++) {
                    if (j < nj) {
                        float4 c;
                        asm volatile("ld.shared.v4.f32 {%0,%1,%2,%3}, [%4];" : "=f"(c.x), "=f"(c.y), "=f"(c.z), "=f"(c.w)
                                     : "r"(sCol + (p * 64 + j * 8 + 2 * t) * 8));
                        a[4 * j] = fmaf(a[4 * j], r0x, fmaf(r0y, c.x, c.y));
                        a[4 * j + 1] = fmaf(a[4 * j + 1], r0x, fmaf(r0y, c.z, c.w));
                        a[4 * j + 2] = fmaf(a[4 * j + 2], r1x, fmaf(r1y, c.x, c.y));
                        a[4 * j + 3] = fmaf(a[4 * j + 3], r1x, fmaf(r1y, c.z, c.w));
                    }
                }
                if (type <= 1) {
                    const uint32_t stg = sbase + (p * 8 + warp) * 2048;
                    uint32_t pk[16];
                    if (type == 0) {
#pragma unroll
                        for (int j = 0; j < 8; j++) {
                            pk[2 * j] = pack_bf16(a[4 * j], a[4 * j + 1]);
                            pk[2 * j + 1] = pack_bf16(a[4 * j + 2], a[4 * j + 3]);
                        }
                    } else {
#pragma unroll
                        for (int j = 0; j < 8; j++) {
                            const uint32_t h0 = pack_bf16_relu(a[4 * j], a[4 * j + 1]), h1 = pack_bf16_relu(a[4 * j + 2], a[4 * j + 3]);
                            pk[2 * j] = mul_bf16x2(h0, h0);
                            pk[2 * j + 1] = mul_bf16x2(h1, h1);
                        }
                    }
#pragma unroll
                    for (int j = 0; j < 8; j += 2) {
                        const int c16 = j + (lane >> 4);
                        stmatrix_x4(stg + srow * 128 + ((c16 ^ (srow & 7)) << 4), pk[2 * j], pk[2 * j + 1], pk[2 * j + 2], pk[2 * j + 3]);
                    }
                    fence_proxy_async();
                    __syncwarp();
                    if (lane == 0) {
                        tma_store_2d(type == 0 ? &tm_qo : &tm_ho, stg, col, rb * 128 + warp * 16);
                        tma_store_commit();
                    }
                } else if (type == 3) {
                    const int r = wg * 64 + wrow + g;
                    const int pos0 = (r >> 2) * 64 + rb * 4 + (r & 3), pos1 = pos0 + 128;
                    uint32_t* dst = reinterpret_cast<uint32_t*>(kv);
                    const uint32_t r00 = pack_bf16(a[0], a[1]), r01 = pack_bf16(a[4], a[5]);
                    const uint32_t r10 = pack_bf16(a[2], a[3]), r11 = pack_bf16(a[6], a[7]);
                    dst[(pos0 >> 4) * 128 + (pos0 & 15) * 4 + t] = r00;
                    dst[16384 + pos0 * 4 + t] = r01;
                    dst[(pos1 >> 4) * 128 + (pos1 & 15) * 4 + t] = r10;
                    dst[16384 + pos1 * 4 + t] = r11;
                    float m = fmaxf(fmaxf(fmaxf(fabsf(bf_lo(r00)), fabsf(bf_hi(r00))), fmaxf(fabsf(bf_lo(r01)), fabsf(bf_hi(r01)))),
                                    fmaxf(fmaxf(fabsf(bf_lo(r10)), fabsf(bf_hi(r10))), fmaxf(fabsf(bf_lo(r11)), fabsf(bf_hi(r11)))));
#pragma unroll
                    for (int o = 16; o > 0; o >>= 1) m = fmaxf(m, __shfl_xor_sync(0xffffffffu, m, o));
                    if (lane == 0) kvmax[128 + rb * 8 + warp] = m;
                } else {
                    float* kf = reinterpret_cast<float*>(smem_raw + 96 * 1024);
                    const int r = wg * 64 + wrow + g;
                    const int pos0 = (r >> 2) * 64 + rb * 4 + (r & 3), pos1 = pos0 + 128;
                    uint32_t* dst = reinterpret_cast<uint32_t*>(kv) + 32768;
                    dst[(pos0 >> 3) * 64 + (pos0 & 7) * 4 + t] = pack_bf16(a[0], a[1]);
                    dst[(pos0 >> 3) * 64 + 32 + (pos0 & 7) * 4 + t] = pack_bf16(a[4], a[5]);
                    dst[(pos1 >> 3) * 64 + (pos1 & 7) * 4 + t] = pack_bf16(a[2], a[3]);
                    dst[(pos1 >> 3) * 64 + 32 + (pos1 & 7) * 4 + t] = pack_bf16(a[6], a[7]);
                    kf[r * 17 + 2 * t] = a[0]; kf[r * 17 + 2 * t + 1] = a[1];
                    kf[r * 17 + 8 + 2 * t] = a[4]; kf[r * 17 + 8 + 2 * t + 1] = a[5];
                    kf[(r + 8) * 17 + 2 * t] = a[2]; kf[(r + 8) * 17 + 2 * t + 1] = a[3];
                    kf[(r + 8) * 17 + 8 + 2 * t] = a[6]; kf[(r + 8) * 17 + 8 + 2 * t + 1] = a[7];
                    named_bar_sync(1, 256);
                    if (tid < 64) {
                        const int i = tid >> 4, dim = tid & 15;
                        const int c = rb * 4 + i;
                        const int inner = (dim >> 3) * 64 + (c & 7) * 8 + (dim & 7);
                        float kt = 0.f;
#pragma unroll 8
                        for (int j = 0; j < 32; j++) {
                            const __nv_bfloat16 d = __float2bfloat16_rn(kf[(j * 4 + i) * 17 + dim] - kt);
                            kt += __bfloat162float(d);
                            kf[(j * 4 + i) * 17 + dim] = kt;
                            const int grp8 = j * 8 + (c >> 3);
                            kv[(grp8 < 128 ? grp8 * 256 + 128 : 49152 + (grp8 - 128) * 128) + inner] = d;
                        }
                    }
                    named_bar_sync(1, 256);
                    if (tid < 128) {
                        float n = 0.f;
#pragma unroll
                        for (int d = 0; d < 16; d++) { const float v = kf[tid * 17 + d]; n += v * v; }
                        if (!(n == n)) n = __int_as_float(0x7f800000);
#pragma unroll
                        for (int o = 8; o > 0; o >>= 1) n = fmaxf(n, __shfl_xor_sync(0xffffffffu, n, o));
                        if ((lane & 15) == 0) kvmax[rb * 8 + (tid >> 4)] = n;
                    }
                }
            }
        }
        if (tid == 0) DEV_STAMP(0, 3);
        if (lane == 0) tma_store_wait();
        if (tid == 0) DEV_STAMP(0, 4);
    }
}

#define K2_MINI 1
constexpr int AT_KT = 64;
constexpr int AT_NCHUNK = 8;
constexpr int AT_NSTEP = S_LEN / AT_KT;
constexpr int AT_SPC = AT_NSTEP / AT_NCHUNK;
constexpr int AT_ONES = 131072;
constexpr int F2_STAGES = 4;
constexpr int F2_STAGE_BYTES = 8192 + 16384;
constexpr int F2_BASE = 132096;
constexpr int F2_NK = F_DIM / 64;
constexpr int AT_BAR = F2_BASE + F2_STAGES * F2_STAGE_BYTES;
constexpr int AT_SMEM = AT_BAR + 256;
#define AT_SWMASK_V 0xB6DB
constexpr uint32_t AT_SWMASK = AT_SWMASK_V;

#define AT_MAGIC (383.0f + 0.00390625f - 0.5849625f)
__device__ __forceinline__ uint32_t exp2_pair_alu(float t0, float t1) {
    uint32_t y;
    asm("prmt.b32 %0, %1, %2, 0x6521;" : "=r"(y) : "f"(t0), "f"(t1));
    const uint32_t e = y & 0x7F807F80u;
    uint32_t uh, p;
    asm("lop3.b32 %0, %1, %2, 0x3F003F00, 0xBE;" : "=r"(uh) : "r"(y), "r"(e));
    asm("fma.rn.bf16x2 %0, %1, %2, %3;" : "=r"(p) : "r"(uh), "r"(y), "r"(e));
    return p;
}

__device__ __forceinline__ void at_load_chunk(uint32_t sbase, const __nv_bfloat16* KV, uint32_t bar0, int c) {
    const uint8_t* src = reinterpret_cast<const uint8_t*>(KV);
    const uint32_t off = c < 4 ? c * 16384 : 98304 + (c - 4) * 8192, bytes = c < 4 ? 16384 : 8192;
    mbar_expect_tx(bar0 + 8 * c, bytes + 4096);
    bulk_g2s(sbase + off, src + off, bytes, bar0 + 8 * c);
    bulk_g2s(sbase + 65536 + c * 4096, src + 65536 + c * 4096, 4096, bar0 + 8 * c);
}

__device__ __forceinline__ void at_store(const float* o, __nv_bfloat16* O, int row, int lane) {
    const float l0 = __shfl_sync(0xffffffffu, o[8], lane & ~3);
    const float l1 = __shfl_sync(0xffffffffu, o[10], lane & ~3);
    const float r0 = __fdividef(1.0f, l0), r1 = __fdividef(1.0f, l1);
    const int t = lane & 3;
    uint32_t* op = reinterpret_cast<uint32_t*>(O + (size_t)(row + (lane >> 2)) * 16);
    op[t] = pack_bf16(o[0] * r0, o[1] * r0);
    op[t + 4] = pack_bf16(o[4] * r0, o[5] * r0);
    op[64 + t] = pack_bf16(o[2] * r1, o[3] * r1);
    op[64 + t + 4] = pack_bf16(o[6] * r1, o[7] * r1);
}

__device__ __forceinline__ void mma16816(float* c, const uint32_t* a, uint32_t b0, uint32_t b1) {
    asm volatile("mma.sync.aligned.m16n8k16.row.col.f32.bf16.bf16.f32 {%0,%1,%2,%3}, {%4,%5,%6,%7}, {%8,%9}, {%0,%1,%2,%3};"
                 : "+f"(c[0]), "+f"(c[1]), "+f"(c[2]), "+f"(c[3]) : "r"(a[0]), "r"(a[1]), "r"(a[2]), "r"(a[3]), "r"(b0), "r"(b1));
}
__device__ __forceinline__ void attn_fallback(const __nv_bfloat16* Q, const __nv_bfloat16* KV, __nv_bfloat16* O, uint32_t sbase) {
    const int tid = threadIdx.x;
    const int lane = tid & 31, g = lane >> 2, t = lane & 3;
    const uint32_t* Kg = reinterpret_cast<const uint32_t*>(KV + 65536);
#pragma unroll 1
    for (int mt = 0; mt < 2; mt++) {
        const int row = blockIdx.x * 512 + (tid >> 7) * 128 + mt * 64 + ((tid >> 5) & 3) * 16;
        const uint32_t* qp = reinterpret_cast<const uint32_t*>(Q + (size_t)(row + g) * 16);
        const uint32_t q[4] = {qp[t], qp[64 + t], qp[t + 4], qp[64 + t + 4]};
        float o[12];
#pragma unroll
        for (int i = 0; i < 12; i++) o[i] = 0.f;
        float m0 = -INFINITY, m1 = -INFINITY;
#pragma unroll 1
        for (int kt = 0; kt < S_LEN / 16; kt++) {
            float s[8];
#pragma unroll
            for (int i = 0; i < 8; i++) s[i] = 0.f;
#pragma unroll
            for (int h = 0; h < 2; h++) {
                const uint32_t* kp = Kg + (kt * 2 + h) * 64 + g * 4 + t;
                mma16816(s + 4 * h, q, kp[0], kp[32]);
            }
            float x0 = fmaxf(fmaxf(s[0], s[1]), fmaxf(s[4], s[5])), x1 = fmaxf(fmaxf(s[2], s[3]), fmaxf(s[6], s[7]));
            x0 = fmaxf(x0, __shfl_xor_sync(0xffffffffu, x0, 1)); x0 = fmaxf(x0, __shfl_xor_sync(0xffffffffu, x0, 2));
            x1 = fmaxf(x1, __shfl_xor_sync(0xffffffffu, x1, 1)); x1 = fmaxf(x1, __shfl_xor_sync(0xffffffffu, x1, 2));
            x0 = fmaxf(x0, m0); x1 = fmaxf(x1, m1);
            const float f0 = ex2(m0 - x0), f1 = ex2(m1 - x1);
            m0 = x0; m1 = x1;
#pragma unroll
            for (int j = 0; j < 3; j++) { o[4 * j] *= f0; o[4 * j + 1] *= f0; o[4 * j + 2] *= f1; o[4 * j + 3] *= f1; }
            const uint32_t p[4] = {pack_bf16(ex2(s[0] - m0), ex2(s[1] - m0)), pack_bf16(ex2(s[2] - m1), ex2(s[3] - m1)),
                                   pack_bf16(ex2(s[4] - m0), ex2(s[5] - m0)), pack_bf16(ex2(s[6] - m1), ex2(s[7] - m1))};
#pragma unroll
            for (int j = 0; j < 3; j++) {
                const uint32_t base = sbase + (j == 0 ? kt * 512 : j == 1 ? 65536 + kt * 256 : AT_ONES) + (lane & 15) * 16;
                uint32_t b0, b1;
                asm volatile("ldmatrix.sync.aligned.m8n8.x2.trans.shared.b16 {%0,%1}, [%2];" : "=r"(b0), "=r"(b1) : "r"(base));
                mma16816(o + 4 * j, p, b0, b1);
            }
        }
        at_store(o, O, row, lane);
    }
}

__global__ void __launch_bounds__(640, 1)
k2_attn(const __grid_constant__ CUtensorMap tm_h, const __grid_constant__ CUtensorMap tm_w2,
        const __nv_bfloat16* __restrict__ Q, const __nv_bfloat16* __restrict__ KV, const float* __restrict__ kvmax,
        const __nv_bfloat16* __restrict__ b2, __nv_bfloat16* __restrict__ O, __nv_bfloat16* __restrict__ G,
        uint2* __restrict__ rowstat, uint2* __restrict__ colpart) {
    extern __shared__ __align__(1024) uint8_t smem_raw[];
    const uint32_t sbase = smem_u32(smem_raw);
    const uint32_t bar0 = sbase + AT_BAR, f2_full = bar0 + 64, f2_empty = f2_full + 32, bar_guard = f2_empty + 32, bar_first = bar_guard + 8, sGuard = bar0 + 192;
    const int tid = threadIdx.x;
    const int wg = __shfl_sync(0xffffffffu, tid >> 7, 0);
    const int warp = (tid >> 5) & 3, lane = tid & 31;
    const int g = lane >> 2, t = lane & 3;
    if (tid == 0) DEV_STAMP(1, 0);
    if (tid == 0) {
        for (int i = 0; i < AT_NCHUNK; i++) mbar_init(bar0 + 8 * i, 1);
        for (int i = 0; i < F2_STAGES; i++) { mbar_init(f2_full + 8 * i, 1); mbar_init(f2_empty + 8 * i, 4); }
        mbar_init(bar_guard, 4);
        mbar_init(bar_first, 1);
        mbar_init_fence();
    }
    if (tid < 16) asm volatile("st.shared.v4.b32 [%0], {%1,%2,%2,%2};" ::"r"(sbase + AT_ONES + tid * 16), "r"(0x00003F80u), "r"(0u) : "memory");
    fence_proxy_async();
    __syncthreads();

    if (wg == 4) {
        const int rb = blockIdx.x >> 2, cb = blockIdx.x & 3;
        const uint32_t fb = sbase + F2_BASE;
        const bool leader = tid == 512;
        if (leader) {
#pragma unroll
            for (int s = 0; s < F2_STAGES; s++) {
                mbar_expect_tx(f2_full + 8 * s, F2_STAGE_BYTES);
                tma_load_2d(fb + s * F2_STAGE_BYTES + 8192, &tm_w2, cb * 128, s * 64, f2_full + 8 * s);
                tma_load_2d(fb + s * F2_STAGE_BYTES + 16384, &tm_w2, cb * 128 + 64, s * 64, f2_full + 8 * s);
            }
        }
        pdl_wait();
        mbar_wait(bar0, 0);
        if (leader) {
#pragma unroll
            for (int s = 0; s < F2_STAGES; s++) tma_load_2d(fb + s * F2_STAGE_BYTES, &tm_h, s * 64, rb * 64, f2_full + 8 * s);
        }
        {
            float km = fmaxf(fmaxf(kvmax[lane], kvmax[lane + 32]), fmaxf(kvmax[lane + 64], kvmax[lane + 96]));
            float vm = fmaxf(fmaxf(kvmax[128 + lane], kvmax[160 + lane]), fmaxf(kvmax[192 + lane], kvmax[224 + lane]));
            uint4 qv[4][2];
#pragma unroll
            for (int i = 0; i < 4; i++) {
                const uint4* qr = reinterpret_cast<const uint4*>(Q + (size_t)(blockIdx.x * 512 + warp * 128 + i * 16 + (lane >> 4) * 64 + (lane & 15)) * 16);
                qv[i][0] = qr[0]; qv[i][1] = qr[1];
            }
#pragma unroll
            for (int o = 16; o > 0; o >>= 1) { km = fmaxf(km, __shfl_xor_sync(0xffffffffu, km, o)); vm = fmaxf(vm, __shfl_xor_sync(0xffffffffu, vm, o)); }
#pragma unroll
            for (int i = 0; i < 4; i++) {
                const uint32_t qw[8] = {qv[i][0].x, qv[i][0].y, qv[i][0].z, qv[i][0].w, qv[i][1].x, qv[i][1].y, qv[i][1].z, qv[i][1].w};
                float qn = 0.f;
#pragma unroll
                for (int j = 0; j < 8; j++) qn += bf_lo(qw[j]) * bf_lo(qw[j]) + bf_hi(qw[j]) * bf_hi(qw[j]);
                const bool ok = (qn * km <= 3600.0f) && (vm <= 1.0e12f);
                const uint32_t bad = __any_sync(0xffffffffu, !ok);
                if (lane == 0) asm volatile("st.shared.u32 [%0], %1;" ::"r"(sGuard + (warp * 4 + i) * 4), "r"(bad) : "memory");
            }
            if (lane == 0) mbar_arrive(bar_guard);
        }
        __syncwarp();
        const uint64_t dA0 = make_desc(fb, 16, 1024, 1);
        const uint64_t dB0 = make_desc(fb + 8192, 8192, 1024, 1);
        float acc[64];
#pragma unroll
        for (int i = 0; i < 64; i++) asm volatile("mov.f32 %0, 0f00000000;" : "=f"(acc[i]));
#pragma unroll 1
        for (int ks = 0; ks < F2_NK; ks++) {
            const int s = ks % F2_STAGES;
            mbar_wait(f2_full + 8 * s, (ks / F2_STAGES) & 1);
            wg_fence();
#pragma unroll
            for (int kk = 0; kk < 4; kk++)
                wgmma_ss_n128_tb(acc, dA0 + (uint64_t)((s * F2_STAGE_BYTES + kk * 32) >> 4),
                                 dB0 + (uint64_t)((s * F2_STAGE_BYTES + kk * 2048) >> 4), 1);
            wg_commit();
            wg_wait<1>();
            if (ks > 0 && ks - 1 + F2_STAGES < F2_NK) {
                const int ps = (ks - 1) % F2_STAGES, k0 = (ks - 1 + F2_STAGES) * 64;
                if (lane == 0) mbar_arrive(f2_empty + 8 * ps);
                if (leader) {
                    mbar_wait(f2_empty + 8 * ps, ((ks - 1) / F2_STAGES) & 1);
                    mbar_expect_tx(f2_full + 8 * ps, F2_STAGE_BYTES);
                    tma_load_2d(fb + ps * F2_STAGE_BYTES, &tm_h, k0, rb * 64, f2_full + 8 * ps);
                    tma_load_2d(fb + ps * F2_STAGE_BYTES + 8192, &tm_w2, cb * 128, k0, f2_full + 8 * ps);
                    tma_load_2d(fb + ps * F2_STAGE_BYTES + 16384, &tm_w2, cb * 128 + 64, k0, f2_full + 8 * ps);
                }
                __syncwarp();
            }
        }
        wg_wait<0>();
        fence_regs<64>(acc);
        uint32_t* gp = reinterpret_cast<uint32_t*>(G + (size_t)(rb * 64 + warp * 16 + g) * D_MODEL + cb * 128) + t;
#pragma unroll
        for (int j = 0; j < 16; j++) {
            const uint32_t bb = __ldg(reinterpret_cast<const uint32_t*>(b2 + cb * 128 + j * 8) + t);
            const float b0 = bf_lo(bb), b1v = bf_hi(bb);
            const float z0 = acc[4 * j] + b0, z1 = acc[4 * j + 1] + b1v, z2 = acc[4 * j + 2] + b0, z3 = acc[4 * j + 3] + b1v;
            gp[j * 4] = pack_bf16(__fdividef(z0, 1.0f + __expf(-z0)), __fdividef(z1, 1.0f + __expf(-z1)));
            gp[j * 4 + 8 * (D_MODEL / 2)] = pack_bf16(__fdividef(z2, 1.0f + __expf(-z2)), __fdividef(z3, 1.0f + __expf(-z3)));
        }
        if (leader) DEV_STAMP(1, 5);
        return;
    }

    pdl_wait();
    pdl_launch();
    if (tid == 0) DEV_STAMP(1, 1);
    if (tid == 0) {
        const uint8_t* src = reinterpret_cast<const uint8_t*>(KV);
        mbar_expect_tx(bar_first, 4096);
        bulk_g2s(sbase, src, 4096, bar_first);
        mbar_expect_tx(bar0, 12288 + 4096);
        bulk_g2s(sbase + 4096, src + 4096, 12288, bar0);
        bulk_g2s(sbase + 65536, src + 65536, 4096, bar0);
        at_load_chunk(sbase, KV, bar0, 1); at_load_chunk(sbase, KV, bar0, 2);
    }
    if (tid >= 128 && tid < 288) colpart[blockIdx.x * 160 + tid - 128] = make_uint2(NOT_READY, NOT_READY);
    if (tid >= 288 && tid < 304) rowstat[blockIdx.x * 16 + tid - 288] = make_uint2(NOT_READY, NOT_READY);
    const int rowA = blockIdx.x * 512 + wg * 128 + warp * 16;
    const uint32_t* qp = reinterpret_cast<const uint32_t*>(Q + (size_t)(rowA + g) * 16);
    const uint32_t lo0 = ((sbase & 0x3FFFF) >> 4) | (8u << 16);

#define AT_EXP(P) _Pragma("unroll") for (int i = 0; i < AT_KT / 4; i++) {                       \
                if ((AT_SWMASK >> (i & 15)) & 1) P[i] = exp2_pair_alu(s[2 * i], s[2 * i + 1]);  \
                else P[i] = pack_bf16(ex2(s[2 * i]), ex2(s[2 * i + 1])); }
#define AT_PV(P, st) _Pragma("unroll") for (int j = 0; j < AT_KT / 16; j++)                     \
                wgmma_pv(o, P[4 * j], P[4 * j + 1], P[4 * j + 2], P[4 * j + 3],                 \
                         desc64(vlo + ((st) * 4 + j) * 32, vhi - ((st) * 4 + j) * 16));
#define AT_PIPE 2
#define AT_EXPH(P, h) _Pragma("unroll") for (int i = (h) * 8; i < (h) * 8 + 8; i++) {           \
                if ((AT_SWMASK >> (i & 15)) & 1) P[i] = exp2_pair_alu(s[2 * i], s[2 * i + 1]);  \
                else P[i] = pack_bf16(ex2(s[2 * i]), ex2(s[2 * i + 1])); }
#define AT_PVH(P, st, h) _Pragma("unroll") for (int j = (h) * 2; j < (h) * 2 + 2; j++)          \
                wgmma_pv(o, P[4 * j], P[4 * j + 1], P[4 * j + 2], P[4 * j + 3],                 \
                         desc64(vlo + ((st) * 4 + j) * 32, vhi - ((st) * 4 + j) * 16));
#define AT_STEP(st, PC, PN, klo, khi) {                                                         \
                wg_wait<0>();                                                                   \
                fence_regs<AT_KT / 2>(s);                                                       \
                AT_EXPH(p0, 0);                                                                 \
                wg_fence();                                                                     \
                AT_PVH(p0, st, 0);                                                              \
                wg_commit();                                                                    \
                AT_EXPH(p0, 1);                                                                 \
                if (st == AT_SPC - 1 && mt == 0) mbar_wait(bar0 + 8 * (c + 1), 0);              \
                wg_wait<0>();                                                                   \
                wg_fence();                                                                     \
                wgmma_qk_acc_n64(s, q, desc64(klo, khi));                                       \
                AT_PVH(p0, st, 1);                                                              \
                wg_commit(); }

#pragma unroll 1
    for (int mt = 0; mt < 2; mt++) {
        uint32_t q[4];
        q[0] = qp[mt * 512 + t]; q[2] = qp[mt * 512 + t + 4]; q[1] = qp[mt * 512 + 64 + t]; q[3] = qp[mt * 512 + 64 + t + 4];
        float o[12];
#pragma unroll
        for (int i = 0; i < 12; i++) asm volatile("mov.f32 %0, 0f00000000;" : "=f"(o[i]));
        float s[AT_KT / 2];
        uint32_t p0[AT_KT / 4], p1[AT_KT / 4];
        (void)p1;
#pragma unroll
        for (int i = 0; i < AT_KT / 2; i++) {
            if ((AT_SWMASK >> ((i >> 1) & 15)) & 1) asm volatile("mov.f32 %0, %1;" : "=f"(s[i]) : "f"(AT_MAGIC));
            else asm volatile("mov.f32 %0, 0f00000000;" : "=f"(s[i]));
        }
        if (mt == 0) mbar_wait(K2_MINI ? bar_first : bar0, 0);
        if (tid == 0) DEV_STAMP(1, 2 + mt);
        uint32_t klo = lo0 + 16, vlo = lo0, vhi = 4096;
        wg_fence();
        wgmma_qk_acc_n64(s, q, desc64(klo, 32));
        wg_commit();
        if (K2_MINI && mt == 0) mbar_wait(bar0, 0);
        uint32_t kst = 256, khi = 32;
#pragma unroll 1
        for (int c = 0; c < AT_NCHUNK - 1; c++) {
            if (tid == 0 && mt == 0 && c + 3 < AT_NCHUNK) at_load_chunk(sbase, KV, bar0, c + 3);
            AT_STEP(0, p0, p1, klo + kst, khi); AT_STEP(1, p1, p0, klo + 2 * kst, khi); AT_STEP(2, p0, p1, klo + 3 * kst, khi);
            if (c == 3) { klo = lo0 + (98304 >> 4); kst = 128; khi = 16; } else klo += 4 * kst;
            AT_STEP(3, p1, p0, klo, khi);
            vlo += 512; vhi -= 256;
        }
        {
            const int c = 0; (void)c;
            AT_STEP(0, p0, p1, klo + 128, 16); AT_STEP(1, p1, p0, klo + 256, 16); AT_STEP(2, p0, p1, klo + 384, 16);
            wg_wait<0>();
            fence_regs<AT_KT / 2>(s);
            AT_EXP(p0);
            wg_fence();
            AT_PV(p0, 3);
            wg_commit();
            wg_wait<0>();
            fence_regs<12>(o);
        }
        at_store(o, O, rowA + mt * 64, lane);
    }
    if (tid == 0) DEV_STAMP(1, 4);

    mbar_wait(bar_guard, 0);
    uint32_t bad;
    asm volatile("ld.shared.u32 %0, [%1];" : "=r"(bad) : "r"(sGuard + (tid >> 5) * 4) : "memory");
    if (__any_sync(0xffffffffu, bad != 0) == 0) return;
    attn_fallback(Q, KV, O, sbase);
}

constexpr int K3_STAGE_BYTES = 16384 + 8192;
constexpr int K3_X = 8 * K3_STAGE_BYTES;
constexpr int K3_G = K3_X + 16384;
constexpr int K3_SMEM = K3_G + 16384 + 256;

__global__ void __launch_bounds__(256, 1)
k3_out(const __grid_constant__ CUtensorMap tm_o, const __grid_constant__ CUtensorMap tm_wo,
       const __grid_constant__ CUtensorMap tm_x, const __grid_constant__ CUtensorMap tm_g,
       const __grid_constant__ CUtensorMap tm_out) {
    extern __shared__ __align__(1024) uint8_t smem_raw[];
    const uint32_t sbase = smem_u32(smem_raw);
    const uint32_t sX = sbase + K3_X, sG = sbase + K3_G;
    const uint32_t bar_full = sG + 16384, bar_x = bar_full + 64;
    const int tid = threadIdx.x, warp = __shfl_sync(0xffffffffu, tid >> 5, 0), lane = tid & 31;
    const int rb = blockIdx.x >> 3, cb = blockIdx.x & 7;
    if (tid == 0) {
        DEV_STAMP(2, 0);
        for (int s = 0; s < 8; s++) mbar_init(bar_full + 8 * s, 1);
        mbar_init(bar_x, 1);
        mbar_init_fence();
        for (int s = 0; s < 8; s++) {
            mbar_expect_tx(bar_full + 8 * s, K3_STAGE_BYTES);
            tma_load_2d(sbase + s * K3_STAGE_BYTES + 16384, &tm_wo, cb * 64, s * 64, bar_full + 8 * s);
        }
        mbar_expect_tx(bar_x, 32768);
        tma_load_2d(sX, &tm_x, cb * 64, rb * 128, bar_x);
        pdl_wait();
        DEV_STAMP(2, 1);
        for (int s = 0; s < 8; s++) tma_load_2d(sbase + s * K3_STAGE_BYTES, &tm_o, s * 64, rb * 128, bar_full + 8 * s);
        tma_load_2d(sG, &tm_g, cb * 64, rb * 128, bar_x);
    }
    __syncthreads();
    const int wg = warp >> 2;
    float acc[32];
#pragma unroll
    for (int i = 0; i < 32; i++) asm volatile("mov.f32 %0, 0f00000000;" : "=f"(acc[i]));
    const uint64_t dA0 = make_desc(sbase + wg * 8192, 16, 1024, 1);
    const uint64_t dB0 = make_desc(sbase + 16384, 8192, 1024, 1);
#pragma unroll 1
    for (int ks = 0; ks < 8; ks++) {
        mbar_wait(bar_full + 8 * ks, 0);
        wg_fence();
#pragma unroll
        for (int kk = 0; kk < 4; kk++)
            wgmma_ss_n64_tb(acc, dA0 + (uint64_t)((ks * K3_STAGE_BYTES + kk * 32) >> 4),
                            dB0 + (uint64_t)((ks * K3_STAGE_BYTES + kk * 2048) >> 4), 1);
        wg_commit();
    }
    wg_wait<0>();
    fence_regs<32>(acc);
    if (tid == 0) DEV_STAMP(2, 2);
    mbar_wait(bar_x, 0);
    const int g = lane >> 2, t = lane & 3;
    const int row0 = warp * 16 + g;
#pragma unroll
    for (int j = 0; j < 8; j++) {
#pragma unroll
        for (int h = 0; h < 2; h++) {
            const int row = row0 + h * 8;
            const uint32_t off = row * 128 + ((j ^ (row & 7)) << 4) + t * 4;
            uint32_t xv, gv;
            asm volatile("ld.shared.b32 %0, [%1];" : "=r"(xv) : "r"(sX + off) : "memory");
            asm volatile("ld.shared.b32 %0, [%1];" : "=r"(gv) : "r"(sG + off) : "memory");
            const uint32_t ov = pack_bf16(fmaf(acc[4 * j + 2 * h], bf_lo(gv), bf_lo(xv)), fmaf(acc[4 * j + 2 * h + 1], bf_hi(gv), bf_hi(xv)));
            asm volatile("st.shared.b32 [%0], %1;" ::"r"(sX + off), "r"(ov) : "memory");
        }
    }
    fence_proxy_async();
    __syncwarp();
    if (lane == 0) {
        tma_store_2d(&tm_out, sX + warp * 2048, cb * 64, rb * 128 + warp * 16);
        tma_store_commit();
        if (tid == 0) DEV_STAMP(2, 3);
        tma_store_wait();
        if (tid == 0) DEV_STAMP(2, 4);
    }
}

typedef CUresult (*EncodeFn)(CUtensorMap*, CUtensorMapDataType, cuuint32_t, void*, const cuuint64_t*, const cuuint64_t*,
                             const cuuint32_t*, const cuuint32_t*, CUtensorMapInterleave, CUtensorMapSwizzle,
                             CUtensorMapL2promotion, CUtensorMapFloatOOBfill);

struct HostState {
    bool ready;
    const void* key[11];
    CUtensorMap wq, wk, wv, w1, qo, ho, hi, oi, w2, wo, xi, gi, out;
    void *pQ, *pKV, *pH, *pO, *pMax, *pRow, *pCol, *pFlag, *pG;
};
HostState g_hs;

void make_map(EncodeFn fn, CUtensorMap* m, const void* ptr, uint64_t inner, uint64_t outer, uint32_t box_in, uint32_t box_out) {
    cuuint64_t dims[2] = {inner, outer};
    cuuint64_t strides[1] = {inner * 2};
    cuuint32_t box[2] = {box_in, box_out};
    cuuint32_t es[2] = {1, 1};
    fn(m, CU_TENSOR_MAP_DATA_TYPE_BFLOAT16, 2, const_cast<void*>(ptr), dims, strides, box, es, CU_TENSOR_MAP_INTERLEAVE_NONE,
       CU_TENSOR_MAP_SWIZZLE_128B, CU_TENSOR_MAP_L2_PROMOTION_L2_256B, CU_TENSOR_MAP_FLOAT_OOB_FILL_NONE);
}

template <typename... KArgs, typename... Args>
void launch(void (*kern)(KArgs...), int grid, int block, int smem, bool pdl, int cluster, Args... args) {
    cudaLaunchConfig_t cfg = {};
    cfg.gridDim = dim3(grid); cfg.blockDim = dim3(block); cfg.dynamicSmemBytes = smem; cfg.stream = cudaStreamPerThread;
    cudaLaunchAttribute at[2];
    int n = 0;
    if (pdl) { at[n].id = cudaLaunchAttributeProgrammaticStreamSerialization; at[n].val.programmaticStreamSerializationAllowed = 1; n++; }
    if (cluster > 1) { at[n].id = cudaLaunchAttributeClusterDimension; at[n].val.clusterDim.x = cluster; at[n].val.clusterDim.y = 1; at[n].val.clusterDim.z = 1; n++; }
    cfg.attrs = at; cfg.numAttrs = n;
    cudaLaunchKernelEx(&cfg, kern, KArgs(args)...);
}

}

extern "C" void kernel_launch(void* const* d_in, const int* in_sizes, int n_in, void* d_out, int out_size) {
    (void)in_sizes; (void)n_in; (void)out_size;
    HostState& hs = g_hs;
    bool same = hs.ready;
    for (int i = 0; i < 10 && same; i++) same = hs.key[i] == d_in[i];
    same = same && hs.key[10] == d_out;
    if (!same) {
        void* fp = nullptr;
        cudaDriverEntryPointQueryResult qr;
        cudaGetDriverEntryPoint("cuTensorMapEncodeTiled", &fp, cudaEnableDefault, &qr);
        EncodeFn fn = (EncodeFn)fp;
        cudaGetSymbolAddress(&hs.pQ, g_Q); cudaGetSymbolAddress(&hs.pKV, g_KV); cudaGetSymbolAddress(&hs.pH, g_H);
        cudaGetSymbolAddress(&hs.pO, g_O); cudaGetSymbolAddress(&hs.pMax, g_kvmax);
        cudaGetSymbolAddress(&hs.pRow, g_rowstat); cudaGetSymbolAddress(&hs.pCol, g_colpart); cudaGetSymbolAddress(&hs.pG, g_G);
        make_map(fn, &hs.wq, d_in[1], 512, 512, 64, 64);
        make_map(fn, &hs.wk, d_in[2], 16, 512, 64, 64);
        make_map(fn, &hs.wv, d_in[3], 16, 512, 64, 64);
        make_map(fn, &hs.w1, d_in[6], F_DIM, 512, 64, 64);
        make_map(fn, &hs.qo, hs.pQ, 512, S_LEN, 64, 16);
        make_map(fn, &hs.ho, hs.pH, F_DIM, S_LEN, 64, 16);
        make_map(fn, &hs.hi, hs.pH, F_DIM, S_LEN, 64, 64);
        make_map(fn, &hs.gi, hs.pG, 512, S_LEN, 64, 128);
        make_map(fn, &hs.oi, hs.pO, 512, S_LEN, 64, 128);
        make_map(fn, &hs.w2, d_in[8], 512, F_DIM, 64, 64);
        make_map(fn, &hs.wo, d_in[4], 512, 512, 64, 64);
        make_map(fn, &hs.xi, d_in[0], 512, S_LEN, 64, 128);
        make_map(fn, &hs.out, d_out, 512, S_LEN, 64, 16);
        cudaFuncSetAttribute(k1_proj, cudaFuncAttributeMaxDynamicSharedMemorySize, K1_SMEM);
        cudaFuncSetAttribute(k2_attn, cudaFuncAttributeMaxDynamicSharedMemorySize, AT_SMEM);
        cudaFuncSetAttribute(k3_out, cudaFuncAttributeMaxDynamicSharedMemorySize, K3_SMEM);
        for (int i = 0; i < 10; i++) hs.key[i] = d_in[i];
        hs.key[10] = d_out;
        hs.ready = true;
    }
    launch(k1_proj, 128, 384, K1_SMEM, false, 2, hs.xi, hs.wq, hs.wk, hs.wv, hs.w1, hs.qo, hs.ho, (const __nv_bfloat16*)d_in[0],
           (const __nv_bfloat16*)d_in[7], (float2*)hs.pRow, (float*)hs.pCol, (__nv_bfloat16*)hs.pKV, (float*)hs.pMax);
    launch(k2_attn, 128, 640, AT_SMEM, true, 1, hs.hi, hs.w2, (const __nv_bfloat16*)hs.pQ, (const __nv_bfloat16*)hs.pKV,
           (const float*)hs.pMax, (const __nv_bfloat16*)d_in[9], (__nv_bfloat16*)hs.pO, (__nv_bfloat16*)hs.pG, (uint2*)hs.pRow, (uint2*)hs.pCol);
    launch(k3_out, 128, 256, K3_SMEM, true, 1, hs.oi, hs.wo, hs.xi, hs.gi, hs.out);
}
```

```cpp
#include <cuda_runtime.h>
#include <cuda_bf16.h>
#include <cuda.h>
#include <stdint.h>

namespace {

constexpr int S_LEN = 2048, D_MODEL = 512, F_DIM = 1792;

__device__ __align__(1024) __nv_bfloat16 g_Q[S_LEN * D_MODEL];
__device__ __align__(1024) __nv_bfloat16 g_KV[6 * S_LEN * 8];
__device__ __align__(1024) __nv_bfloat16 g_G[S_LEN * D_MODEL];
__device__ __align__(1024) __nv_bfloat16 g_H[S_LEN * F_DIM];
__device__ __align__(1024) __nv_bfloat16 g_O[S_LEN * D_MODEL];
__device__ __align__(1024) float g_kvmax[256];
__device__ __align__(1024) float2 g_rowstat[S_LEN];
__device__ __align__(1024) float g_colpart[8 * 16 * 320];

__device__ __align__(1024) int g_sync[256];

#define DEV_STAMP(k, e) do {} while (0)
__device__ __forceinline__ uint32_t smem_u32(const void* p) { return (uint32_t)__cvta_generic_to_shared(p); }
__device__ __forceinline__ void wg_fence() { asm volatile("wgmma.fence.sync.aligned;" ::: "memory"); }
__device__ __forceinline__ void wg_commit() { asm volatile("wgmma.commit_group.sync.aligned;" ::: "memory"); }
template <int N> __device__ __forceinline__ void wg_wait() { asm volatile("wgmma.wait_group.sync.aligned %0;" ::"n"(N) : "memory"); }
template <int N> __device__ __forceinline__ void fence_regs(float* r) {
#pragma unroll
    for (int i = 0; i < N; i++) asm volatile("" : "+f"(r[i])::"memory");
}
__device__ __forceinline__ void fence_proxy_async() { asm volatile("fence.proxy.async.shared::cta;" ::: "memory"); }
__device__ __forceinline__ void mbar_init(uint32_t bar, int cnt) { asm volatile("mbarrier.init.shared::cta.b64 [%0], %1;" ::"r"(bar), "r"(cnt) : "memory"); }
__device__ __forceinline__ void mbar_init_fence() { asm volatile("fence.mbarrier_init.release.cluster;" ::: "memory"); }
__device__ __forceinline__ void mbar_expect_tx(uint32_t bar, uint32_t bytes) {
    asm volatile("mbarrier.arrive.expect_tx.shared::cta.b64 _, [%0], %1;" ::"r"(bar), "r"(bytes) : "memory");
}
__device__ __forceinline__ void mbar_arrive(uint32_t bar) { asm volatile("mbarrier.arrive.shared::cta.b64 _, [%0];" ::"r"(bar) : "memory"); }
__device__ __forceinline__ bool mbar_try(uint32_t bar, uint32_t parity) {
    uint32_t ok;
    asm volatile("{\n.reg .pred p;\nmbarrier.try_wait.parity.shared::cta.b64 p, [%1], %2;\nselp.u32 %0, 1, 0, p;\n}\n"
                 : "=r"(ok) : "r"(bar), "r"(parity) : "memory");
    return ok != 0;
}
__device__ __forceinline__ void mbar_wait(uint32_t bar, uint32_t parity) {
    if (mbar_try(bar, parity)) return;
    const long long t0 = clock64();
#pragma unroll 1
    while (!mbar_try(bar, parity)) {
        if (clock64() - t0 > 20000000ll) {
            break;
        }
    }
}
__device__ __forceinline__ void bulk_g2s(uint32_t dst, const void* src, uint32_t bytes, uint32_t bar) {
    asm volatile("cp.async.bulk.shared::cluster.global.mbarrier::complete_tx::bytes [%0], [%1], %2, [%3];"
                 ::"r"(dst), "l"(src), "r"(bytes), "r"(bar) : "memory");
}
__device__ __forceinline__ void tma_load_2d(uint32_t dst, const CUtensorMap* tm, int c0, int c1, uint32_t bar) {
    asm volatile("cp.async.bulk.tensor.2d.shared::cluster.global.mbarrier::complete_tx::bytes [%0], [%1, {%3, %4}], [%2];"
                 ::"r"(dst), "l"((uint64_t)tm), "r"(bar), "r"(c0), "r"(c1) : "memory");
}
__device__ __forceinline__ void tma_load_2d_mc(uint32_t dst, const CUtensorMap* tm, int c0, int c1, uint32_t bar, uint16_t mask) {
    asm volatile("cp.async.bulk.tensor.2d.shared::cluster.global.mbarrier::complete_tx::bytes.multicast::cluster [%0], [%1, {%3, %4}], [%2], %5;"
                 ::"r"(dst), "l"((uint64_t)tm), "r"(bar), "r"(c0), "r"(c1), "h"(mask) : "memory");
}
__device__ __forceinline__ void mbar_arrive_remote(uint32_t bar, uint32_t cta) {
    asm volatile("{\n.reg .b32 ra;\nmapa.shared::cluster.u32 ra, %0, %1;\nmbarrier.arrive.shared::cluster.b64 _, [ra];\n}\n"
                 ::"r"(bar), "r"(cta) : "memory");
}
__device__ __forceinline__ void cluster_sync_relaxed() {
    asm volatile("barrier.cluster.arrive.relaxed;\nbarrier.cluster.wait;" ::: "memory");
}
__device__ __forceinline__ uint2 ld_relaxed_v2(const void* p) {
    uint2 v; asm volatile("ld.relaxed.gpu.global.v2.b32 {%0,%1}, [%2];" : "=r"(v.x), "=r"(v.y) : "l"(p) : "memory"); return v;
}
__device__ __forceinline__ void signal_add(int* p) {
    asm volatile("fence.acq_rel.gpu;\nred.relaxed.gpu.global.add.s32 [%0], 1;" ::"l"(p) : "memory");
}
__device__ __forceinline__ void wait_count(const int* p, int target) {
    int v = -1;
#pragma unroll 1
    for (uint32_t n = 0; n < (1u << 18); n++) {
        asm volatile("ld.acquire.gpu.global.s32 %0, [%1];" : "=r"(v) : "l"(p) : "memory");
        if (v >= target) break;
        __nanosleep(64);
    }
    asm volatile("fence.proxy.async;" ::: "memory");
}
constexpr uint32_t NOT_READY = 0u;
__device__ __forceinline__ float xch_enc(float v) { return __uint_as_float((v == 0.f ? 0u : __float_as_uint(v)) ^ 0x80000000u); }
__device__ __forceinline__ float xch_dec(uint32_t u) { return __uint_as_float(u ^ 0x80000000u); }
__device__ __forceinline__ void tma_store_2d(const CUtensorMap* tm, uint32_t src, int c0, int c1) {
    asm volatile("cp.async.bulk.tensor.2d.global.shared::cta.bulk_group [%0, {%2, %3}], [%1];"
                 ::"l"((uint64_t)tm), "r"(src), "r"(c0), "r"(c1) : "memory");
}
__device__ __forceinline__ void tma_store_commit() { asm volatile("cp.async.bulk.commit_group;" ::: "memory"); }
__device__ __forceinline__ void tma_store_wait() { asm volatile("cp.async.bulk.wait_group 0;" ::: "memory"); }
__device__ __forceinline__ void tma_prefetch_desc(const CUtensorMap* tm) { asm volatile("prefetch.tensormap [%0];" ::"l"((uint64_t)tm) : "memory"); }
__device__ __forceinline__ void named_bar_sync(int id, int n) { asm volatile("bar.sync %0, %1;" ::"r"(id), "r"(n) : "memory"); }
__device__ __forceinline__ void pdl_wait() { asm volatile("griddepcontrol.wait;" ::: "memory"); }
__device__ __forceinline__ void pdl_launch() { asm volatile("griddepcontrol.launch_dependents;" ::: "memory"); }
template <int N> __device__ __forceinline__ void reg_alloc() { asm volatile("setmaxnreg.inc.sync.aligned.u32 %0;" ::"n"(N)); }
template <int N> __device__ __forceinline__ void reg_dealloc() { asm volatile("setmaxnreg.dec.sync.aligned.u32 %0;" ::"n"(N)); }
__device__ __forceinline__ float ex2(float x) { float y; asm("ex2.approx.ftz.f32 %0, %1;" : "=f"(y) : "f"(x)); return y; }
__device__ __forceinline__ uint32_t pack_bf16(float lo, float hi) {
    uint32_t r; asm("cvt.rn.bf16x2.f32 %0, %1, %2;" : "=r"(r) : "f"(hi), "f"(lo)); return r;
}
__device__ __forceinline__ uint32_t pack_bf16_relu(float lo, float hi) {
    uint32_t r; asm("cvt.rn.relu.bf16x2.f32 %0, %1, %2;" : "=r"(r) : "f"(hi), "f"(lo)); return r;
}
__device__ __forceinline__ uint32_t mul_bf16x2(uint32_t a, uint32_t b) {
    uint32_t r; asm("mul.rn.bf16x2 %0, %1, %2;" : "=r"(r) : "r"(a), "r"(b)); return r;
}
__device__ __forceinline__ float bf_lo(uint32_t v) { return __uint_as_float(v << 16); }
__device__ __forceinline__ float bf_hi(uint32_t v) { return __uint_as_float(v & 0xFFFF0000u); }
__device__ __forceinline__ void stmatrix_x4(uint32_t addr, uint32_t r0, uint32_t r1, uint32_t r2, uint32_t r3) {
    asm volatile("stmatrix.sync.aligned.m8n8.x4.shared.b16 [%0], {%1,%2,%3,%4};" ::"r"(addr), "r"(r0), "r"(r1), "r"(r2), "r"(r3) : "memory");
}
__device__ __forceinline__ uint64_t make_desc(uint32_t addr, uint32_t lbo, uint32_t sbo, uint32_t swz) {
    return (uint64_t)((addr & 0x3FFFF) >> 4) | ((uint64_t)(lbo >> 4) << 16) | ((uint64_t)(sbo >> 4) << 32) | ((uint64_t)swz << 62);
}

__device__ __forceinline__ uint64_t desc64(uint32_t lo, uint32_t hi) {
    uint64_t d; asm("mov.b64 %0, {%1, %2};" : "=l"(d) : "r"(lo), "r"(hi)); return d;
}

__device__ __forceinline__ void wgmma_ss_n256_tb(float* d, uint64_t descA, uint64_t descB, int scaleD) {
    asm volatile("{\n.reg .pred p;\nsetp.ne.b32 p, %130, 0;\n"
      "wgmma.mma_async.sync.aligned.m64n256k16.f32.bf16.bf16 {%0,%1,%2,%3,%4,%5,%6,%7,%8,%9,%10,%11,%12,%13,%14,%15,%16,%17,%18,%19,%20,%21,%22,%23,%24,%25,%26,%27,%28,%29,%30,%31,%32,%33,%34,%35,%36,%37,%38,%39,%40,%41,%42,%43,%44,%45,%46,%47,%48,%49,%50,%51,%52,%53,%54,%55,%56,%57,%58,%59,%60,%61,%62,%63,%64,%65,%66,%67,%68,%69,%70,%71,%72,%73,%74,%75,%76,%77,%78,%79,%80,%81,%82,%83,%84,%85,%86,%87,%88,%89,%90,%91,%92,%93,%94,%95,%96,%97,%98,%99,%100,%101,%102,%103,%104,%105,%106,%107,%108,%109,%110,%111,%112,%113,%114,%115,%116,%117,%118,%119,%120,%121,%122,%123,%124,%125,%126,%127}, %128, %129, p, 1, 1, 0, 1;\n}\n"
      : "+f"(d[0]), "+f"(d[1]), "+f"(d[2]), "+f"(d[3]), "+f"(d[4]), "+f"(d[5]), "+f"(d[6]), "+f"(d[7]), "+f"(d[8]), "+f"(d[9]), "+f"(d[10]), "+f"(d[11]), "+f"(d[12]), "+f"(d[13]), "+f"(d[14]), "+f"(d[15]), "+f"(d[16]), "+f"(d[17]), "+f"(d[18]), "+f"(d[19]), "+f"(d[20]), "+f"(d[21]), "+f"(d[22]), "+f"(d[23]), "+f"(d[24]), "+f"(d[25]), "+f"(d[26]), "+f"(d[27]), "+f"(d[28]), "+f"(d[29]), "+f"(d[30]), "+f"(d[31]), "+f"(d[32]), "+f"(d[33]), "+f"(d[34]), "+f"(d[35]), "+f"(d[36]), "+f"(d[37]), "+f"(d[38]), "+f"(d[39]), "+f"(d[40]), "+f"(d[41]), "+f"(d[42]), "+f"(d[43]), "+f"(d[44]), "+f"(d[45]), "+f"(d[46]), "+f"(d[47]), "+f"(d[48]), "+f"(d[49]), "+f"(d[50]), "+f"(d[51]), "+f"(d[52]), "+f"(d[53]), "+f"(d[54]), "+f"(d[55]), "+f"(d[56]), "+f"(d[57]), "+f"(d[58]), "+f"(d[59]), "+f"(d[60]), "+f"(d[61]), "+f"(d[62]), "+f"(d[63]), "+f"(d[64]), "+f"(d[65]), "+f"(d[66]), "+f"(d[67]), "+f"(d[68]), "+f"(d[69]), "+f"(d[70]), "+f"(d[71]), "+f"(d[72]), "+f"(d[73]), "+f"(d[74]), "+f"(d[75]), "+f"(d[76]), "+f"(d[77]), "+f"(d[78]), "+f"(d[79]), "+f"(d[80]), "+f"(d[81]), "+f"(d[82]), "+f"(d[83]), "+f"(d[84]), "+f"(d[85]), "+f"(d[86]), "+f"(d[87]), "+f"(d[88]), "+f"(d[89]), "+f"(d[90]), "+f"(d[91]), "+f"(d[92]), "+f"(d[93]), "+f"(d[94]), "+f"(d[95]), "+f"(d[96]), "+f"(d[97]), "+f"(d[98]), "+f"(d[99]), "+f"(d[100]), "+f"(d[101]), "+f"(d[102]), "+f"(d[103]), "+f"(d[104]), "+f"(d[105]), "+f"(d[106]), "+f"(d[107]), "+f"(d[108]), "+f"(d[109]), "+f"(d[110]), "+f"(d[111]), "+f"(d[112]), "+f"(d[113]), "+f"(d[114]), "+f"(d[115]), "+f"(d[116]), "+f"(d[117]), "+f"(d[118]), "+f"(d[119]), "+f"(d[120]), "+f"(d[121]), "+f"(d[122]), "+f"(d[123]), "+f"(d[124]), "+f"(d[125]), "+f"(d[126]), "+f"(d[127])
      : "l"(descA), "l"(descB), "r"(scaleD));
}
__device__ __forceinline__ void wgmma_ss_n128_tb(float* d, uint64_t descA, uint64_t descB, int scaleD) {
    asm volatile("{\n.reg .pred p;\nsetp.ne.b32 p, %66, 0;\n"
      "wgmma.mma_async.sync.aligned.m64n128k16.f32.bf16.bf16 {%0,%1,%2,%3,%4,%5,%6,%7,%8,%9,%10,%11,%12,%13,%14,%15,%16,%17,%18,%19,%20,%21,%22,%23,%24,%25,%26,%27,%28,%29,%30,%31,%32,%33,%34,%35,%36,%37,%38,%39,%40,%41,%42,%43,%44,%45,%46,%47,%48,%49,%50,%51,%52,%53,%54,%55,%56,%57,%58,%59,%60,%61,%62,%63}, %64, %65, p, 1, 1, 0, 1;\n}\n"
      : "+f"(d[0]), "+f"(d[1]), "+f"(d[2]), "+f"(d[3]), "+f"(d[4]), "+f"(d[5]), "+f"(d[6]), "+f"(d[7]), "+f"(d[8]), "+f"(d[9]), "+f"(d[10]), "+f"(d[11]), "+f"(d[12]), "+f"(d[13]), "+f"(d[14]), "+f"(d[15]), "+f"(d[16]), "+f"(d[17]), "+f"(d[18]), "+f"(d[19]), "+f"(d[20]), "+f"(d[21]), "+f"(d[22]), "+f"(d[23]), "+f"(d[24]), "+f"(d[25]), "+f"(d[26]), "+f"(d[27]), "+f"(d[28]), "+f"(d[29]), "+f"(d[30]), "+f"(d[31]), "+f"(d[32]), "+f"(d[33]), "+f"(d[34]), "+f"(d[35]), "+f"(d[36]), "+f"(d[37]), "+f"(d[38]), "+f"(d[39]), "+f"(d[40]), "+f"(d[41]), "+f"(d[42]), "+f"(d[43]), "+f"(d[44]), "+f"(d[45]), "+f"(d[46]), "+f"(d[47]), "+f"(d[48]), "+f"(d[49]), "+f"(d[50]), "+f"(d[51]), "+f"(d[52]), "+f"(d[53]), "+f"(d[54]), "+f"(d[55]), "+f"(d[56]), "+f"(d[57]), "+f"(d[58]), "+f"(d[59]), "+f"(d[60]), "+f"(d[61]), "+f"(d[62]), "+f"(d[63])
      : "l"(descA), "l"(descB), "r"(scaleD));
}
__device__ __forceinline__ void wgmma_ss_n64_tb(float* d, uint64_t descA, uint64_t descB, int scaleD) {
    asm volatile("{\n.reg .pred p;\nsetp.ne.b32 p, %34, 0;\n"
      "wgmma.mma_async.sync.aligned.m64n64k16.f32.bf16.bf16 {%0,%1,%2,%3,%4,%5,%6,%7,%8,%9,%10,%11,%12,%13,%14,%15,%16,%17,%18,%19,%20,%21,%22,%23,%24,%25,%26,%27,%28,%29,%30,%31}, %32, %33, p, 1, 1, 0, 1;\n}\n"
      : "+f"(d[0]), "+f"(d[1]), "+f"(d[2]), "+f"(d[3]), "+f"(d[4]), "+f"(d[5]), "+f"(d[6]), "+f"(d[7]), "+f"(d[8]), "+f"(d[9]), "+f"(d[10]), "+f"(d[11]), "+f"(d[12]), "+f"(d[13]), "+f"(d[14]), "+f"(d[15]), "+f"(d[16]), "+f"(d[17]), "+f"(d[18]), "+f"(d[19]), "+f"(d[20]), "+f"(d[21]), "+f"(d[22]), "+f"(d[23]), "+f"(d[24]), "+f"(d[25]), "+f"(d[26]), "+f"(d[27]), "+f"(d[28]), "+f"(d[29]), "+f"(d[30]), "+f"(d[31])
      : "l"(descA), "l"(descB), "r"(scaleD));
}
__device__ __forceinline__ void wgmma_qk_acc_n64(float* d, const uint32_t* a, uint64_t descB) {
    asm volatile("wgmma.mma_async.sync.aligned.m64n64k16.f32.bf16.bf16 {%0,%1,%2,%3,%4,%5,%6,%7,%8,%9,%10,%11,%12,%13,%14,%15,%16,%17,%18,%19,%20,%21,%22,%23,%24,%25,%26,%27,%28,%29,%30,%31}, {%32,%33,%34,%35}, %36, 1, 1, 1, 0;\n"
      : "+f"(d[0]), "+f"(d[1]), "+f"(d[2]), "+f"(d[3]), "+f"(d[4]), "+f"(d[5]), "+f"(d[6]), "+f"(d[7]), "+f"(d[8]), "+f"(d[9]), "+f"(d[10]), "+f"(d[11]), "+f"(d[12]), "+f"(d[13]), "+f"(d[14]), "+f"(d[15]), "+f"(d[16]), "+f"(d[17]), "+f"(d[18]), "+f"(d[19]), "+f"(d[20]), "+f"(d[21]), "+f"(d[22]), "+f"(d[23]), "+f"(d[24]), "+f"(d[25]), "+f"(d[26]), "+f"(d[27]), "+f"(d[28]), "+f"(d[29]), "+f"(d[30]), "+f"(d[31])
      : "r"(a[0]), "r"(a[1]), "r"(a[2]), "r"(a[3]), "l"(descB));
}

__device__ __forceinline__ void wgmma_pv(float* d, uint32_t a0, uint32_t a1, uint32_t a2, uint32_t a3, uint64_t descB) {
    asm volatile("wgmma.mma_async.sync.aligned.m64n24k16.f32.bf16.bf16 {%0,%1,%2,%3,%4,%5,%6,%7,%8,%9,%10,%11}, {%12,%13,%14,%15}, %16, 1, 1, 1, 1;\n"
                 : "+f"(d[0]), "+f"(d[1]), "+f"(d[2]), "+f"(d[3]), "+f"(d[4]), "+f"(d[5]), "+f"(d[6]), "+f"(d[7]), "+f"(d[8]), "+f"(d[9]), "+f"(d[10]), "+f"(d[11])
                 : "r"(a0), "r"(a1), "r"(a2), "r"(a3), "l"(descB));
}

__device__ __forceinline__ void k1_panel(int g, int i, int& type, int& col) {
    if (g < 6) {
        int p = g * 5 + i;
        if (p < 8) { type = 0; col = p * 64; } else { type = 1; col = (p - 8) * 64; }
    } else {
        if (i < 3) { type = 1; col = (22 + (g - 6) * 3 + i) * 64; } else { type = 2 + (g - 6); col = 0; }
    }
}

constexpr int K1_STAGES = 4;
constexpr int K1_PANEL_BYTES = 64 * 128;
constexpr int K1_STAGE_BYTES = 16384 + 5 * K1_PANEL_BYTES;
constexpr int K1_SMEM = K1_STAGES * K1_STAGE_BYTES + 128 + 320 * 8;
constexpr float Q_SCALE = 0.25f * 1.4426950408889634f;

__global__ void __launch_bounds__(384, 1)
k1_proj(const __grid_constant__ CUtensorMap tm_x, const __grid_constant__ CUtensorMap tm_wq,
        const __grid_constant__ CUtensorMap tm_wk, const __grid_constant__ CUtensorMap tm_wv,
        const __grid_constant__ CUtensorMap tm_w1, const __grid_constant__ CUtensorMap tm_qo,
        const __grid_constant__ CUtensorMap tm_ho, const __nv_bfloat16* __restrict__ x, const __nv_bfloat16* __restrict__ b1,
        float2* rowstat, float* colpart, int* syncp,
        __nv_bfloat16* __restrict__ kv, float* __restrict__ kvmax) {
    extern __shared__ __align__(1024) uint8_t smem_raw[];
    const uint32_t sbase = smem_u32(smem_raw);
    const uint32_t bar_full = sbase + K1_STAGES * K1_STAGE_BYTES, bar_empty = bar_full + 8 * K1_STAGES, bar_col = bar_empty + 8 * K1_STAGES;
    const uint32_t sCol = bar_full + 128;
    const int tid = threadIdx.x, warp = __shfl_sync(0xffffffffu, tid >> 5, 0), lane = tid & 31;
    const int crank = blockIdx.x & 1, grp = (blockIdx.x >> 1) & 7, rb = (blockIdx.x >> 4) * 2 + crank;
    const int npanels = grp < 6 ? 5 : 4;
    if (tid == 0) DEV_STAMP(0, 0);

    if (tid == 288) {
        tma_prefetch_desc(&tm_x); tma_prefetch_desc(&tm_w1); tma_prefetch_desc(grp < 2 ? &tm_wq : grp == 6 ? &tm_wk : &tm_wv);
        tma_prefetch_desc(&tm_ho); tma_prefetch_desc(&tm_qo);
    }
    uint4 v[2][2];
    if (warp < 8) {
        const uint4* xp = reinterpret_cast<const uint4*>(x + (size_t)(rb * 128 + grp * 16 + warp * 2) * D_MODEL);
#pragma unroll
        for (int r = 0; r < 2; r++) { v[r][0] = __ldg(xp + r * 64 + lane); v[r][1] = __ldg(xp + r * 64 + 32 + lane); }
    }
    const int krot = rb & 8 ? 4 : 0, cstage = (rb >> 1) & 3;
    if (tid == 256) {
        for (int s = 0; s < K1_STAGES; s++) { mbar_init(bar_full + 8 * s, 1); mbar_init(bar_empty + 8 * s, s == cstage ? 18 : 16); }
        mbar_init(bar_col, 96);
        mbar_init_fence();
    }
    if (tid >= 128 && tid < 130) syncp[(tid - 128) * 128 + blockIdx.x] = 0;
    asm volatile("barrier.cluster.arrive.relaxed;" ::: "memory");
    if (warp != 8) asm volatile("barrier.cluster.wait;" ::: "memory");
    pdl_launch();

    if (warp >= 8) {
        reg_dealloc<88>();
        if (warp == 8) {
            const CUtensorMap* tms[5]; int cols[5];
#pragma unroll
            for (int i = 0; i < 5; i++) {
                int type, col; k1_panel(grp, i, type, col);
                tms[i] = type == 0 ? &tm_wq : type == 1 ? &tm_w1 : type == 2 ? &tm_wk : &tm_wv;
                cols[i] = col;
            }
            if (lane == 0) {
                mbar_expect_tx(bar_full, 16384 + npanels * K1_PANEL_BYTES);
                tma_load_2d(sbase, &tm_x, krot * 64, rb * 128, bar_full);
#pragma unroll
                for (int i = 0; i < 5; i++)
                    if (i < npanels) tma_load_2d(sbase + 16384 + i * K1_PANEL_BYTES, tms[i], cols[i], krot * 64, bar_full);
            }
            __syncwarp();
            asm volatile("barrier.cluster.wait;" ::: "memory");
            constexpr int KS0 = 1;
            if (lane == 0) {
                for (int ks = KS0; ks < 8; ks++) {
                    const int s = ks % K1_STAGES;
                    const uint32_t st = sbase + s * K1_STAGE_BYTES;
                    mbar_wait(bar_empty + 8 * s, ((ks / K1_STAGES) & 1) ^ 1);
                    const int k0 = ((ks + krot) & 7) * 64;
                    mbar_expect_tx(bar_full + 8 * s, 16384 + npanels * K1_PANEL_BYTES);
                    tma_load_2d(st, &tm_x, k0, rb * 128, bar_full + 8 * s);
#pragma unroll
                    for (int i = 0; i < 5; i++)
                        if (i < npanels && ((i + ks + crank) & 1) == 0)
                            tma_load_2d_mc(st + 16384 + i * K1_PANEL_BYTES, tms[i], cols[i], k0, bar_full + 8 * s, (uint16_t)3);
                }
            }
        } else {
            const int ht = tid - 288;
            mbar_wait(bar_full + 8 * cstage, 0);
            {
                const int pc = ht >> 1, half = ht & 1;
                float sacc[8];
#pragma unroll
                for (int c = 0; c < 8; c++) sacc[c] = 0.f;
                if (pc < npanels * 8) {
                    const uint32_t pb = sbase + cstage * K1_STAGE_BYTES + 16384 + (pc >> 3) * K1_PANEL_BYTES;
#pragma unroll
                    for (int i = 0; i < 16; i++) {
                        const int k = crank * 32 + 2 * i + half;
                        uint4 u;
                        asm volatile("ld.shared.v4.b32 {%0,%1,%2,%3}, [%4];" : "=r"(u.x), "=r"(u.y), "=r"(u.z), "=r"(u.w)
                                     : "r"(pb + k * 128 + (((pc & 7) ^ (k & 7)) << 4)));
                        sacc[0] += bf_lo(u.x); sacc[1] += bf_hi(u.x); sacc[2] += bf_lo(u.y); sacc[3] += bf_hi(u.y);
                        sacc[4] += bf_lo(u.z); sacc[5] += bf_hi(u.z); sacc[6] += bf_lo(u.w); sacc[7] += bf_hi(u.w);
                    }
                }
#pragma unroll
                for (int c = 0; c < 8; c++) sacc[c] += __shfl_xor_sync(0xffffffffu, sacc[c], 1);
                if (pc < npanels * 8) {
                    float4* dst = reinterpret_cast<float4*>(colpart + (grp * 16 + rb) * 320 + pc * 8) + half;
                    *dst = half ? make_float4(xch_enc(sacc[4]), xch_enc(sacc[5]), xch_enc(sacc[6]), xch_enc(sacc[7]))
                                : make_float4(xch_enc(sacc[0]), xch_enc(sacc[1]), xch_enc(sacc[2]), xch_enc(sacc[3]));
                }
                named_bar_sync(4, 96);
                if (ht < 2) mbar_arrive_remote(bar_empty + 8 * cstage, ht);
            }
            if (ht == 0) DEV_STAMP(0, 6);
            for (int c2 = ht; c2 < npanels * 32; c2 += 96) {
                int type, col; k1_panel(grp, c2 >> 5, type, col);
                uint32_t bb = 0;
                if (type == 1) bb = __ldg(reinterpret_cast<const uint32_t*>(b1 + col) + (c2 & 31));
                uint2 pv[16];
                bool okv = false;
#pragma unroll 1
                for (uint32_t n = 0; n < (1u << 14) && !okv; n++) {
                    okv = true;
#pragma unroll
                    for (int k = 0; k < 16; k++) pv[k] = ld_relaxed_v2(colpart + (grp * 16 + k) * 320 + c2 * 2);
#pragma unroll
                    for (int k = 0; k < 16; k++) okv = okv && pv[k].x != NOT_READY && pv[k].y != NOT_READY;
                }
                float s0 = 0.f, s1 = 0.f;
#pragma unroll
                for (int k = 0; k < 16; k++) { s0 += xch_dec(pv[k].x); s1 += xch_dec(pv[k].y); }
                asm volatile("st.shared.v4.f32 [%0], {%1,%2,%3,%4};" ::"r"(sCol + c2 * 16), "f"(s0), "f"(bf_lo(bb)), "f"(s1), "f"(bf_hi(bb)) : "memory");
            }
            mbar_arrive(bar_col);
            if (ht == 0) DEV_STAMP(0, 7);
        }
    } else {
        reg_alloc<208>();
        const int wg = warp >> 2;
        const int g = lane >> 2, t = lane & 3;
        const int wrow = (warp & 3) * 16;
        {
            float f[2][16], sum[2], sq[2];
#pragma unroll
            for (int r = 0; r < 2; r++) {
                const uint32_t w[8] = {v[r][0].x, v[r][0].y, v[r][0].z, v[r][0].w, v[r][1].x, v[r][1].y, v[r][1].z, v[r][1].w};
#pragma unroll
                for (int i = 0; i < 8; i++) { f[r][2 * i] = bf_lo(w[i]); f[r][2 * i + 1] = bf_hi(w[i]); }
                sum[r] = 0.f;
#pragma unroll
                for (int i = 0; i < 16; i++) sum[r] += f[r][i];
            }
#pragma unroll
            for (int o = 16; o > 0; o >>= 1) { sum[0] += __shfl_xor_sync(0xffffffffu, sum[0], o); sum[1] += __shfl_xor_sync(0xffffffffu, sum[1], o); }
#pragma unroll
            for (int r = 0; r < 2; r++) {
                sum[r] *= (1.0f / D_MODEL);
                sq[r] = 0.f;
#pragma unroll
                for (int i = 0; i < 16; i++) { const float d = f[r][i] - sum[r]; sq[r] += d * d; }
            }
#pragma unroll
            for (int o = 16; o > 0; o >>= 1) { sq[0] += __shfl_xor_sync(0xffffffffu, sq[0], o); sq[1] += __shfl_xor_sync(0xffffffffu, sq[1], o); }
            if (lane < 2) {
                const float rstd = rsqrtf((lane ? sq[1] : sq[0]) * (1.0f / D_MODEL) + 1e-5f);
                rowstat[rb * 128 + grp * 16 + warp * 2 + lane] = make_float2(xch_enc(rstd), (lane ? sum[1] : sum[0]) * rstd);
            }
            if (tid == 0) DEV_STAMP(0, 5);
        }
        float acc[160];
#pragma unroll
        for (int i = 0; i < 160; i++) acc[i] = 0.f;
        float2 rs0, rs1;
        const uint64_t dA0 = make_desc(sbase + wg * 8192, 16, 1024, 1);
        const uint64_t dB0 = make_desc(sbase + 16384, K1_PANEL_BYTES, 1024, 1);
#define K1_MAINLOOP(FIVE)                                                                                          \
        for (int ks = 0; ks < 8; ks++) {                                                                           \
            const int s = ks % K1_STAGES;                                                                          \
            mbar_wait(bar_full + 8 * s, (ks / K1_STAGES) & 1);                                                     \
            if (ks == 0 && tid == 0) DEV_STAMP(0, 1);                                                              \
            wg_fence();                                                                                            \
            _Pragma("unroll") for (int kk = 0; kk < 4; kk++) {                                                     \
                const uint64_t dA = dA0 + (uint64_t)((s * K1_STAGE_BYTES + kk * 32) >> 4);                         \
                const uint64_t dB = dB0 + (uint64_t)((s * K1_STAGE_BYTES + kk * 2048) >> 4);                       \
                wgmma_ss_n256_tb(acc, dA, dB, (ks | kk) != 0);                                                     \
                if (FIVE) wgmma_ss_n64_tb(acc + 128, dA, dB + (uint64_t)((4 * K1_PANEL_BYTES) >> 4), (ks | kk) != 0); \
            }                                                                                                      \
            wg_commit();                                                                                           \
            if (ks == 7) {                                                                                         \
                uint2 r0, r1;                                                                                      \
                uint32_t n = 0;                                                                                    \
                _Pragma("unroll 1") do {                                                                           \
                    r0 = ld_relaxed_v2(rowstat + rb * 128 + wg * 64 + wrow + g);                                   \
                    r1 = ld_relaxed_v2(rowstat + rb * 128 + wg * 64 + wrow + g + 8);                               \
                } while ((r0.x == NOT_READY || r1.x == NOT_READY) && ++n < (1u << 14));                            \
                rs0 = make_float2(xch_dec(r0.x), __uint_as_float(r0.y));                                           \
                rs1 = make_float2(xch_dec(r1.x), __uint_as_float(r1.y));                                           \
                mbar_wait(bar_col, 0);                                                                             \
            }                                                                                                      \
            if (ks > 0 && ks <= 4) {                                                                               \
                wg_wait<1>();                                                                                      \
                if (lane < 2) mbar_arrive_remote(bar_empty + 8 * ((ks - 1) % K1_STAGES), lane);                    \
            }                                                                                                      \
        }                                                                                                          \
        wg_wait<0>();
        const int srow = (lane & 7) + ((lane >> 3) & 1) * 8;
        if (npanels == 5) { K1_MAINLOOP(true) } else { K1_MAINLOOP(false) }
        fence_regs<160>(acc);
        if (tid == 0) DEV_STAMP(0, 2);
        named_bar_sync(1, 256);
#pragma unroll
        for (int p = 0; p < 5; p++) {
            if (p < npanels) {
                int type, col; k1_panel(grp, p, type, col);
                float* a = acc + p * 32;
                const int nj = type <= 1 ? 8 : 2;
                const float sc = type == 0 ? Q_SCALE : 1.0f;
                const float r0x = rs0.x * sc, r0y = -rs0.y * sc, r1x = rs1.x * sc, r1y = -rs1.y * sc;
#pragma unroll
                for (int j = 0; j < 8; j++) {
                    if (j < nj) {
                        float4 c;
                        asm volatile("ld.shared.v4.f32 {%0,%1,%2,%3}, [%4];" : "=f"(c.x), "=f"(c.y), "=f"(c.z), "=f"(c.w)
                                     : "r"(sCol + (p * 64 + j * 8 + 2 * t) * 8));
                        a[4 * j] = fmaf(a[4 * j], r0x, fmaf(r0y, c.x, c.y));
                        a[4 * j + 1] = fmaf(a[4 * j + 1], r0x, fmaf(r0y, c.z, c.w));
                        a[4 * j + 2] = fmaf(a[4 * j + 2], r1x, fmaf(r1y, c.x, c.y));
                        a[4 * j + 3] = fmaf(a[4 * j + 3], r1x, fmaf(r1y, c.z, c.w));
                    }
                }
                if (type <= 1) {
                    const uint32_t stg = sbase + (p * 8 + warp) * 2048;
                    uint32_t pk[16];
                    if (type == 0) {
#pragma unroll
                        for (int j = 0; j < 8; j++) {
                            pk[2 * j] = pack_bf16(a[4 * j], a[4 * j + 1]);
                            pk[2 * j + 1] = pack_bf16(a[4 * j + 2], a[4 * j + 3]);
                        }
                    } else {
#pragma unroll
                        for (int j = 0; j < 8; j++) {
                            const uint32_t h0 = pack_bf16_relu(a[4 * j], a[4 * j + 1]), h1 = pack_bf16_relu(a[4 * j + 2], a[4 * j + 3]);
                            pk[2 * j] = mul_bf16x2(h0, h0);
                            pk[2 * j + 1] = mul_bf16x2(h1, h1);
                        }
                    }
#pragma unroll
                    for (int j = 0; j < 8; j += 2) {
                        const int c16 = j + (lane >> 4);
                        stmatrix_x4(stg + srow * 128 + ((c16 ^ (srow & 7)) << 4), pk[2 * j], pk[2 * j + 1], pk[2 * j + 2], pk[2 * j + 3]);
                    }
                    fence_proxy_async();
                    __syncwarp();
                    if (lane == 0) {
                        tma_store_2d(type == 0 ? &tm_qo : &tm_ho, stg, col, rb * 128 + warp * 16);
                        tma_store_commit();
                    }
                } else if (type == 3) {
                    const int r = wg * 64 + wrow + g;
                    const int pos0 = (r >> 2) * 64 + rb * 4 + (r & 3), pos1 = pos0 + 128;
                    uint32_t* dst = reinterpret_cast<uint32_t*>(kv);
                    const uint32_t r00 = pack_bf16(a[0], a[1]), r01 = pack_bf16(a[4], a[5]);
                    const uint32_t r10 = pack_bf16(a[2], a[3]), r11 = pack_bf16(a[6], a[7]);
                    dst[(pos0 >> 4) * 128 + (pos0 & 15) * 4 + t] = r00;
                    dst[16384 + pos0 * 4 + t] = r01;
                    dst[(pos1 >> 4) * 128 + (pos1 & 15) * 4 + t] = r10;
                    dst[16384 + pos1 * 4 + t] = r11;
                    float m = fmaxf(fmaxf(fmaxf(fabsf(bf_lo(r00)), fabsf(bf_hi(r00))), fmaxf(fabsf(bf_lo(r01)), fabsf(bf_hi(r01)))),
                                    fmaxf(fmaxf(fabsf(bf_lo(r10)), fabsf(bf_hi(r10))), fmaxf(fabsf(bf_lo(r11)), fabsf(bf_hi(r11)))));
#pragma unroll
                    for (int o = 16; o > 0; o >>= 1) m = fmaxf(m, __shfl_xor_sync(0xffffffffu, m, o));
                    if (lane == 0) kvmax[128 + rb * 8 + warp] = m;
                } else {
                    float* kf = reinterpret_cast<float*>(smem_raw + 96 * 1024);
                    const int r = wg * 64 + wrow + g;
                    const int pos0 = (r >> 2) * 64 + rb * 4 + (r & 3), pos1 = pos0 + 128;
                    uint32_t* dst = reinterpret_cast<uint32_t*>(kv) + 32768;
                    dst[(pos0 >> 3) * 64 + (pos0 & 7) * 4 + t] = pack_bf16(a[0], a[1]);
                    dst[(pos0 >> 3) * 64 + 32 + (pos0 & 7) * 4 + t] = pack_bf16(a[4], a[5]);
                    dst[(pos1 >> 3) * 64 + (pos1 & 7) * 4 + t] = pack_bf16(a[2], a[3]);
                    dst[(pos1 >> 3) * 64 + 32 + (pos1 & 7) * 4 + t] = pack_bf16(a[6], a[7]);
                    kf[r * 17 + 2 * t] = a[0]; kf[r * 17 + 2 * t + 1] = a[1];
                    kf[r * 17 + 8 + 2 * t] = a[4]; kf[r * 17 + 8 + 2 * t + 1] = a[5];
                    kf[(r + 8) * 17 + 2 * t] = a[2]; kf[(r + 8) * 17 + 2 * t + 1] = a[3];
                    kf[(r + 8) * 17 + 8 + 2 * t] = a[6]; kf[(r + 8) * 17 + 8 + 2 * t + 1] = a[7];
                    named_bar_sync(1, 256);
                    if (tid < 64) {
                        const int i = tid >> 4, dim = tid & 15;
                        const int c = rb * 4 + i;
                        const int inner = (dim >> 3) * 64 + (c & 7) * 8 + (dim & 7);
                        float kt = 0.f;
#pragma unroll 8
                        for (int j = 0; j < 32; j++) {
                            const __nv_bfloat16 d = __float2bfloat16_rn(kf[(j * 4 + i) * 17 + dim] - kt);
                            kt += __bfloat162float(d);
                            kf[(j * 4 + i) * 17 + dim] = kt;
                            const int grp8 = j * 8 + (c >> 3);
                            kv[(grp8 < 128 ? grp8 * 256 + 128 : 49152 + (grp8 - 128) * 128) + inner] = d;
                        }
                    }
                    named_bar_sync(1, 256);
                    if (tid < 128) {
                        float n = 0.f;
#pragma unroll
                        for (int d = 0; d < 16; d++) { const float v = kf[tid * 17 + d]; n += v * v; }
                        if (!(n == n)) n = __int_as_float(0x7f800000);
#pragma unroll
                        for (int o = 8; o > 0; o >>= 1) n = fmaxf(n, __shfl_xor_sync(0xffffffffu, n, o));
                        if ((lane & 15) == 0) kvmax[rb * 8 + (tid >> 4)] = n;
                    }
                }
            }
        }
        if (tid == 0) DEV_STAMP(0, 3);
        if (lane == 0) tma_store_wait();
        if (tid == 0) DEV_STAMP(0, 4);
    }
}

#define K2_MINI 1
constexpr int AT_KT = 64;
constexpr int AT_NCHUNK = 8;
constexpr int AT_NSTEP = S_LEN / AT_KT;
constexpr int AT_SPC = AT_NSTEP / AT_NCHUNK;
constexpr int AT_ONES = 131072;
constexpr int F2_STAGES = 4;
constexpr int F2_STAGE_BYTES = 8192 + 16384;
constexpr int F2_BASE = 132096;
constexpr int F2_NK = F_DIM / 64;
constexpr int AT_BAR = F2_BASE + F2_STAGES * F2_STAGE_BYTES;
constexpr int AT_SMEM = AT_BAR + 256;
#define AT_SWMASK_V 0xB6DB
constexpr uint32_t AT_SWMASK = AT_SWMASK_V;

#define AT_MAGIC (383.0f + 0.00390625f - 0.5849625f)
__device__ __forceinline__ uint32_t exp2_pair_alu(float t0, float t1) {
    uint32_t y;
    asm("prmt.b32 %0, %1, %2, 0x6521;" : "=r"(y) : "f"(t0), "f"(t1));
    const uint32_t e = y & 0x7F807F80u;
    uint32_t uh, p;
    asm("lop3.b32 %0, %1, %2, 0x3F003F00, 0xBE;" : "=r"(uh) : "r"(y), "r"(e));
    asm("fma.rn.bf16x2 %0, %1, %2, %3;" : "=r"(p) : "r"(uh), "r"(y), "r"(e));
    return p;
}

__device__ __forceinline__ void at_load_chunk(uint32_t sbase, const __nv_bfloat16* KV, uint32_t bar0, int c) {
    const uint8_t* src = reinterpret_cast<const uint8_t*>(KV);
    const uint32_t off = c < 4 ? c * 16384 : 98304 + (c - 4) * 8192, bytes = c < 4 ? 16384 : 8192;
    mbar_expect_tx(bar0 + 8 * c, bytes + 4096);
    bulk_g2s(sbase + off, src + off, bytes, bar0 + 8 * c);
    bulk_g2s(sbase + 65536 + c * 4096, src + 65536 + c * 4096, 4096, bar0 + 8 * c);
}

__device__ __forceinline__ void at_store(const float* o, __nv_bfloat16* O, int row, int lane) {
    const float l0 = __shfl_sync(0xffffffffu, o[8], lane & ~3);
    const float l1 = __shfl_sync(0xffffffffu, o[10], lane & ~3);
    const float r0 = __fdividef(1.0f, l0), r1 = __fdividef(1.0f, l1);
    const int t = lane & 3;
    uint32_t* op = reinterpret_cast<uint32_t*>(O + (size_t)(row + (lane >> 2)) * 16);
    op[t] = pack_bf16(o[0] * r0, o[1] * r0);
    op[t + 4] = pack_bf16(o[4] * r0, o[5] * r0);
    op[64 + t] = pack_bf16(o[2] * r1, o[3] * r1);
    op[64 + t + 4] = pack_bf16(o[6] * r1, o[7] * r1);
}

__device__ __forceinline__ void mma16816(float* c, const uint32_t* a, uint32_t b0, uint32_t b1) {
    asm volatile("mma.sync.aligned.m16n8k16.row.col.f32.bf16.bf16.f32 {%0,%1,%2,%3}, {%4,%5,%6,%7}, {%8,%9}, {%0,%1,%2,%3};"
                 : "+f"(c[0]), "+f"(c[1]), "+f"(c[2]), "+f"(c[3]) : "r"(a[0]), "r"(a[1]), "r"(a[2]), "r"(a[3]), "r"(b0), "r"(b1));
}
__device__ __forceinline__ void attn_fallback(const __nv_bfloat16* Q, const __nv_bfloat16* KV, __nv_bfloat16* O, uint32_t sbase) {
    const int tid = threadIdx.x;
    const int lane = tid & 31, g = lane >> 2, t = lane & 3;
    const uint32_t* Kg = reinterpret_cast<const uint32_t*>(KV + 65536);
#pragma unroll 1
    for (int mt = 0; mt < 2; mt++) {
        const int row = blockIdx.x * 512 + (tid >> 7) * 128 + mt * 64 + ((tid >> 5) & 3) * 16;
        const uint32_t* qp = reinterpret_cast<const uint32_t*>(Q + (size_t)(row + g) * 16);
        const uint32_t q[4] = {qp[t], qp[64 + t], qp[t + 4], qp[64 + t + 4]};
        float o[12];
#pragma unroll
        for (int i = 0; i < 12; i++) o[i] = 0.f;
        float m0 = -INFINITY, m1 = -INFINITY;
#pragma unroll 1
        for (int kt = 0; kt < S_LEN / 16; kt++) {
            float s[8];
#pragma unroll
            for (int i = 0; i < 8; i++) s[i] = 0.f;
#pragma unroll
            for (int h = 0; h < 2; h++) {
                const uint32_t* kp = Kg + (kt * 2 + h) * 64 + g * 4 + t;
                mma16816(s + 4 * h, q, kp[0], kp[32]);
            }
            float x0 = fmaxf(fmaxf(s[0], s[1]), fmaxf(s[4], s[5])), x1 = fmaxf(fmaxf(s[2], s[3]), fmaxf(s[6], s[7]));
            x0 = fmaxf(x0, __shfl_xor_sync(0xffffffffu, x0, 1)); x0 = fmaxf(x0, __shfl_xor_sync(0xffffffffu, x0, 2));
            x1 = fmaxf(x1, __shfl_xor_sync(0xffffffffu, x1, 1)); x1 = fmaxf(x1, __shfl_xor_sync(0xffffffffu, x1, 2));
            x0 = fmaxf(x0, m0); x1 = fmaxf(x1, m1);
            const float f0 = ex2(m0 - x0), f1 = ex2(m1 - x1);
            m0 = x0; m1 = x1;
#pragma unroll
            for (int j = 0; j < 3; j++) { o[4 * j] *= f0; o[4 * j + 1] *= f0; o[4 * j + 2] *= f1; o[4 * j + 3] *= f1; }
            const uint32_t p[4] = {pack_bf16(ex2(s[0] - m0), ex2(s[1] - m0)), pack_bf16(ex2(s[2] - m1), ex2(s[3] - m1)),
                                   pack_bf16(ex2(s[4] - m0), ex2(s[5] - m0)), pack_bf16(ex2(s[6] - m1), ex2(s[7] - m1))};
#pragma unroll
            for (int j = 0; j < 3; j++) {
                const uint32_t base = sbase + (j == 0 ? kt * 512 : j == 1 ? 65536 + kt * 256 : AT_ONES) + (lane & 15) * 16;
                uint32_t b0, b1;
                asm volatile("ldmatrix.sync.aligned.m8n8.x2.trans.shared.b16 {%0,%1}, [%2];" : "=r"(b0), "=r"(b1) : "r"(base));
                mma16816(o + 4 * j, p, b0, b1);
            }
        }
        at_store(o, O, row, lane);
    }
}

__global__ void __launch_bounds__(640, 1)
k2_attn(const __grid_constant__ CUtensorMap tm_h, const __grid_constant__ CUtensorMap tm_w2,
        const __grid_constant__ CUtensorMap tm_o, const __grid_constant__ CUtensorMap tm_wo,
        const __grid_constant__ CUtensorMap tm_x, const __grid_constant__ CUtensorMap tm_g,
        const __grid_constant__ CUtensorMap tm_out,
        const __nv_bfloat16* __restrict__ Q, const __nv_bfloat16* __restrict__ KV, const float* __restrict__ kvmax,
        const __nv_bfloat16* __restrict__ b2, __nv_bfloat16* __restrict__ O, __nv_bfloat16* __restrict__ G,
        uint2* __restrict__ rowstat, uint2* __restrict__ colpart, int* syncp) {
    extern __shared__ __align__(1024) uint8_t smem_raw[];
    const uint32_t sbase = smem_u32(smem_raw);
    const uint32_t bar0 = sbase + AT_BAR, f2_full = bar0 + 64, f2_empty = f2_full + 32, bar_guard = f2_empty + 32, bar_first = bar_guard + 8, bar_w = bar_first + 8, sGuard = bar0 + 192;
    const int tid = threadIdx.x;
    const int wg = __shfl_sync(0xffffffffu, tid >> 7, 0);
    const int warp = (tid >> 5) & 3, lane = tid & 31;
    const int g = lane >> 2, t = lane & 3;
    if (tid == 0) DEV_STAMP(1, 0);
    if (tid == 0) {
        for (int i = 0; i < AT_NCHUNK; i++) mbar_init(bar0 + 8 * i, 1);
        for (int i = 0; i < F2_STAGES; i++) { mbar_init(f2_full + 8 * i, 1); mbar_init(f2_empty + 8 * i, 4); }
        mbar_init(bar_guard, 4);
        mbar_init(bar_first, 1);
        mbar_init(bar_w, 1);
        mbar_init_fence();
    }
    if (tid < 16) asm volatile("st.shared.v4.b32 [%0], {%1,%2,%2,%2};" ::"r"(sbase + AT_ONES + tid * 16), "r"(0x00003F80u), "r"(0u) : "memory");
    fence_proxy_async();
    __syncthreads();

    if (wg == 4) {
        const int rb = blockIdx.x >> 2, cb = blockIdx.x & 3;
        const uint32_t fb = sbase + F2_BASE;
        const bool leader = tid == 512;
        if (leader) {
#pragma unroll
            for (int s = 0; s < F2_STAGES; s++) {
                mbar_expect_tx(f2_full + 8 * s, F2_STAGE_BYTES);
                tma_load_2d(fb + s * F2_STAGE_BYTES + 8192, &tm_w2, cb * 128, s * 64, f2_full + 8 * s);
                tma_load_2d(fb + s * F2_STAGE_BYTES + 16384, &tm_w2, cb * 128 + 64, s * 64, f2_full + 8 * s);
            }
        }
        pdl_wait();
        mbar_wait(bar0, 0);
        if (leader) {
#pragma unroll
            for (int s = 0; s < F2_STAGES; s++) tma_load_2d(fb + s * F2_STAGE_BYTES, &tm_h, s * 64, rb * 64, f2_full + 8 * s);
        }
        {
            float km = fmaxf(fmaxf(kvmax[lane], kvmax[lane + 32]), fmaxf(kvmax[lane + 64], kvmax[lane + 96]));
            float vm = fmaxf(fmaxf(kvmax[128 + lane], kvmax[160 + lane]), fmaxf(kvmax[192 + lane], kvmax[224 + lane]));
            uint4 qv[4][2];
#pragma unroll
            for (int i = 0; i < 4; i++) {
                const uint4* qr = reinterpret_cast<const uint4*>(Q + (size_t)(blockIdx.x * 512 + warp * 128 + i * 16 + (lane >> 4) * 64 + (lane & 15)) * 16);
                qv[i][0] = qr[0]; qv[i][1] = qr[1];
            }
#pragma unroll
            for (int o = 16; o > 0; o >>= 1) { km = fmaxf(km, __shfl_xor_sync(0xffffffffu, km, o)); vm = fmaxf(vm, __shfl_xor_sync(0xffffffffu, vm, o)); }
#pragma unroll
            for (int i = 0; i < 4; i++) {
                const uint32_t qw[8] = {qv[i][0].x, qv[i][0].y, qv[i][0].z, qv[i][0].w, qv[i][1].x, qv[i][1].y, qv[i][1].z, qv[i][1].w};
                float qn = 0.f;
#pragma unroll
                for (int j = 0; j < 8; j++) qn += bf_lo(qw[j]) * bf_lo(qw[j]) + bf_hi(qw[j]) * bf_hi(qw[j]);
                const bool ok = (qn * km <= 3600.0f) && (vm <= 1.0e12f);
                const uint32_t bad = __any_sync(0xffffffffu, !ok);
                if (lane == 0) asm volatile("st.shared.u32 [%0], %1;" ::"r"(sGuard + (warp * 4 + i) * 4), "r"(bad) : "memory");
            }
            if (lane == 0) mbar_arrive(bar_guard);
        }
        __syncwarp();
        const uint64_t dA0 = make_desc(fb, 16, 1024, 1);
        const uint64_t dB0 = make_desc(fb + 8192, 8192, 1024, 1);
        float acc[64];
#pragma unroll
        for (int i = 0; i < 64; i++) asm volatile("mov.f32 %0, 0f00000000;" : "=f"(acc[i]));
#pragma unroll 1
        for (int ks = 0; ks < F2_NK; ks++) {
            const int s = ks % F2_STAGES;
            mbar_wait(f2_full + 8 * s, (ks / F2_STAGES) & 1);
            wg_fence();
#pragma unroll
            for (int kk = 0; kk < 4; kk++)
                wgmma_ss_n128_tb(acc, dA0 + (uint64_t)((s * F2_STAGE_BYTES + kk * 32) >> 4),
                                 dB0 + (uint64_t)((s * F2_STAGE_BYTES + kk * 2048) >> 4), 1);
            wg_commit();
            wg_wait<1>();
            if (ks > 0 && ks - 1 + F2_STAGES < F2_NK) {
                const int ps = (ks - 1) % F2_STAGES, k0 = (ks - 1 + F2_STAGES) * 64;
                if (lane == 0) mbar_arrive(f2_empty + 8 * ps);
                if (leader) {
                    mbar_wait(f2_empty + 8 * ps, ((ks - 1) / F2_STAGES) & 1);
                    mbar_expect_tx(f2_full + 8 * ps, F2_STAGE_BYTES);
                    tma_load_2d(fb + ps * F2_STAGE_BYTES, &tm_h, k0, rb * 64, f2_full + 8 * ps);
                    tma_load_2d(fb + ps * F2_STAGE_BYTES + 8192, &tm_w2, cb * 128, k0, f2_full + 8 * ps);
                    tma_load_2d(fb + ps * F2_STAGE_BYTES + 16384, &tm_w2, cb * 128 + 64, k0, f2_full + 8 * ps);
                }
                __syncwarp();
            }
        }
        wg_wait<0>();
        fence_regs<64>(acc);
        uint32_t* gp = reinterpret_cast<uint32_t*>(G + (size_t)(rb * 64 + warp * 16 + g) * D_MODEL + cb * 128) + t;
#pragma unroll
        for (int j = 0; j < 16; j++) {
            const uint32_t bb = __ldg(reinterpret_cast<const uint32_t*>(b2 + cb * 128 + j * 8) + t);
            const float b0 = bf_lo(bb), b1v = bf_hi(bb);
            const float z0 = acc[4 * j] + b0, z1 = acc[4 * j + 1] + b1v, z2 = acc[4 * j + 2] + b0, z3 = acc[4 * j + 3] + b1v;
            gp[j * 4] = pack_bf16(__fdividef(z0, 1.0f + __expf(-z0)), __fdividef(z1, 1.0f + __expf(-z1)));
            gp[j * 4 + 8 * (D_MODEL / 2)] = pack_bf16(__fdividef(z2, 1.0f + __expf(-z2)), __fdividef(z3, 1.0f + __expf(-z3)));
        }
        if (leader) DEV_STAMP(1, 5);
        named_bar_sync(3, 128);
        const int rb2 = blockIdx.x >> 3, cb2 = blockIdx.x & 7;
        const uint32_t sX = fb + 65536, sG = sX + 16384;
        if (leader) {
            signal_add(syncp + 128 + blockIdx.x);
            mbar_expect_tx(bar_w, 65536 + 32768);
#pragma unroll
            for (int s = 0; s < 8; s++) tma_load_2d(fb + s * 8192, &tm_wo, cb2 * 64, s * 64, bar_w);
            tma_load_2d(sX, &tm_x, cb2 * 64, rb2 * 128, bar_w);
            wait_count(syncp + 128 + rb2 * 8 + (cb2 >> 1), 1);
            wait_count(syncp + 128 + rb2 * 8 + 4 + (cb2 >> 1), 1);
            tma_load_2d(sG, &tm_g, cb2 * 64, rb2 * 128, bar_w);
            wait_count(syncp + rb2, 8);
            DEV_STAMP(2, 1);
#pragma unroll
            for (int s = 0; s < 8; s++) {
                mbar_expect_tx(bar0 + 8 * s, 16384);
                tma_load_2d(sbase + s * 16384, &tm_o, s * 64, rb2 * 128, bar0 + 8 * s);
            }
        }
        __syncwarp();
#pragma unroll
        for (int i = 0; i < 64; i++) asm volatile("mov.f32 %0, 0f00000000;" : "=f"(acc[i]));
        mbar_wait(bar_w, 0);
        {
            const uint64_t oA = make_desc(sbase, 16, 1024, 1), oB = make_desc(fb, 8192, 1024, 1);
#pragma unroll 1
            for (int ks = 0; ks < 8; ks++) {
                mbar_wait(bar0 + 8 * ks, 1);
                wg_fence();
#pragma unroll
                for (int kk = 0; kk < 4; kk++) {
                    wgmma_ss_n64_tb(acc, oA + (uint64_t)((ks * 16384 + kk * 32) >> 4), oB + (uint64_t)((ks * 8192 + kk * 2048) >> 4), 1);
                    wgmma_ss_n64_tb(acc + 32, oA + (uint64_t)((ks * 16384 + 8192 + kk * 32) >> 4), oB + (uint64_t)((ks * 8192 + kk * 2048) >> 4), 1);
                }
                wg_commit();
            }
            wg_wait<0>();
            fence_regs<64>(acc);
        }
        if (leader) DEV_STAMP(2, 2);
#pragma unroll
        for (int m = 0; m < 2; m++) {
#pragma unroll
            for (int j = 0; j < 8; j++) {
#pragma unroll
                for (int h = 0; h < 2; h++) {
                    const int row = m * 64 + warp * 16 + g + h * 8;
                    const uint32_t off = row * 128 + ((j ^ (row & 7)) << 4) + t * 4;
                    uint32_t xv, gv;
                    asm volatile("ld.shared.b32 %0, [%1];" : "=r"(xv) : "r"(sX + off) : "memory");
                    asm volatile("ld.shared.b32 %0, [%1];" : "=r"(gv) : "r"(sG + off) : "memory");
                    const uint32_t ov = pack_bf16(fmaf(acc[m * 32 + 4 * j + 2 * h], bf_lo(gv), bf_lo(xv)),
                                                  fmaf(acc[m * 32 + 4 * j + 2 * h + 1], bf_hi(gv), bf_hi(xv)));
                    asm volatile("st.shared.b32 [%0], %1;" ::"r"(sX + off), "r"(ov) : "memory");
                }
            }
            fence_proxy_async();
            __syncwarp();
            if (lane == 0) {
                tma_store_2d(&tm_out, sX + (m * 4 + warp) * 2048, cb2 * 64, rb2 * 128 + m * 64 + warp * 16);
                tma_store_commit();
            }
        }
        if (leader) DEV_STAMP(2, 3);
        if (lane == 0) tma_store_wait();
        if (leader) DEV_STAMP(2, 4);
        return;
    }

    pdl_wait();
    if (tid == 0) DEV_STAMP(1, 1);
    if (tid == 0) {
        const uint8_t* src = reinterpret_cast<const uint8_t*>(KV);
        mbar_expect_tx(bar_first, 4096);
        bulk_g2s(sbase, src, 4096, bar_first);
        mbar_expect_tx(bar0, 12288 + 4096);
        bulk_g2s(sbase + 4096, src + 4096, 12288, bar0);
        bulk_g2s(sbase + 65536, src + 65536, 4096, bar0);
        at_load_chunk(sbase, KV, bar0, 1); at_load_chunk(sbase, KV, bar0, 2);
    }
    if (tid >= 128 && tid < 288) colpart[blockIdx.x * 160 + tid - 128] = make_uint2(NOT_READY, NOT_READY);
    if (tid >= 288 && tid < 304) rowstat[blockIdx.x * 16 + tid - 288] = make_uint2(NOT_READY, NOT_READY);
    const int rowA = blockIdx.x * 512 + wg * 128 + warp * 16;
    const uint32_t* qp = reinterpret_cast<const uint32_t*>(Q + (size_t)(rowA + g) * 16);
    const uint32_t lo0 = ((sbase & 0x3FFFF) >> 4) | (8u << 16);

#define AT_EXP(P) _Pragma("unroll") for (int i = 0; i < AT_KT / 4; i++) {                       \
                if ((AT_SWMASK >> (i & 15)) & 1) P[i] = exp2_pair_alu(s[2 * i], s[2 * i + 1]);  \
                else P[i] = pack_bf16(ex2(s[2 * i]), ex2(s[2 * i + 1])); }
#define AT_PV(P, st) _Pragma("unroll") for (int j = 0; j < AT_KT / 16; j++)                     \
                wgmma_pv(o, P[4 * j], P[4 * j + 1], P[4 * j + 2], P[4 * j + 3],                 \
                         desc64(vlo + ((st) * 4 + j) * 32, vhi - ((st) * 4 + j) * 16));
#define AT_PIPE 2
#define AT_EXPH(P, h) _Pragma("unroll") for (int i = (h) * 8; i < (h) * 8 + 8; i++) {           \
                if ((AT_SWMASK >> (i & 15)) & 1) P[i] = exp2_pair_alu(s[2 * i], s[2 * i + 1]);  \
                else P[i] = pack_bf16(ex2(s[2 * i]), ex2(s[2 * i + 1])); }
#define AT_PVH(P, st, h) _Pragma("unroll") for (int j = (h) * 2; j < (h) * 2 + 2; j++)          \
                wgmma_pv(o, P[4 * j], P[4 * j + 1], P[4 * j + 2], P[4 * j + 3],                 \
                         desc64(vlo + ((st) * 4 + j) * 32, vhi - ((st) * 4 + j) * 16));
#define AT_STEP(st, PC, PN, klo, khi) {                                                         \
                wg_wait<0>();                                                                   \
                fence_regs<AT_KT / 2>(s);                                                       \
                AT_EXPH(p0, 0);                                                                 \
                wg_fence();                                                                     \
                AT_PVH(p0, st, 0);                                                              \
                wg_commit();                                                                    \
                AT_EXPH(p0, 1);                                                                 \
                if (st == AT_SPC - 1 && mt == 0) mbar_wait(bar0 + 8 * (c + 1), 0);              \
                wg_wait<0>();                                                                   \
                wg_fence();                                                                     \
                wgmma_qk_acc_n64(s, q, desc64(klo, khi));                                       \
                AT_PVH(p0, st, 1);                                                              \
                wg_commit(); }

#pragma unroll 1
    for (int mt = 0; mt < 2; mt++) {
        uint32_t q[4];
        q[0] = qp[mt * 512 + t]; q[2] = qp[mt * 512 + t + 4]; q[1] = qp[mt * 512 + 64 + t]; q[3] = qp[mt * 512 + 64 + t + 4];
        float o[12];
#pragma unroll
        for (int i = 0; i < 12; i++) asm volatile("mov.f32 %0, 0f00000000;" : "=f"(o[i]));
        float s[AT_KT / 2];
        uint32_t p0[AT_KT / 4], p1[AT_KT / 4];
        (void)p1;
#pragma unroll
        for (int i = 0; i < AT_KT / 2; i++) {
            if ((AT_SWMASK >> ((i >> 1) & 15)) & 1) asm volatile("mov.f32 %0, %1;" : "=f"(s[i]) : "f"(AT_MAGIC));
            else asm volatile("mov.f32 %0, 0f00000000;" : "=f"(s[i]));
        }
        if (mt == 0) mbar_wait(K2_MINI ? bar_first : bar0, 0);
        if (tid == 0) DEV_STAMP(1, 2 + mt);
        uint32_t klo = lo0 + 16, vlo = lo0, vhi = 4096;
        wg_fence();
        wgmma_qk_acc_n64(s, q, desc64(klo, 32));
        wg_commit();
        if (K2_MINI && mt == 0) mbar_wait(bar0, 0);
        uint32_t kst = 256, khi = 32;
#pragma unroll 1
        for (int c = 0; c < AT_NCHUNK - 1; c++) {
            if (tid == 0 && mt == 0 && c + 3 < AT_NCHUNK) at_load_chunk(sbase, KV, bar0, c + 3);
            AT_STEP(0, p0, p1, klo + kst, khi); AT_STEP(1, p1, p0, klo + 2 * kst, khi); AT_STEP(2, p0, p1, klo + 3 * kst, khi);
            if (c == 3) { klo = lo0 + (98304 >> 4); kst = 128; khi = 16; } else klo += 4 * kst;
            AT_STEP(3, p1, p0, klo, khi);
            vlo += 512; vhi -= 256;
        }
        {
            const int c = 0; (void)c;
            AT_STEP(0, p0, p1, klo + 128, 16); AT_STEP(1, p1, p0, klo + 256, 16); AT_STEP(2, p0, p1, klo + 384, 16);
            wg_wait<0>();
            fence_regs<AT_KT / 2>(s);
            AT_EXP(p0);
            wg_fence();
            AT_PV(p0, 3);
            wg_commit();
            wg_wait<0>();
            fence_regs<12>(o);
        }
        at_store(o, O, rowA + mt * 64, lane);
    }
    if (tid == 0) DEV_STAMP(1, 4);

    mbar_wait(bar_guard, 0);
    uint32_t bad;
    asm volatile("ld.shared.u32 %0, [%1];" : "=r"(bad) : "r"(sGuard + (tid >> 5) * 4) : "memory");
    if (__any_sync(0xffffffffu, bad != 0)) attn_fallback(Q, KV, O, sbase);
    named_bar_sync(2, 512);
    if (tid == 0) signal_add(syncp + (blockIdx.x >> 3));
}

typedef CUresult (*EncodeFn)(CUtensorMap*, CUtensorMapDataType, cuuint32_t, void*, const cuuint64_t*, const cuuint64_t*,
                             const cuuint32_t*, const cuuint32_t*, CUtensorMapInterleave, CUtensorMapSwizzle,
                             CUtensorMapL2promotion, CUtensorMapFloatOOBfill);

struct HostState {
    bool ready;
    const void* key[11];
    CUtensorMap wq, wk, wv, w1, qo, ho, hi, oi, w2, wo, xi, gi, out;
    void *pQ, *pKV, *pH, *pO, *pMax, *pRow, *pCol, *pFlag, *pG;
};
HostState g_hs;

void make_map(EncodeFn fn, CUtensorMap* m, const void* ptr, uint64_t inner, uint64_t outer, uint32_t box_in, uint32_t box_out) {
    cuuint64_t dims[2] = {inner, outer};
    cuuint64_t strides[1] = {inner * 2};
    cuuint32_t box[2] = {box_in, box_out};
    cuuint32_t es[2] = {1, 1};
    fn(m, CU_TENSOR_MAP_DATA_TYPE_BFLOAT16, 2, const_cast<void*>(ptr), dims, strides, box, es, CU_TENSOR_MAP_INTERLEAVE_NONE,
       CU_TENSOR_MAP_SWIZZLE_128B, CU_TENSOR_MAP_L2_PROMOTION_L2_256B, CU_TENSOR_MAP_FLOAT_OOB_FILL_NONE);
}

template <typename... KArgs, typename... Args>
void launch(void (*kern)(KArgs...), int grid, int block, int smem, bool pdl, int cluster, Args... args) {
    cudaLaunchConfig_t cfg = {};
    cfg.gridDim = dim3(grid); cfg.blockDim = dim3(block); cfg.dynamicSmemBytes = smem; cfg.stream = cudaStreamPerThread;
    cudaLaunchAttribute at[2];
    int n = 0;
    if (pdl) { at[n].id = cudaLaunchAttributeProgrammaticStreamSerialization; at[n].val.programmaticStreamSerializationAllowed = 1; n++; }
    if (cluster > 1) { at[n].id = cudaLaunchAttributeClusterDimension; at[n].val.clusterDim.x = cluster; at[n].val.clusterDim.y = 1; at[n].val.clusterDim.z = 1; n++; }
    cfg.attrs = at; cfg.numAttrs = n;
    cudaLaunchKernelEx(&cfg, kern, KArgs(args)...);
}

}

extern "C" void kernel_launch(void* const* d_in, const int* in_sizes, int n_in, void* d_out, int out_size) {
    (void)in_sizes; (void)n_in; (void)out_size;
    HostState& hs = g_hs;
    bool same = hs.ready;
    for (int i = 0; i < 10 && same; i++) same = hs.key[i] == d_in[i];
    same = same && hs.key[10] == d_out;
    if (!same) {
        void* fp = nullptr;
        cudaDriverEntryPointQueryResult qr;
        cudaGetDriverEntryPoint("cuTensorMapEncodeTiled", &fp, cudaEnableDefault, &qr);
        EncodeFn fn = (EncodeFn)fp;
        cudaGetSymbolAddress(&hs.pQ, g_Q); cudaGetSymbolAddress(&hs.pKV, g_KV); cudaGetSymbolAddress(&hs.pH, g_H);
        cudaGetSymbolAddress(&hs.pO, g_O); cudaGetSymbolAddress(&hs.pMax, g_kvmax);
        cudaGetSymbolAddress(&hs.pRow, g_rowstat); cudaGetSymbolAddress(&hs.pCol, g_colpart); cudaGetSymbolAddress(&hs.pG, g_G); cudaGetSymbolAddress(&hs.pFlag, g_sync);
        make_map(fn, &hs.wq, d_in[1], 512, 512, 64, 64);
        make_map(fn, &hs.wk, d_in[2], 16, 512, 64, 64);
        make_map(fn, &hs.wv, d_in[3], 16, 512, 64, 64);
        make_map(fn, &hs.w1, d_in[6], F_DIM, 512, 64, 64);
        make_map(fn, &hs.qo, hs.pQ, 512, S_LEN, 64, 16);
        make_map(fn, &hs.ho, hs.pH, F_DIM, S_LEN, 64, 16);
        make_map(fn, &hs.hi, hs.pH, F_DIM, S_LEN, 64, 64);
        make_map(fn, &hs.gi, hs.pG, 512, S_LEN, 64, 128);
        make_map(fn, &hs.oi, hs.pO, 512, S_LEN, 64, 128);
        make_map(fn, &hs.w2, d_in[8], 512, F_DIM, 64, 64);
        make_map(fn, &hs.wo, d_in[4], 512, 512, 64, 64);
        make_map(fn, &hs.xi, d_in[0], 512, S_LEN, 64, 128);
        make_map(fn, &hs.out, d_out, 512, S_LEN, 64, 16);
        cudaFuncSetAttribute(k1_proj, cudaFuncAttributeMaxDynamicSharedMemorySize, K1_SMEM);
        cudaFuncSetAttribute(k2_attn, cudaFuncAttributeMaxDynamicSharedMemorySize, AT_SMEM);
        for (int i = 0; i < 10; i++) hs.key[i] = d_in[i];
        hs.key[10] = d_out;
        hs.ready = true;
    }
    launch(k1_proj, 128, 384, K1_SMEM, false, 2, hs.xi, hs.wq, hs.wk, hs.wv, hs.w1, hs.qo, hs.ho, (const __nv_bfloat16*)d_in[0],
           (const __nv_bfloat16*)d_in[7], (float2*)hs.pRow, (float*)hs.pCol, (int*)hs.pFlag, (__nv_bfloat16*)hs.pKV, (float*)hs.pMax);
    launch(k2_attn, 128, 640, AT_SMEM, true, 1, hs.hi, hs.w2, hs.oi, hs.wo, hs.xi, hs.gi, hs.out, (const __nv_bfloat16*)hs.pQ, (const __nv_bfloat16*)hs.pKV,
           (const float*)hs.pMax, (const __nv_bfloat16*)d_in[9], (__nv_bfloat16*)hs.pO, (__nv_bfloat16*)hs.pG, (uint2*)hs.pRow, (uint2*)hs.pCol, (int*)hs.pFlag);
}
```

```cpp
#include <cuda_runtime.h>
#include <cuda_bf16.h>
#include <cuda.h>
#include <stdint.h>

namespace {

constexpr int S_LEN = 2048, D_MODEL = 512, F_DIM = 1792;

__device__ __align__(1024) __nv_bfloat16 g_Q[S_LEN * D_MODEL];
__device__ __align__(1024) __nv_bfloat16 g_KV[6 * S_LEN * 8];
__device__ __align__(1024) __nv_bfloat16 g_G[S_LEN * D_MODEL];
__device__ __align__(1024) __nv_bfloat16 g_H[S_LEN * F_DIM];
__device__ __align__(1024) __nv_bfloat16 g_O[S_LEN * D_MODEL];
__device__ __align__(1024) float g_kvmax[256];
__device__ __align__(1024) float2 g_rowstat[S_LEN];
__device__ __align__(1024) float g_colpart[8 * 16 * 320];

#define DEV_STAMP(k, e) do {} while (0)
__device__ __forceinline__ uint32_t smem_u32(const void* p) { return (uint32_t)__cvta_generic_to_shared(p); }
__device__ __forceinline__ void wg_fence() { asm volatile("wgmma.fence.sync.aligned;" ::: "memory"); }
__device__ __forceinline__ void wg_commit() { asm volatile("wgmma.commit_group.sync.aligned;" ::: "memory"); }
template <int N> __device__ __forceinline__ void wg_wait() { asm volatile("wgmma.wait_group.sync.aligned %0;" ::"n"(N) : "memory"); }
template <int N> __device__ __forceinline__ void fence_regs(float* r) {
#pragma unroll
    for (int i = 0; i < N; i++) asm volatile("" : "+f"(r[i])::"memory");
}
__device__ __forceinline__ void fence_proxy_async() { asm volatile("fence.proxy.async.shared::cta;" ::: "memory"); }
__device__ __forceinline__ void mbar_init(uint32_t bar, int cnt) { asm volatile("mbarrier.init.shared::cta.b64 [%0], %1;" ::"r"(bar), "r"(cnt) : "memory"); }
__device__ __forceinline__ void mbar_init_fence() { asm volatile("fence.mbarrier_init.release.cluster;" ::: "memory"); }
__device__ __forceinline__ void mbar_expect_tx(uint32_t bar, uint32_t bytes) {
    asm volatile("mbarrier.arrive.expect_tx.shared::cta.b64 _, [%0], %1;" ::"r"(bar), "r"(bytes) : "memory");
}
__device__ __forceinline__ void mbar_arrive(uint32_t bar) { asm volatile("mbarrier.arrive.shared::cta.b64 _, [%0];" ::"r"(bar) : "memory"); }
__device__ __forceinline__ bool mbar_try(uint32_t bar, uint32_t parity) {
    uint32_t ok;
    asm volatile("{\n.reg .pred p;\nmbarrier.try_wait.parity.shared::cta.b64 p, [%1], %2;\nselp.u32 %0, 1, 0, p;\n}\n"
                 : "=r"(ok) : "r"(bar), "r"(parity) : "memory");
    return ok != 0;
}
__device__ __forceinline__ void mbar_wait(uint32_t bar, uint32_t parity) {
    if (mbar_try(bar, parity)) return;
    const long long t0 = clock64();
#pragma unroll 1
    while (!mbar_try(bar, parity)) {
        if (clock64() - t0 > 20000000ll) {
            break;
        }
    }
}
__device__ __forceinline__ void bulk_g2s(uint32_t dst, const void* src, uint32_t bytes, uint32_t bar) {
    asm volatile("cp.async.bulk.shared::cluster.global.mbarrier::complete_tx::bytes [%0], [%1], %2, [%3];"
                 ::"r"(dst), "l"(src), "r"(bytes), "r"(bar) : "memory");
}
__device__ __forceinline__ void tma_load_2d(uint32_t dst, const CUtensorMap* tm, int c0, int c1, uint32_t bar) {
    asm volatile("cp.async.bulk.tensor.2d.shared::cluster.global.mbarrier::complete_tx::bytes [%0], [%1, {%3, %4}], [%2];"
                 ::"r"(dst), "l"((uint64_t)tm), "r"(bar), "r"(c0), "r"(c1) : "memory");
}
__device__ __forceinline__ void tma_load_2d_mc(uint32_t dst, const CUtensorMap* tm, int c0, int c1, uint32_t bar, uint16_t mask) {
    asm volatile("cp.async.bulk.tensor.2d.shared::cluster.global.mbarrier::complete_tx::bytes.multicast::cluster [%0], [%1, {%3, %4}], [%2], %5;"
                 ::"r"(dst), "l"((uint64_t)tm), "r"(bar), "r"(c0), "r"(c1), "h"(mask) : "memory");
}
__device__ __forceinline__ void mbar_arrive_remote(uint32_t bar, uint32_t cta) {
    asm volatile("{\n.reg .b32 ra;\nmapa.shared::cluster.u32 ra, %0, %1;\nmbarrier.arrive.shared::cluster.b64 _, [ra];\n}\n"
                 ::"r"(bar), "r"(cta) : "memory");
}
__device__ __forceinline__ uint2 ld_relaxed_v2(const void* p) {
    uint2 v; asm volatile("ld.relaxed.gpu.global.v2.b32 {%0,%1}, [%2];" : "=r"(v.x), "=r"(v.y) : "l"(p) : "memory"); return v;
}
constexpr uint32_t NOT_READY = 0u;
__device__ __forceinline__ float xch_enc(float v) { return __uint_as_float((v == 0.f ? 0u : __float_as_uint(v)) ^ 0x80000000u); }
__device__ __forceinline__ float xch_dec(uint32_t u) { return __uint_as_float(u ^ 0x80000000u); }
__device__ __forceinline__ void tma_store_2d(const CUtensorMap* tm, uint32_t src, int c0, int c1) {
    asm volatile("cp.async.bulk.tensor.2d.global.shared::cta.bulk_group [%0, {%2, %3}], [%1];"
                 ::"l"((uint64_t)tm), "r"(src), "r"(c0), "r"(c1) : "memory");
}
__device__ __forceinline__ void tma_store_commit() { asm volatile("cp.async.bulk.commit_group;" ::: "memory"); }
__device__ __forceinline__ void tma_store_wait() { asm volatile("cp.async.bulk.wait_group 0;" ::: "memory"); }
__device__ __forceinline__ void tma_prefetch_desc(const CUtensorMap* tm) { asm volatile("prefetch.tensormap [%0];" ::"l"((uint64_t)tm) : "memory"); }
__device__ __forceinline__ void named_bar_sync(int id, int n) { asm volatile("bar.sync %0, %1;" ::"r"(id), "r"(n) : "memory"); }
__device__ __forceinline__ void pdl_wait() { asm volatile("griddepcontrol.wait;" ::: "memory"); }
__device__ __forceinline__ void pdl_launch() { asm volatile("griddepcontrol.launch_dependents;" ::: "memory"); }
template <int N> __device__ __forceinline__ void reg_alloc() { asm volatile("setmaxnreg.inc.sync.aligned.u32 %0;" ::"n"(N)); }
template <int N> __device__ __forceinline__ void reg_dealloc() { asm volatile("setmaxnreg.dec.sync.aligned.u32 %0;" ::"n"(N)); }
__device__ __forceinline__ float ex2(float x) { float y; asm("ex2.approx.ftz.f32 %0, %1;" : "=f"(y) : "f"(x)); return y; }
__device__ __forceinline__ uint32_t pack_bf16(float lo, float hi) {
    uint32_t r; asm("cvt.rn.bf16x2.f32 %0, %1, %2;" : "=r"(r) : "f"(hi), "f"(lo)); return r;
}
__device__ __forceinline__ uint32_t pack_bf16_relu(float lo, float hi) {
    uint32_t r; asm("cvt.rn.relu.bf16x2.f32 %0, %1, %2;" : "=r"(r) : "f"(hi), "f"(lo)); return r;
}
__device__ __forceinline__ uint32_t mul_bf16x2(uint32_t a, uint32_t b) {
    uint32_t r; asm("mul.rn.bf16x2 %0, %1, %2;" : "=r"(r) : "r"(a), "r"(b)); return r;
}
__device__ __forceinline__ float bf_lo(uint32_t v) { return __uint_as_float(v << 16); }
__device__ __forceinline__ float bf_hi(uint32_t v) { return __uint_as_float(v & 0xFFFF0000u); }
__device__ __forceinline__ void stmatrix_x4(uint32_t addr, uint32_t r0, uint32_t r1, uint32_t r2, uint32_t r3) {
    asm volatile("stmatrix.sync.aligned.m8n8.x4.shared.b16 [%0], {%1,%2,%3,%4};" ::"r"(addr), "r"(r0), "r"(r1), "r"(r2), "r"(r3) : "memory");
}
__device__ __forceinline__ uint64_t make_desc(uint32_t addr, uint32_t lbo, uint32_t sbo, uint32_t swz) {
    return (uint64_t)((addr & 0x3FFFF) >> 4) | ((uint64_t)(lbo >> 4) << 16) | ((uint64_t)(sbo >> 4) << 32) | ((uint64_t)swz << 62);
}

__device__ __forceinline__ uint64_t desc64(uint32_t lo, uint32_t hi) {
    uint64_t d; asm("mov.b64 %0, {%1, %2};" : "=l"(d) : "r"(lo), "r"(hi)); return d;
}

__device__ __forceinline__ void wgmma_ss_n256_tb(float* d, uint64_t descA, uint64_t descB, int scaleD) {
    asm volatile("{\n.reg .pred p;\nsetp.ne.b32 p, %130, 0;\n"
      "wgmma.mma_async.sync.aligned.m64n256k16.f32.bf16.bf16 {%0,%1,%2,%3,%4,%5,%6,%7,%8,%9,%10,%11,%12,%13,%14,%15,%16,%17,%18,%19,%20,%21,%22,%23,%24,%25,%26,%27,%28,%29,%30,%31,%32,%33,%34,%35,%36,%37,%38,%39,%40,%41,%42,%43,%44,%45,%46,%47,%48,%49,%50,%51,%52,%53,%54,%55,%56,%57,%58,%59,%60,%61,%62,%63,%64,%65,%66,%67,%68,%69,%70,%71,%72,%73,%74,%75,%76,%77,%78,%79,%80,%81,%82,%83,%84,%85,%86,%87,%88,%89,%90,%91,%92,%93,%94,%95,%96,%97,%98,%99,%100,%101,%102,%103,%104,%105,%106,%107,%108,%109,%110,%111,%112,%113,%114,%115,%116,%117,%118,%119,%120,%121,%122,%123,%124,%125,%126,%127}, %128, %129, p, 1, 1, 0, 1;\n}\n"
      : "+f"(d[0]), "+f"(d[1]), "+f"(d[2]), "+f"(d[3]), "+f"(d[4]), "+f"(d[5]), "+f"(d[6]), "+f"(d[7]), "+f"(d[8]), "+f"(d[9]), "+f"(d[10]), "+f"(d[11]), "+f"(d[12]), "+f"(d[13]), "+f"(d[14]), "+f"(d[15]), "+f"(d[16]), "+f"(d[17]), "+f"(d[18]), "+f"(d[19]), "+f"(d[20]), "+f"(d[21]), "+f"(d[22]), "+f"(d[23]), "+f"(d[24]), "+f"(d[25]), "+f"(d[26]), "+f"(d[27]), "+f"(d[28]), "+f"(d[29]), "+f"(d[30]), "+f"(d[31]), "+f"(d[32]), "+f"(d[33]), "+f"(d[34]), "+f"(d[35]), "+f"(d[36]), "+f"(d[37]), "+f"(d[38]), "+f"(d[39]), "+f"(d[40]), "+f"(d[41]), "+f"(d[42]), "+f"(d[43]), "+f"(d[44]), "+f"(d[45]), "+f"(d[46]), "+f"(d[47]), "+f"(d[48]), "+f"(d[49]), "+f"(d[50]), "+f"(d[51]), "+f"(d[52]), "+f"(d[53]), "+f"(d[54]), "+f"(d[55]), "+f"(d[56]), "+f"(d[57]), "+f"(d[58]), "+f"(d[59]), "+f"(d[60]), "+f"(d[61]), "+f"(d[62]), "+f"(d[63]), "+f"(d[64]), "+f"(d[65]), "+f"(d[66]), "+f"(d[67]), "+f"(d[68]), "+f"(d[69]), "+f"(d[70]), "+f"(d[71]), "+f"(d[72]), "+f"(d[73]), "+f"(d[74]), "+f"(d[75]), "+f"(d[76]), "+f"(d[77]), "+f"(d[78]), "+f"(d[79]), "+f"(d[80]), "+f"(d[81]), "+f"(d[82]), "+f"(d[83]), "+f"(d[84]), "+f"(d[85]), "+f"(d[86]), "+f"(d[87]), "+f"(d[88]), "+f"(d[89]), "+f"(d[90]), "+f"(d[91]), "+f"(d[92]), "+f"(d[93]), "+f"(d[94]), "+f"(d[95]), "+f"(d[96]), "+f"(d[97]), "+f"(d[98]), "+f"(d[99]), "+f"(d[100]), "+f"(d[101]), "+f"(d[102]), "+f"(d[103]), "+f"(d[104]), "+f"(d[105]), "+f"(d[106]), "+f"(d[107]), "+f"(d[108]), "+f"(d[109]), "+f"(d[110]), "+f"(d[111]), "+f"(d[112]), "+f"(d[113]), "+f"(d[114]), "+f"(d[115]), "+f"(d[116]), "+f"(d[117]), "+f"(d[118]), "+f"(d[119]), "+f"(d[120]), "+f"(d[121]), "+f"(d[122]), "+f"(d[123]), "+f"(d[124]), "+f"(d[125]), "+f"(d[126]), "+f"(d[127])
      : "l"(descA), "l"(descB), "r"(scaleD));
}
__device__ __forceinline__ void wgmma_ss_n128_tb(float* d, uint64_t descA, uint64_t descB, int scaleD) {
    asm volatile("{\n.reg .pred p;\nsetp.ne.b32 p, %66, 0;\n"
      "wgmma.mma_async.sync.aligned.m64n128k16.f32.bf16.bf16 {%0,%1,%2,%3,%4,%5,%6,%7,%8,%9,%10,%11,%12,%13,%14,%15,%16,%17,%18,%19,%20,%21,%22,%23,%24,%25,%26,%27,%28,%29,%30,%31,%32,%33,%34,%35,%36,%37,%38,%39,%40,%41,%42,%43,%44,%45,%46,%47,%48,%49,%50,%51,%52,%53,%54,%55,%56,%57,%58,%59,%60,%61,%62,%63}, %64, %65, p, 1, 1, 0, 1;\n}\n"
      : "+f"(d[0]), "+f"(d[1]), "+f"(d[2]), "+f"(d[3]), "+f"(d[4]), "+f"(d[5]), "+f"(d[6]), "+f"(d[7]), "+f"(d[8]), "+f"(d[9]), "+f"(d[10]), "+f"(d[11]), "+f"(d[12]), "+f"(d[13]), "+f"(d[14]), "+f"(d[15]), "+f"(d[16]), "+f"(d[17]), "+f"(d[18]), "+f"(d[19]), "+f"(d[20]), "+f"(d[21]), "+f"(d[22]), "+f"(d[23]), "+f"(d[24]), "+f"(d[25]), "+f"(d[26]), "+f"(d[27]), "+f"(d[28]), "+f"(d[29]), "+f"(d[30]), "+f"(d[31]), "+f"(d[32]), "+f"(d[33]), "+f"(d[34]), "+f"(d[35]), "+f"(d[36]), "+f"(d[37]), "+f"(d[38]), "+f"(d[39]), "+f"(d[40]), "+f"(d[41]), "+f"(d[42]), "+f"(d[43]), "+f"(d[44]), "+f"(d[45]), "+f"(d[46]), "+f"(d[47]), "+f"(d[48]), "+f"(d[49]), "+f"(d[50]), "+f"(d[51]), "+f"(d[52]), "+f"(d[53]), "+f"(d[54]), "+f"(d[55]), "+f"(d[56]), "+f"(d[57]), "+f"(d[58]), "+f"(d[59]), "+f"(d[60]), "+f"(d[61]), "+f"(d[62]), "+f"(d[63])
      : "l"(descA), "l"(descB), "r"(scaleD));
}
__device__ __forceinline__ void wgmma_ss_n64_tb(float* d, uint64_t descA, uint64_t descB, int scaleD) {
    asm volatile("{\n.reg .pred p;\nsetp.ne.b32 p, %34, 0;\n"
      "wgmma.mma_async.sync.aligned.m64n64k16.f32.bf16.bf16 {%0,%1,%2,%3,%4,%5,%6,%7,%8,%9,%10,%11,%12,%13,%14,%15,%16,%17,%18,%19,%20,%21,%22,%23,%24,%25,%26,%27,%28,%29,%30,%31}, %32, %33, p, 1, 1, 0, 1;\n}\n"
      : "+f"(d[0]), "+f"(d[1]), "+f"(d[2]), "+f"(d[3]), "+f"(d[4]), "+f"(d[5]), "+f"(d[6]), "+f"(d[7]), "+f"(d[8]), "+f"(d[9]), "+f"(d[10]), "+f"(d[11]), "+f"(d[12]), "+f"(d[13]), "+f"(d[14]), "+f"(d[15]), "+f"(d[16]), "+f"(d[17]), "+f"(d[18]), "+f"(d[19]), "+f"(d[20]), "+f"(d[21]), "+f"(d[22]), "+f"(d[23]), "+f"(d[24]), "+f"(d[25]), "+f"(d[26]), "+f"(d[27]), "+f"(d[28]), "+f"(d[29]), "+f"(d[30]), "+f"(d[31])
      : "l"(descA), "l"(descB), "r"(scaleD));
}
__device__ __forceinline__ void wgmma_qk_acc_n64(float* d, const uint32_t* a, uint64_t descB) {
    asm volatile("wgmma.mma_async.sync.aligned.m64n64k16.f32.bf16.bf16 {%0,%1,%2,%3,%4,%5,%6,%7,%8,%9,%10,%11,%12,%13,%14,%15,%16,%17,%18,%19,%20,%21,%22,%23,%24,%25,%26,%27,%28,%29,%30,%31}, {%32,%33,%34,%35}, %36, 1, 1, 1, 0;\n"
      : "+f"(d[0]), "+f"(d[1]), "+f"(d[2]), "+f"(d[3]), "+f"(d[4]), "+f"(d[5]), "+f"(d[6]), "+f"(d[7]), "+f"(d[8]), "+f"(d[9]), "+f"(d[10]), "+f"(d[11]), "+f"(d[12]), "+f"(d[13]), "+f"(d[14]), "+f"(d[15]), "+f"(d[16]), "+f"(d[17]), "+f"(d[18]), "+f"(d[19]), "+f"(d[20]), "+f"(d[21]), "+f"(d[22]), "+f"(d[23]), "+f"(d[24]), "+f"(d[25]), "+f"(d[26]), "+f"(d[27]), "+f"(d[28]), "+f"(d[29]), "+f"(d[30]), "+f"(d[31])
      : "r"(a[0]), "r"(a[1]), "r"(a[2]), "r"(a[3]), "l"(descB));
}

__device__ __forceinline__ void wgmma_pv(float* d, uint32_t a0, uint32_t a1, uint32_t a2, uint32_t a3, uint64_t descB) {
    asm volatile("wgmma.mma_async.sync.aligned.m64n24k16.f32.bf16.bf16 {%0,%1,%2,%3,%4,%5,%6,%7,%8,%9,%10,%11}, {%12,%13,%14,%15}, %16, 1, 1, 1, 1;\n"
                 : "+f"(d[0]), "+f"(d[1]), "+f"(d[2]), "+f"(d[3]), "+f"(d[4]), "+f"(d[5]), "+f"(d[6]), "+f"(d[7]), "+f"(d[8]), "+f"(d[9]), "+f"(d[10]), "+f"(d[11])
                 : "r"(a0), "r"(a1), "r"(a2), "r"(a3), "l"(descB));
}

__device__ __forceinline__ void k1_panel(int g, int i, int& type, int& col) {
    if (g < 6) {
        int p = g * 5 + i;
        if (p < 8) { type = 0; col = p * 64; } else { type = 1; col = (p - 8) * 64; }
    } else {
        if (i < 3) { type = 1; col = (22 + (g - 6) * 3 + i) * 64; } else { type = 2 + (g - 6); col = 0; }
    }
}

constexpr int K1_STAGES = 4;
constexpr int K1_PANEL_BYTES = 64 * 128;
constexpr int K1_STAGE_BYTES = 16384 + 5 * K1_PANEL_BYTES;
constexpr int K1_SMEM = K1_STAGES * K1_STAGE_BYTES + 128 + 320 * 8;
constexpr float Q_SCALE = 0.25f * 1.4426950408889634f;

__global__ void __launch_bounds__(384, 1)
k1_proj(const __grid_constant__ CUtensorMap tm_x, const __grid_constant__ CUtensorMap tm_wq,
        const __grid_constant__ CUtensorMap tm_wk, const __grid_constant__ CUtensorMap tm_wv,
        const __grid_constant__ CUtensorMap tm_w1, const __grid_constant__ CUtensorMap tm_qo,
        const __grid_constant__ CUtensorMap tm_ho, const __nv_bfloat16* __restrict__ x, const __nv_bfloat16* __restrict__ b1,
        float2* rowstat, float* colpart,
        __nv_bfloat16* __restrict__ kv, float* __restrict__ kvmax) {
    extern __shared__ __align__(1024) uint8_t smem_raw[];
    const uint32_t sbase = smem_u32(smem_raw);
    const uint32_t bar_full = sbase + K1_STAGES * K1_STAGE_BYTES, bar_empty = bar_full + 8 * K1_STAGES, bar_col = bar_empty + 8 * K1_STAGES;
    const uint32_t sCol = bar_full + 128;
    const int tid = threadIdx.x, warp = __shfl_sync(0xffffffffu, tid >> 5, 0), lane = tid & 31;
    const int crank = blockIdx.x & 1, grp = (blockIdx.x >> 1) & 7, rb = (blockIdx.x >> 4) * 2 + crank;
    const int npanels = grp < 6 ? 5 : 4;
    if (tid == 0) DEV_STAMP(0, 0);

    if (tid == 288) {
        tma_prefetch_desc(&tm_x); tma_prefetch_desc(&tm_w1); tma_prefetch_desc(grp < 2 ? &tm_wq : grp == 6 ? &tm_wk : &tm_wv);
        tma_prefetch_desc(&tm_ho); tma_prefetch_desc(&tm_qo);
    }
    uint4 v[2][2];
    if (warp < 8) {
        const uint4* xp = reinterpret_cast<const uint4*>(x + (size_t)(rb * 128 + grp * 16 + warp * 2) * D_MODEL);
#pragma unroll
        for (int r = 0; r < 2; r++) { v[r][0] = __ldg(xp + r * 64 + lane); v[r][1] = __ldg(xp + r * 64 + 32 + lane); }
    }
    const int krot = rb & 8 ? 4 : 0, cstage = (rb >> 1) & 3;
    if (tid == 256) {
        for (int s = 0; s < K1_STAGES; s++) { mbar_init(bar_full + 8 * s, 1); mbar_init(bar_empty + 8 * s, s == cstage ? 18 : 16); }
        mbar_init(bar_col, 96);
        mbar_init_fence();
    }
    asm volatile("barrier.cluster.arrive.relaxed;" ::: "memory");
    if (warp != 8) asm volatile("barrier.cluster.wait;" ::: "memory");
    pdl_launch();

    if (warp >= 8) {
        reg_dealloc<88>();
        if (warp == 8) {
            const CUtensorMap* tms[5]; int cols[5];
#pragma unroll
            for (int i = 0; i < 5; i++) {
                int type, col; k1_panel(grp, i, type, col);
                tms[i] = type == 0 ? &tm_wq : type == 1 ? &tm_w1 : type == 2 ? &tm_wk : &tm_wv;
                cols[i] = col;
            }
            if (lane == 0) {
                mbar_expect_tx(bar_full, 16384 + npanels * K1_PANEL_BYTES);
                tma_load_2d(sbase, &tm_x, krot * 64, rb * 128, bar_full);
#pragma unroll
                for (int i = 0; i < 5; i++)
                    if (i < npanels) tma_load_2d(sbase + 16384 + i * K1_PANEL_BYTES, tms[i], cols[i], krot * 64, bar_full);
            }
            __syncwarp();
            asm volatile("barrier.cluster.wait;" ::: "memory");
            if (lane == 0) {
                for (int ks = 1; ks < 8; ks++) {
                    const int s = ks % K1_STAGES;
                    const uint32_t st = sbase + s * K1_STAGE_BYTES;
                    mbar_wait(bar_empty + 8 * s, ((ks / K1_STAGES) & 1) ^ 1);
                    const int k0 = ((ks + krot) & 7) * 64;
                    mbar_expect_tx(bar_full + 8 * s, 16384 + npanels * K1_PANEL_BYTES);
                    tma_load_2d(st, &tm_x, k0, rb * 128, bar_full + 8 * s);
#pragma unroll
                    for (int i = 0; i < 5; i++)
                        if (i < npanels && ((i + ks + crank) & 1) == 0)
                            tma_load_2d_mc(st + 16384 + i * K1_PANEL_BYTES, tms[i], cols[i], k0, bar_full + 8 * s, (uint16_t)3);
                }
            }
        } else {
            const int ht = tid - 288;
            mbar_wait(bar_full + 8 * cstage, 0);
            {
                const int pc = ht >> 1, half = ht & 1;
                float sacc[8];
#pragma unroll
                for (int c = 0; c < 8; c++) sacc[c] = 0.f;
                if (pc < npanels * 8) {
                    const uint32_t pb = sbase + cstage * K1_STAGE_BYTES + 16384 + (pc >> 3) * K1_PANEL_BYTES;
#pragma unroll
                    for (int i = 0; i < 16; i++) {
                        const int k = crank * 32 + 2 * i + half;
                        uint4 u;
                        asm volatile("ld.shared.v4.b32 {%0,%1,%2,%3}, [%4];" : "=r"(u.x), "=r"(u.y), "=r"(u.z), "=r"(u.w)
                                     : "r"(pb + k * 128 + (((pc & 7) ^ (k & 7)) << 4)));
                        sacc[0] += bf_lo(u.x); sacc[1] += bf_hi(u.x); sacc[2] += bf_lo(u.y); sacc[3] += bf_hi(u.y);
                        sacc[4] += bf_lo(u.z); sacc[5] += bf_hi(u.z); sacc[6] += bf_lo(u.w); sacc[7] += bf_hi(u.w);
                    }
                }
#pragma unroll
                for (int c = 0; c < 8; c++) sacc[c] += __shfl_xor_sync(0xffffffffu, sacc[c], 1);
                if (pc < npanels * 8) {
                    float4* dst = reinterpret_cast<float4*>(colpart + (grp * 16 + rb) * 320 + pc * 8) + half;
                    *dst = half ? make_float4(xch_enc(sacc[4]), xch_enc(sacc[5]), xch_enc(sacc[6]), xch_enc(sacc[7]))
                                : make_float4(xch_enc(sacc[0]), xch_enc(sacc[1]), xch_enc(sacc[2]), xch_enc(sacc[3]));
                }
                named_bar_sync(4, 96);
                if (ht < 2) mbar_arrive_remote(bar_empty + 8 * cstage, ht);
            }
            if (ht == 0) DEV_STAMP(0, 6);
            for (int c2 = ht; c2 < npanels * 32; c2 += 96) {
                int type, col; k1_panel(grp, c2 >> 5, type, col);
                uint32_t bb = 0;
                if (type == 1) bb = __ldg(reinterpret_cast<const uint32_t*>(b1 + col) + (c2 & 31));
                uint2 pv[16];
                bool okv = false;
#pragma unroll 1
                for (uint32_t n = 0; n < (1u << 14) && !okv; n++) {
                    okv = true;
#pragma unroll
                    for (int k = 0; k < 16; k++) pv[k] = ld_relaxed_v2(colpart + (grp * 16 + k) * 320 + c2 * 2);
#pragma unroll
                    for (int k = 0; k < 16; k++) okv = okv && pv[k].x != NOT_READY && pv[k].y != NOT_READY;
                }
                float s0 = 0.f, s1 = 0.f;
#pragma unroll
                for (int k = 0; k < 16; k++) { s0 += xch_dec(pv[k].x); s1 += xch_dec(pv[k].y); }
                asm volatile("st.shared.v4.f32 [%0], {%1,%2,%3,%4};" ::"r"(sCol + c2 * 16), "f"(s0), "f"(bf_lo(bb)), "f"(s1), "f"(bf_hi(bb)) : "memory");
            }
            mbar_arrive(bar_col);
            if (ht == 0) DEV_STAMP(0, 7);
        }
    } else {
        reg_alloc<208>();
        const int wg = warp >> 2;
        const int g = lane >> 2, t = lane & 3;
        const int wrow = (warp & 3) * 16;
        {
            float f[2][16], sum[2], sq[2];
#pragma unroll
            for (int r = 0; r < 2; r++) {
                const uint32_t w[8] = {v[r][0].x, v[r][0].y, v[r][0].z, v[r][0].w, v[r][1].x, v[r][1].y, v[r][1].z, v[r][1].w};
#pragma unroll
                for (int i = 0; i < 8; i++) { f[r][2 * i] = bf_lo(w[i]); f[r][2 * i + 1] = bf_hi(w[i]); }
                sum[r] = 0.f;
#pragma unroll
                for (int i = 0; i < 16; i++) sum[r] += f[r][i];
            }
#pragma unroll
            for (int o = 16; o > 0; o >>= 1) { sum[0] += __shfl_xor_sync(0xffffffffu, sum[0], o); sum[1] += __shfl_xor_sync(0xffffffffu, sum[1], o); }
#pragma unroll
            for (int r = 0; r < 2; r++) {
                sum[r] *= (1.0f / D_MODEL);
                sq[r] = 0.f;
#pragma unroll
                for (int i = 0; i < 16; i++) { const float d = f[r][i] - sum[r]; sq[r] += d * d; }
            }
#pragma unroll
            for (int o = 16; o > 0; o >>= 1) { sq[0] += __shfl_xor_sync(0xffffffffu, sq[0], o); sq[1] += __shfl_xor_sync(0xffffffffu, sq[1], o); }
            if (lane < 2) {
                const float rstd = rsqrtf((lane ? sq[1] : sq[0]) * (1.0f / D_MODEL) + 1e-5f);
                rowstat[rb * 128 + grp * 16 + warp * 2 + lane] = make_float2(xch_enc(rstd), (lane ? sum[1] : sum[0]) * rstd);
            }
            if (tid == 0) DEV_STAMP(0, 5);
        }
        float acc[160];
#pragma unroll
        for (int i = 0; i < 160; i++) acc[i] = 0.f;
        float2 rs0, rs1;
        const uint64_t dA0 = make_desc(sbase + wg * 8192, 16, 1024, 1);
        const uint64_t dB0 = make_desc(sbase + 16384, K1_PANEL_BYTES, 1024, 1);
#define K1_MAINLOOP(FIVE)                                                                                          \
        for (int ks = 0; ks < 8; ks++) {                                                                           \
            const int s = ks % K1_STAGES;                                                                          \
            mbar_wait(bar_full + 8 * s, (ks / K1_STAGES) & 1);                                                     \
            if (ks == 0 && tid == 0) DEV_STAMP(0, 1);                                                              \
            wg_fence();                                                                                            \
            _Pragma("unroll") for (int kk = 0; kk < 4; kk++) {                                                     \
                const uint64_t dA = dA0 + (uint64_t)((s * K1_STAGE_BYTES + kk * 32) >> 4);                         \
                const uint64_t dB = dB0 + (uint64_t)((s * K1_STAGE_BYTES + kk * 2048) >> 4);                       \
                wgmma_ss_n256_tb(acc, dA, dB, (ks | kk) != 0);                                                     \
                if (FIVE) wgmma_ss_n64_tb(acc + 128, dA, dB + (uint64_t)((4 * K1_PANEL_BYTES) >> 4), (ks | kk) != 0); \
            }                                                                                                      \
            wg_commit();                                                                                           \
            if (ks == 7) {                                                                                         \
                uint2 r0, r1;                                                                                      \
                uint32_t n = 0;                                                                                    \
                _Pragma("unroll 1") do {                                                                           \
                    r0 = ld_relaxed_v2(rowstat + rb * 128 + wg * 64 + wrow + g);                                   \
                    r1 = ld_relaxed_v2(rowstat + rb * 128 + wg * 64 + wrow + g + 8);                               \
                } while ((r0.x == NOT_READY || r1.x == NOT_READY) && ++n < (1u << 14));                            \
                rs0 = make_float2(xch_dec(r0.x), __uint_as_float(r0.y));                                           \
                rs1 = make_float2(xch_dec(r1.x), __uint_as_float(r1.y));                                           \
                mbar_wait(bar_col, 0);                                                                             \
            }                                                                                                      \
            if (ks > 0 && ks <= 4) {                                                                               \
                wg_wait<1>();                                                                                      \
                if (lane < 2) mbar_arrive_remote(bar_empty + 8 * ((ks - 1) % K1_STAGES), lane);                    \
            }                                                                                                      \
        }                                                                                                          \
        wg_wait<0>();
        const int srow = (lane & 7) + ((lane >> 3) & 1) * 8;
        if (npanels == 5) { K1_MAINLOOP(true) } else { K1_MAINLOOP(false) }
        fence_regs<160>(acc);
        if (tid == 0) DEV_STAMP(0, 2);
        named_bar_sync(1, 256);
#pragma unroll
        for (int p = 0; p < 5; p++) {
            if (p < npanels) {
                int type, col; k1_panel(grp, p, type, col);
                float* a = acc + p * 32;
                const int nj = type <= 1 ? 8 : 2;
                const float sc = type == 0 ? Q_SCALE : 1.0f;
                const float r0x = rs0.x * sc, r0y = -rs0.y * sc, r1x = rs1.x * sc, r1y = -rs1.y * sc;
#pragma unroll
                for (int j = 0; j < 8; j++) {
                    if (j < nj) {
                        float4 c;
                        asm volatile("ld.shared.v4.f32 {%0,%1,%2,%3}, [%4];" : "=f"(c.x), "=f"(c.y), "=f"(c.z), "=f"(c.w)
                                     : "r"(sCol + (p * 64 + j * 8 + 2 * t) * 8));
                        a[4 * j] = fmaf(a[4 * j], r0x, fmaf(r0y, c.x, c.y));
                        a[4 * j + 1] = fmaf(a[4 * j + 1], r0x, fmaf(r0y, c.z, c.w));
                        a[4 * j + 2] = fmaf(a[4 * j + 2], r1x, fmaf(r1y, c.x, c.y));
                        a[4 * j + 3] = fmaf(a[4 * j + 3], r1x, fmaf(r1y, c.z, c.w));
                    }
                }
                if (type <= 1) {
                    const uint32_t stg = sbase + (p * 8 + warp) * 2048;
                    uint32_t pk[16];
                    if (type == 0) {
#pragma unroll
                        for (int j = 0; j < 8; j++) {
                            pk[2 * j] = pack_bf16(a[4 * j], a[4 * j + 1]);
                            pk[2 * j + 1] = pack_bf16(a[4 * j + 2], a[4 * j + 3]);
                        }
                    } else {
#pragma unroll
                        for (int j = 0; j < 8; j++) {
                            const uint32_t h0 = pack_bf16_relu(a[4 * j], a[4 * j + 1]), h1 = pack_bf16_relu(a[4 * j + 2], a[4 * j + 3]);
                            pk[2 * j] = mul_bf16x2(h0, h0);
                            pk[2 * j + 1] = mul_bf16x2(h1, h1);
                        }
                    }
#pragma unroll
                    for (int j = 0; j < 8; j += 2) {
                        const int c16 = j + (lane >> 4);
                        stmatrix_x4(stg + srow * 128 + ((c16 ^ (srow & 7)) << 4), pk[2 * j], pk[2 * j + 1], pk[2 * j + 2], pk[2 * j + 3]);
                    }
                    fence_proxy_async();
                    __syncwarp();
                    if (lane == 0) {
                        tma_store_2d(type == 0 ? &tm_qo : &tm_ho, stg, col, rb * 128 + warp * 16);
                        tma_store_commit();
                    }
                } else if (type == 3) {
                    const int r = wg * 64 + wrow + g;
                    const int pos0 = (r >> 2) * 64 + rb * 4 + (r & 3), pos1 = pos0 + 128;
                    uint32_t* dst = reinterpret_cast<uint32_t*>(kv);
                    const uint32_t r00 = pack_bf16(a[0], a[1]), r01 = pack_bf16(a[4], a[5]);
                    const uint32_t r10 = pack_bf16(a[2], a[3]), r11 = pack_bf16(a[6], a[7]);
                    dst[(pos0 >> 4) * 128 + (pos0 & 15) * 4 + t] = r00;
                    dst[16384 + pos0 * 4 + t] = r01;
                    dst[(pos1 >> 4) * 128 + (pos1 & 15) * 4 + t] = r10;
                    dst[16384 + pos1 * 4 + t] = r11;
                    float m = fmaxf(fmaxf(fmaxf(fabsf(bf_lo(r00)), fabsf(bf_hi(r00))), fmaxf(fabsf(bf_lo(r01)), fabsf(bf_hi(r01)))),
                                    fmaxf(fmaxf(fabsf(bf_lo(r10)), fabsf(bf_hi(r10))), fmaxf(fabsf(bf_lo(r11)), fabsf(bf_hi(r11)))));
#pragma unroll
                    for (int o = 16; o > 0; o >>= 1) m = fmaxf(m, __shfl_xor_sync(0xffffffffu, m, o));
                    if (lane == 0) kvmax[128 + rb * 8 + warp] = m;
                } else {
                    float* kf = reinterpret_cast<float*>(smem_raw + 96 * 1024);
                    const int r = wg * 64 + wrow + g;
                    const int pos0 = (r >> 2) * 64 + rb * 4 + (r & 3), pos1 = pos0 + 128;
                    uint32_t* dst = reinterpret_cast<uint32_t*>(kv) + 32768;
                    dst[(pos0 >> 3) * 64 + (pos0 & 7) * 4 + t] = pack_bf16(a[0], a[1]);
                    dst[(pos0 >> 3) * 64 + 32 + (pos0 & 7) * 4 + t] = pack_bf16(a[4], a[5]);
                    dst[(pos1 >> 3) * 64 + (pos1 & 7) * 4 + t] = pack_bf16(a[2], a[3]);
                    dst[(pos1 >> 3) * 64 + 32 + (pos1 & 7) * 4 + t] = pack_bf16(a[6], a[7]);
                    kf[r * 17 + 2 * t] = a[0]; kf[r * 17 + 2 * t + 1] = a[1];
                    kf[r * 17 + 8 + 2 * t] = a[4]; kf[r * 17 + 8 + 2 * t + 1] = a[5];
                    kf[(r + 8) * 17 + 2 * t] = a[2]; kf[(r + 8) * 17 + 2 * t + 1] = a[3];
                    kf[(r + 8) * 17 + 8 + 2 * t] = a[6]; kf[(r + 8) * 17 + 8 + 2 * t + 1] = a[7];
                    named_bar_sync(1, 256);
                    if (tid < 64) {
                        const int i = tid >> 4, dim = tid & 15;
                        const int c = rb * 4 + i;
                        const int inner = (dim >> 3) * 64 + (c & 7) * 8 + (dim & 7);
                        float kt = 0.f;
#pragma unroll 8
                        for (int j = 0; j < 32; j++) {
                            const __nv_bfloat16 d = __float2bfloat16_rn(kf[(j * 4 + i) * 17 + dim] - kt);
                            kt += __bfloat162float(d);
                            kf[(j * 4 + i) * 17 + dim] = kt;
                            const int grp8 = j * 8 + (c >> 3);
                            kv[(grp8 < 128 ? grp8 * 256 + 128 : 49152 + (grp8 - 128) * 128) + inner] = d;
                        }
                    }
                    named_bar_sync(1, 256);
                    if (tid < 128) {
                        float n = 0.f;
#pragma unroll
                        for (int d = 0; d < 16; d++) { const float v = kf[tid * 17 + d]; n += v * v; }
                        if (!(n == n)) n = __int_as_float(0x7f800000);
#pragma unroll
                        for (int o = 8; o > 0; o >>= 1) n = fmaxf(n, __shfl_xor_sync(0xffffffffu, n, o));
                        if ((lane & 15) == 0) kvmax[rb * 8 + (tid >> 4)] = n;
                    }
                }
            }
        }
        if (tid == 0) DEV_STAMP(0, 3);
        if (lane == 0) tma_store_wait();
        if (tid == 0) DEV_STAMP(0, 4);
    }
}

constexpr int AT_KT = 64;
constexpr int AT_NCHUNK = 8;
constexpr int AT_NSTEP = S_LEN / AT_KT;
constexpr int AT_SPC = AT_NSTEP / AT_NCHUNK;
constexpr int AT_ONES = 131072;
constexpr int F2_STAGES = 4;
constexpr int F2_STAGE_BYTES = 8192 + 16384;
constexpr int F2_BASE = 132096;
constexpr int F2_NK = F_DIM / 64;
constexpr int AT_BAR = F2_BASE + F2_STAGES * F2_STAGE_BYTES;
constexpr int AT_SMEM = AT_BAR + 256;
#define AT_SWMASK_V 0xB6DB
constexpr uint32_t AT_SWMASK = AT_SWMASK_V;

#define AT_MAGIC 382.41765f
__device__ __forceinline__ uint32_t exp2_pair_alu(float t0, float t1) {
    uint32_t y;
    asm("prmt.b32 %0, %1, %2, 0x6521;" : "=r"(y) : "f"(t0), "f"(t1));
    const uint32_t e = y & 0x7F807F80u;
    uint32_t uh, p;
    asm("lop3.b32 %0, %1, %2, 0x3F003F00, 0xBE;" : "=r"(uh) : "r"(y), "r"(e));
    asm("fma.rn.bf16x2 %0, %1, %2, %3;" : "=r"(p) : "r"(uh), "r"(y), "r"(e));
    return p;
}

__device__ __forceinline__ void at_load_chunk(uint32_t sbase, const __nv_bfloat16* KV, uint32_t bar0, int c) {
    const uint8_t* src = reinterpret_cast<const uint8_t*>(KV);
    const uint32_t off = c < 4 ? c * 16384 : 98304 + (c - 4) * 8192, bytes = c < 4 ? 16384 : 8192;
    mbar_expect_tx(bar0 + 8 * c, bytes + 4096);
    bulk_g2s(sbase + off, src + off, bytes, bar0 + 8 * c);
    bulk_g2s(sbase + 65536 + c * 4096, src + 65536 + c * 4096, 4096, bar0 + 8 * c);
}

__device__ __forceinline__ void at_store(const float* o, __nv_bfloat16* O, int row, int lane) {
    const float l0 = __shfl_sync(0xffffffffu, o[8], lane & ~3);
    const float l1 = __shfl_sync(0xffffffffu, o[10], lane & ~3);
    const float r0 = __fdividef(1.0f, l0), r1 = __fdividef(1.0f, l1);
    const int t = lane & 3;
    uint32_t* op = reinterpret_cast<uint32_t*>(O + (size_t)(row + (lane >> 2)) * 16);
    op[t] = pack_bf16(o[0] * r0, o[1] * r0);
    op[t + 4] = pack_bf16(o[4] * r0, o[5] * r0);
    op[64 + t] = pack_bf16(o[2] * r1, o[3] * r1);
    op[64 + t + 4] = pack_bf16(o[6] * r1, o[7] * r1);
}

__device__ __forceinline__ void mma16816(float* c, const uint32_t* a, uint32_t b0, uint32_t b1) {
    asm volatile("mma.sync.aligned.m16n8k16.row.col.f32.bf16.bf16.f32 {%0,%1,%2,%3}, {%4,%5,%6,%7}, {%8,%9}, {%0,%1,%2,%3};"
                 : "+f"(c[0]), "+f"(c[1]), "+f"(c[2]), "+f"(c[3]) : "r"(a[0]), "r"(a[1]), "r"(a[2]), "r"(a[3]), "r"(b0), "r"(b1));
}
__device__ __forceinline__ void attn_fallback(const __nv_bfloat16* Q, const __nv_bfloat16* KV, __nv_bfloat16* O, uint32_t sbase) {
    const int tid = threadIdx.x;
    const int lane = tid & 31, g = lane >> 2, t = lane & 3;
    const uint32_t* Kg = reinterpret_cast<const uint32_t*>(KV + 65536);
#pragma unroll 1
    for (int mt = 0; mt < 2; mt++) {
        const int row = blockIdx.x * 512 + (tid >> 7) * 128 + mt * 64 + ((tid >> 5) & 3) * 16;
        const uint32_t* qp = reinterpret_cast<const uint32_t*>(Q + (size_t)(row + g) * 16);
        const uint32_t q[4] = {qp[t], qp[64 + t], qp[t + 4], qp[64 + t + 4]};
        float o[12];
#pragma unroll
        for (int i = 0; i < 12; i++) o[i] = 0.f;
        float m0 = -INFINITY, m1 = -INFINITY;
#pragma unroll 1
        for (int kt = 0; kt < S_LEN / 16; kt++) {
            float s[8];
#pragma unroll
            for (int i = 0; i < 8; i++) s[i] = 0.f;
#pragma unroll
            for (int h = 0; h < 2; h++) {
                const uint32_t* kp = Kg + (kt * 2 + h) * 64 + g * 4 + t;
                mma16816(s + 4 * h, q, kp[0], kp[32]);
            }
            float x0 = fmaxf(fmaxf(s[0], s[1]), fmaxf(s[4], s[5])), x1 = fmaxf(fmaxf(s[2], s[3]), fmaxf(s[6], s[7]));
            x0 = fmaxf(x0, __shfl_xor_sync(0xffffffffu, x0, 1)); x0 = fmaxf(x0, __shfl_xor_sync(0xffffffffu, x0, 2));
            x1 = fmaxf(x1, __shfl_xor_sync(0xffffffffu, x1, 1)); x1 = fmaxf(x1, __shfl_xor_sync(0xffffffffu, x1, 2));
            x0 = fmaxf(x0, m0); x1 = fmaxf(x1, m1);
            const float f0 = ex2(m0 - x0), f1 = ex2(m1 - x1);
            m0 = x0; m1 = x1;
#pragma unroll
            for (int j = 0; j < 3; j++) { o[4 * j] *= f0; o[4 * j + 1] *= f0; o[4 * j + 2] *= f1; o[4 * j + 3] *= f1; }
            const uint32_t p[4] = {pack_bf16(ex2(s[0] - m0), ex2(s[1] - m0)), pack_bf16(ex2(s[2] - m1), ex2(s[3] - m1)),
                                   pack_bf16(ex2(s[4] - m0), ex2(s[5] - m0)), pack_bf16(ex2(s[6] - m1), ex2(s[7] - m1))};
#pragma unroll
            for (int j = 0; j < 3; j++) {
                const uint32_t base = sbase + (j == 0 ? kt * 512 : j == 1 ? 65536 + kt * 256 : AT_ONES) + (lane & 15) * 16;
                uint32_t b0, b1;
                asm volatile("ldmatrix.sync.aligned.m8n8.x2.trans.shared.b16 {%0,%1}, [%2];" : "=r"(b0), "=r"(b1) : "r"(base));
                mma16816(o + 4 * j, p, b0, b1);
            }
        }
        at_store(o, O, row, lane);
    }
}

__global__ void __launch_bounds__(640, 1)
k2_attn(const __grid_constant__ CUtensorMap tm_h, const __grid_constant__ CUtensorMap tm_w2,
        const __nv_bfloat16* __restrict__ Q, const __nv_bfloat16* __restrict__ KV, const float* __restrict__ kvmax,
        const __nv_bfloat16* __restrict__ b2, __nv_bfloat16* __restrict__ O, __nv_bfloat16* __restrict__ G,
        uint2* __restrict__ rowstat, uint2* __restrict__ colpart) {
    extern __shared__ __align__(1024) uint8_t smem_raw[];
    const uint32_t sbase = smem_u32(smem_raw);
    const uint32_t bar0 = sbase + AT_BAR, f2_full = bar0 + 64, f2_empty = f2_full + 32, bar_guard = f2_empty + 32, bar_first = bar_guard + 8, sGuard = bar0 + 192;
    const int tid = threadIdx.x;
    const int wg = __shfl_sync(0xffffffffu, tid >> 7, 0);
    const int warp = (tid >> 5) & 3, lane = tid & 31;
    const int g = lane >> 2, t = lane & 3;
    if (tid == 0) DEV_STAMP(1, 0);
    if (tid == 0) {
        for (int i = 0; i < AT_NCHUNK; i++) mbar_init(bar0 + 8 * i, 1);
        for (int i = 0; i < F2_STAGES; i++) { mbar_init(f2_full + 8 * i, 1); mbar_init(f2_empty + 8 * i, 4); }
        mbar_init(bar_guard, 4);
        mbar_init(bar_first, 1);
        mbar_init_fence();
    }
    if (tid < 16) asm volatile("st.shared.v4.b32 [%0], {%1,%2,%2,%2};" ::"r"(sbase + AT_ONES + tid * 16), "r"(0x00003F80u), "r"(0u) : "memory");
    fence_proxy_async();
    __syncthreads();

    if (wg == 4) {
        const int rb = blockIdx.x >> 2, cb = blockIdx.x & 3;
        const uint32_t fb = sbase + F2_BASE;
        const bool leader = tid == 512;
        if (leader) {
#pragma unroll
            for (int s = 0; s < F2_STAGES; s++) {
                mbar_expect_tx(f2_full + 8 * s, F2_STAGE_BYTES);
                tma_load_2d(fb + s * F2_STAGE_BYTES + 8192, &tm_w2, cb * 128, s * 64, f2_full + 8 * s);
                tma_load_2d(fb + s * F2_STAGE_BYTES + 16384, &tm_w2, cb * 128 + 64, s * 64, f2_full + 8 * s);
            }
        }
        pdl_wait();
        mbar_wait(bar0, 0);
        if (leader) {
#pragma unroll
            for (int s = 0; s < F2_STAGES; s++) tma_load_2d(fb + s * F2_STAGE_BYTES, &tm_h, s * 64, rb * 64, f2_full + 8 * s);
        }
        {
            float km = fmaxf(fmaxf(kvmax[lane], kvmax[lane + 32]), fmaxf(kvmax[lane + 64], kvmax[lane + 96]));
            float vm = fmaxf(fmaxf(kvmax[128 + lane], kvmax[160 + lane]), fmaxf(kvmax[192 + lane], kvmax[224 + lane]));
            uint4 qv[4][2];
#pragma unroll
            for (int i = 0; i < 4; i++) {
                const uint4* qr = reinterpret_cast<const uint4*>(Q + (size_t)(blockIdx.x * 512 + warp * 128 + i * 16 + (lane >> 4) * 64 + (lane & 15)) * 16);
                qv[i][0] = qr[0]; qv[i][1] = qr[1];
            }
#pragma unroll
            for (int o = 16; o > 0; o >>= 1) { km = fmaxf(km, __shfl_xor_sync(0xffffffffu, km, o)); vm = fmaxf(vm, __shfl_xor_sync(0xffffffffu, vm, o)); }
#pragma unroll
            for (int i = 0; i < 4; i++) {
                const uint32_t qw[8] = {qv[i][0].x, qv[i][0].y, qv[i][0].z, qv[i][0].w, qv[i][1].x, qv[i][1].y, qv[i][1].z, qv[i][1].w};
                float qn = 0.f;
#pragma unroll
                for (int j = 0; j < 8; j++) qn += bf_lo(qw[j]) * bf_lo(qw[j]) + bf_hi(qw[j]) * bf_hi(qw[j]);
                const bool ok = (qn * km <= 3600.0f) && (vm <= 1.0e12f);
                const uint32_t bad = __any_sync(0xffffffffu, !ok);
                if (lane == 0) asm volatile("st.shared.u32 [%0], %1;" ::"r"(sGuard + (warp * 4 + i) * 4), "r"(bad) : "memory");
            }
            if (lane == 0) mbar_arrive(bar_guard);
        }
        __syncwarp();
        const uint64_t dA0 = make_desc(fb, 16, 1024, 1);
        const uint64_t dB0 = make_desc(fb + 8192, 8192, 1024, 1);
        float acc[64];
#pragma unroll
        for (int i = 0; i < 64; i++) asm volatile("mov.f32 %0, 0f00000000;" : "=f"(acc[i]));
#pragma unroll 1
        for (int ks = 0; ks < F2_NK; ks++) {
            const int s = ks % F2_STAGES;
            mbar_wait(f2_full + 8 * s, (ks / F2_STAGES) & 1);
            wg_fence();
#pragma unroll
            for (int kk = 0; kk < 4; kk++)
                wgmma_ss_n128_tb(acc, dA0 + (uint64_t)((s * F2_STAGE_BYTES + kk * 32) >> 4),
                                 dB0 + (uint64_t)((s * F2_STAGE_BYTES + kk * 2048) >> 4), 1);
            wg_commit();
            wg_wait<1>();
            if (ks > 0 && ks - 1 + F2_STAGES < F2_NK) {
                const int ps = (ks - 1) % F2_STAGES, k0 = (ks - 1 + F2_STAGES) * 64;
                if (lane == 0) mbar_arrive(f2_empty + 8 * ps);
                if (leader) {
                    mbar_wait(f2_empty + 8 * ps, ((ks - 1) / F2_STAGES) & 1);
                    mbar_expect_tx(f2_full + 8 * ps, F2_STAGE_BYTES);
                    tma_load_2d(fb + ps * F2_STAGE_BYTES, &tm_h, k0, rb * 64, f2_full + 8 * ps);
                    tma_load_2d(fb + ps * F2_STAGE_BYTES + 8192, &tm_w2, cb * 128, k0, f2_full + 8 * ps);
                    tma_load_2d(fb + ps * F2_STAGE_BYTES + 16384, &tm_w2, cb * 128 + 64, k0, f2_full + 8 * ps);
                }
                __syncwarp();
            }
        }
        wg_wait<0>();
        fence_regs<64>(acc);
        uint32_t* gp = reinterpret_cast<uint32_t*>(G + (size_t)(rb * 64 + warp * 16 + g) * D_MODEL + cb * 128) + t;
#pragma unroll
        for (int j = 0; j < 16; j++) {
            const uint32_t bb = __ldg(reinterpret_cast<const uint32_t*>(b2 + cb * 128 + j * 8) + t);
            const float b0 = bf_lo(bb), b1v = bf_hi(bb);
            const float z0 = acc[4 * j] + b0, z1 = acc[4 * j + 1] + b1v, z2 = acc[4 * j + 2] + b0, z3 = acc[4 * j + 3] + b1v;
            gp[j * 4] = pack_bf16(__fdividef(z0, 1.0f + __expf(-z0)), __fdividef(z1, 1.0f + __expf(-z1)));
            gp[j * 4 + 8 * (D_MODEL / 2)] = pack_bf16(__fdividef(z2, 1.0f + __expf(-z2)), __fdividef(z3, 1.0f + __expf(-z3)));
        }
        if (leader) DEV_STAMP(1, 5);
        return;
    }

    pdl_wait();
    pdl_launch();
    if (tid == 0) DEV_STAMP(1, 1);
    if (tid == 0) {
        const uint8_t* src = reinterpret_cast<const uint8_t*>(KV);
        mbar_expect_tx(bar_first, 4096);
        bulk_g2s(sbase, src, 4096, bar_first);
        mbar_expect_tx(bar0, 12288 + 4096);
        bulk_g2s(sbase + 4096, src + 4096, 12288, bar0);
        bulk_g2s(sbase + 65536, src + 65536, 4096, bar0);
        at_load_chunk(sbase, KV, bar0, 1); at_load_chunk(sbase, KV, bar0, 2);
    }
    if (tid >= 128 && tid < 288) colpart[blockIdx.x * 160 + tid - 128] = make_uint2(NOT_READY, NOT_READY);
    if (tid >= 288 && tid < 304) rowstat[blockIdx.x * 16 + tid - 288] = make_uint2(NOT_READY, NOT_READY);
    const int rowA = blockIdx.x * 512 + wg * 128 + warp * 16;
    const uint32_t* qp = reinterpret_cast<const uint32_t*>(Q + (size_t)(rowA + g) * 16);
    const uint32_t lo0 = ((sbase & 0x3FFFF) >> 4) | (8u << 16);

#define AT_EXP(P) _Pragma("unroll") for (int i = 0; i < AT_KT / 4; i++) {                       \
                if ((AT_SWMASK >> (i & 15)) & 1) P[i] = exp2_pair_alu(s[2 * i], s[2 * i + 1]);  \
                else P[i] = pack_bf16(ex2(s[2 * i]), ex2(s[2 * i + 1])); }
#define AT_PV(P, st) _Pragma("unroll") for (int j = 0; j < AT_KT / 16; j++)                     \
                wgmma_pv(o, P[4 * j], P[4 * j + 1], P[4 * j + 2], P[4 * j + 3],                 \
                         desc64(vlo + ((st) * 4 + j) * 32, vhi - ((st) * 4 + j) * 16));
#define AT_EXPH(P, h) _Pragma("unroll") for (int i = (h) * 8; i < (h) * 8 + 8; i++) {           \
                if ((AT_SWMASK >> (i & 15)) & 1) P[i] = exp2_pair_alu(s[2 * i], s[2 * i + 1]);  \
                else P[i] = pack_bf16(ex2(s[2 * i]), ex2(s[2 * i + 1])); }
#define AT_PVH(P, st, h) _Pragma("unroll") for (int j = (h) * 2; j < (h) * 2 + 2; j++)          \
                wgmma_pv(o, P[4 * j], P[4 * j + 1], P[4 * j + 2], P[4 * j + 3],                 \
                         desc64(vlo + ((st) * 4 + j) * 32, vhi - ((st) * 4 + j) * 16));
#define AT_STEP(st, klo, khi) {                                                                 \
                wg_wait<0>();                                                                   \
                fence_regs<AT_KT / 2>(s);                                                       \
                AT_EXPH(p0, 0);                                                                 \
                wg_fence();                                                                     \
                AT_PVH(p0, st, 0);                                                              \
                wg_commit();                                                                    \
                AT_EXPH(p0, 1);                                                                 \
                if (st == AT_SPC - 1 && mt == 0) mbar_wait(bar0 + 8 * (c + 1), 0);              \
                wg_wait<0>();                                                                   \
                wg_fence();                                                                     \
                wgmma_qk_acc_n64(s, q, desc64(klo, khi));                                       \
                AT_PVH(p0, st, 1);                                                              \
                wg_commit(); }

#pragma unroll 1
    for (int mt = 0; mt < 2; mt++) {
        uint32_t q[4];
        q[0] = qp[mt * 512 + t]; q[2] = qp[mt * 512 + t + 4]; q[1] = qp[mt * 512 + 64 + t]; q[3] = qp[mt * 512 + 64 + t + 4];
        float o[12];
#pragma unroll
        for (int i = 0; i < 12; i++) asm volatile("mov.f32 %0, 0f00000000;" : "=f"(o[i]));
        float s[AT_KT / 2];
        uint32_t p0[AT_KT / 4];
#pragma unroll
        for (int i = 0; i < AT_KT / 2; i++) {
            if ((AT_SWMASK >> ((i >> 1) & 15)) & 1) asm volatile("mov.f32 %0, %1;" : "=f"(s[i]) : "f"(AT_MAGIC));
            else asm volatile("mov.f32 %0, 0f00000000;" : "=f"(s[i]));
        }
        if (mt == 0) mbar_wait(bar_first, 0);
        if (tid == 0) DEV_STAMP(1, 2 + mt);
        uint32_t klo = lo0 + 16, vlo = lo0, vhi = 4096;
        wg_fence();
        wgmma_qk_acc_n64(s, q, desc64(klo, 32));
        wg_commit();
        if (mt == 0) mbar_wait(bar0, 0);
        uint32_t kst = 256, khi = 32;
#pragma unroll 1
        for (int c = 0; c < AT_NCHUNK - 1; c++) {
            if (tid == 0 && mt == 0 && c + 3 < AT_NCHUNK) at_load_chunk(sbase, KV, bar0, c + 3);
            AT_STEP(0, klo + kst, khi); AT_STEP(1, klo + 2 * kst, khi); AT_STEP(2, klo + 3 * kst, khi);
            if (c == 3) { klo = lo0 + (98304 >> 4); kst = 128; khi = 16; } else klo += 4 * kst;
            AT_STEP(3, klo, khi);
            vlo += 512; vhi -= 256;
        }
        {
            const int c = 0; (void)c;
            AT_STEP(0, klo + 128, 16); AT_STEP(1, klo + 256, 16); AT_STEP(2, klo + 384, 16);
            wg_wait<0>();
            fence_regs<AT_KT / 2>(s);
            AT_EXP(p0);
            wg_fence();
            AT_PV(p0, 3);
            wg_commit();
            wg_wait<0>();
            fence_regs<12>(o);
        }
        at_store(o, O, rowA + mt * 64, lane);
    }
    if (tid == 0) DEV_STAMP(1, 4);

    mbar_wait(bar_guard, 0);
    uint32_t bad;
    asm volatile("ld.shared.u32 %0, [%1];" : "=r"(bad) : "r"(sGuard + (tid >> 5) * 4) : "memory");
    if (__any_sync(0xffffffffu, bad != 0) == 0) return;
    attn_fallback(Q, KV, O, sbase);
}

constexpr int K3_STAGE_BYTES = 16384 + 8192;
constexpr int K3_X = 8 * K3_STAGE_BYTES;
constexpr int K3_G = K3_X + 16384;
constexpr int K3_SMEM = K3_G + 16384 + 256;

__global__ void __launch_bounds__(256, 1)
k3_out(const __grid_constant__ CUtensorMap tm_o, const __grid_constant__ CUtensorMap tm_wo,
       const __grid_constant__ CUtensorMap tm_x, const __grid_constant__ CUtensorMap tm_g,
       const __grid_constant__ CUtensorMap tm_out) {
    extern __shared__ __align__(1024) uint8_t smem_raw[];
    const uint32_t sbase = smem_u32(smem_raw);
    const uint32_t sX = sbase + K3_X, sG = sbase + K3_G;
    const uint32_t bar_full = sG + 16384, bar_x = bar_full + 64;
    const int tid = threadIdx.x, warp = __shfl_sync(0xffffffffu, tid >> 5, 0), lane = tid & 31;
    const int rb = blockIdx.x >> 3, cb = blockIdx.x & 7;
    if (tid == 0) {
        DEV_STAMP(2, 0);
        for (int s = 0; s < 8; s++) mbar_init(bar_full + 8 * s, 1);
        mbar_init(bar_x, 1);
        mbar_init_fence();
        for (int s = 0; s < 8; s++) {
            mbar_expect_tx(bar_full + 8 * s, K3_STAGE_BYTES);
            tma_load_2d(sbase + s * K3_STAGE_BYTES + 16384, &tm_wo, cb * 64, s * 64, bar_full + 8 * s);
        }
        mbar_expect_tx(bar_x, 32768);
        tma_load_2d(sX, &tm_x, cb * 64, rb * 128, bar_x);
        pdl_wait();
        DEV_STAMP(2, 1);
        for (int s = 0; s < 8; s++) tma_load_2d(sbase + s * K3_STAGE_BYTES, &tm_o, s * 64, rb * 128, bar_full + 8 * s);
        tma_load_2d(sG, &tm_g, cb * 64, rb * 128, bar_x);
    }
    __syncthreads();
    const int wg = warp >> 2;
    float acc[32];
#pragma unroll
    for (int i = 0; i < 32; i++) asm volatile("mov.f32 %0, 0f00000000;" : "=f"(acc[i]));
    const uint64_t dA0 = make_desc(sbase + wg * 8192, 16, 1024, 1);
    const uint64_t dB0 = make_desc(sbase + 16384, 8192, 1024, 1);
#pragma unroll 1
    for (int ks = 0; ks < 8; ks++) {
        mbar_wait(bar_full + 8 * ks, 0);
        wg_fence();
#pragma unroll
        for (int kk = 0; kk < 4; kk++)
            wgmma_ss_n64_tb(acc, dA0 + (uint64_t)((ks * K3_STAGE_BYTES + kk * 32) >> 4),
                            dB0 + (uint64_t)((ks * K3_STAGE_BYTES + kk * 2048) >> 4), 1);
        wg_commit();
    }
    wg_wait<0>();
    fence_regs<32>(acc);
    if (tid == 0) DEV_STAMP(2, 2);
    mbar_wait(bar_x, 0);
    const int g = lane >> 2, t = lane & 3;
    const int row0 = warp * 16 + g;
#pragma unroll
    for (int j = 0; j < 8; j++) {
#pragma unroll
        for (int h = 0; h < 2; h++) {
            const int row = row0 + h * 8;
            const uint32_t off = row * 128 + ((j ^ (row & 7)) << 4) + t * 4;
            uint32_t xv, gv;
            asm volatile("ld.shared.b32 %0, [%1];" : "=r"(xv) : "r"(sX + off) : "memory");
            asm volatile("ld.shared.b32 %0, [%1];" : "=r"(gv) : "r"(sG + off) : "memory");
            const uint32_t ov = pack_bf16(fmaf(acc[4 * j + 2 * h], bf_lo(gv), bf_lo(xv)), fmaf(acc[4 * j + 2 * h + 1], bf_hi(gv), bf_hi(xv)));
            asm volatile("st.shared.b32 [%0], %1;" ::"r"(sX + off), "r"(ov) : "memory");
        }
    }
    fence_proxy_async();
    __syncwarp();
    if (lane == 0) {
        tma_store_2d(&tm_out, sX + warp * 2048, cb * 64, rb * 128 + warp * 16);
        tma_store_commit();
        if (tid == 0) DEV_STAMP(2, 3);
        tma_store_wait();
        if (tid == 0) DEV_STAMP(2, 4);
    }
}

typedef CUresult (*EncodeFn)(CUtensorMap*, CUtensorMapDataType, cuuint32_t, void*, const cuuint64_t*, const cuuint64_t*,
                             const cuuint32_t*, const cuuint32_t*, CUtensorMapInterleave, CUtensorMapSwizzle,
                             CUtensorMapL2promotion, CUtensorMapFloatOOBfill);

struct HostState {
    bool ready;
    const void* key[11];
    CUtensorMap wq, wk, wv, w1, qo, ho, hi, oi, w2, wo, xi, gi, out;
    void *pQ, *pKV, *pH, *pO, *pMax, *pRow, *pCol, *pFlag, *pG;
};
HostState g_hs;

void make_map(EncodeFn fn, CUtensorMap* m, const void* ptr, uint64_t inner, uint64_t outer, uint32_t box_in, uint32_t box_out) {
    cuuint64_t dims[2] = {inner, outer};
    cuuint64_t strides[1] = {inner * 2};
    cuuint32_t box[2] = {box_in, box_out};
    cuuint32_t es[2] = {1, 1};
    fn(m, CU_TENSOR_MAP_DATA_TYPE_BFLOAT16, 2, const_cast<void*>(ptr), dims, strides, box, es, CU_TENSOR_MAP_INTERLEAVE_NONE,
       CU_TENSOR_MAP_SWIZZLE_128B, CU_TENSOR_MAP_L2_PROMOTION_L2_256B, CU_TENSOR_MAP_FLOAT_OOB_FILL_NONE);
}

template <typename... KArgs, typename... Args>
void launch(void (*kern)(KArgs...), int grid, int block, int smem, bool pdl, int cluster, Args... args) {
    cudaLaunchConfig_t cfg = {};
    cfg.gridDim = dim3(grid); cfg.blockDim = dim3(block); cfg.dynamicSmemBytes = smem; cfg.stream = cudaStreamPerThread;
    cudaLaunchAttribute at[2];
    int n = 0;
    if (pdl) { at[n].id = cudaLaunchAttributeProgrammaticStreamSerialization; at[n].val.programmaticStreamSerializationAllowed = 1; n++; }
    if (cluster > 1) { at[n].id = cudaLaunchAttributeClusterDimension; at[n].val.clusterDim.x = cluster; at[n].val.clusterDim.y = 1; at[n].val.clusterDim.z = 1; n++; }
    cfg.attrs = at; cfg.numAttrs = n;
    cudaLaunchKernelEx(&cfg, kern, KArgs(args)...);
}

}

extern "C" void kernel_launch(void* const* d_in, const int* in_sizes, int n_in, void* d_out, int out_size) {
    (void)in_sizes; (void)n_in; (void)out_size;
    HostState& hs = g_hs;
    bool same = hs.ready;
    for (int i = 0; i < 10 && same; i++) same = hs.key[i] == d_in[i];
    same = same && hs.key[10] == d_out;
    if (!same) {
        void* fp = nullptr;
        cudaDriverEntryPointQueryResult qr;
        cudaGetDriverEntryPoint("cuTensorMapEncodeTiled", &fp, cudaEnableDefault, &qr);
        EncodeFn fn = (EncodeFn)fp;
        cudaGetSymbolAddress(&hs.pQ, g_Q); cudaGetSymbolAddress(&hs.pKV, g_KV); cudaGetSymbolAddress(&hs.pH, g_H);
        cudaGetSymbolAddress(&hs.pO, g_O); cudaGetSymbolAddress(&hs.pMax, g_kvmax);
        cudaGetSymbolAddress(&hs.pRow, g_rowstat); cudaGetSymbolAddress(&hs.pCol, g_colpart); cudaGetSymbolAddress(&hs.pG, g_G);
        make_map(fn, &hs.wq, d_in[1], 512, 512, 64, 64);
        make_map(fn, &hs.wk, d_in[2], 16, 512, 64, 64);
        make_map(fn, &hs.wv, d_in[3], 16, 512, 64, 64);
        make_map(fn, &hs.w1, d_in[6], F_DIM, 512, 64, 64);
        make_map(fn, &hs.qo, hs.pQ, 512, S_LEN, 64, 16);
        make_map(fn, &hs.ho, hs.pH, F_DIM, S_LEN, 64, 16);
        make_map(fn, &hs.hi, hs.pH, F_DIM, S_LEN, 64, 64);
        make_map(fn, &hs.gi, hs.pG, 512, S_LEN, 64, 128);
        make_map(fn, &hs.oi, hs.pO, 512, S_LEN, 64, 128);
        make_map(fn, &hs.w2, d_in[8], 512, F_DIM, 64, 64);
        make_map(fn, &hs.wo, d_in[4], 512, 512, 64, 64);
        make_map(fn, &hs.xi, d_in[0], 512, S_LEN, 64, 128);
        make_map(fn, &hs.out, d_out, 512, S_LEN, 64, 16);
        cudaFuncSetAttribute(k1_proj, cudaFuncAttributeMaxDynamicSharedMemorySize, K1_SMEM);
        cudaFuncSetAttribute(k2_attn, cudaFuncAttributeMaxDynamicSharedMemorySize, AT_SMEM);
        cudaFuncSetAttribute(k3_out, cudaFuncAttributeMaxDynamicSharedMemorySize, K3_SMEM);
        for (int i = 0; i < 10; i++) hs.key[i] = d_in[i];
        hs.key[10] = d_out;
        hs.ready = true;
    }
    launch(k1_proj, 128, 384, K1_SMEM, false, 2, hs.xi, hs.wq, hs.wk, hs.wv, hs.w1, hs.qo, hs.ho, (const __nv_bfloat16*)d_in[0],
           (const __nv_bfloat16*)d_in[7], (float2*)hs.pRow, (float*)hs.pCol, (__nv_bfloat16*)hs.pKV, (float*)hs.pMax);
    launch(k2_attn, 128, 640, AT_SMEM, true, 1, hs.hi, hs.w2, (const __nv_bfloat16*)hs.pQ, (const __nv_bfloat16*)hs.pKV,
           (const float*)hs.pMax, (const __nv_bfloat16*)d_in[9], (__nv_bfloat16*)hs.pO, (__nv_bfloat16*)hs.pG, (uint2*)hs.pRow, (uint2*)hs.pCol);
    launch(k3_out, 128, 256, K3_SMEM, true, 1, hs.oi, hs.wo, hs.xi, hs.gi, hs.out);
}
```

```cpp
#include <cuda_runtime.h>
#include <cuda_bf16.h>
#include <cuda.h>
#include <stdint.h>

namespace {

constexpr int S_LEN = 2048, D_MODEL = 512, F_DIM = 1792;

__device__ __align__(1024) __nv_bfloat16 g_Q[S_LEN * D_MODEL];
__device__ __align__(1024) __nv_bfloat16 g_KV[6 * S_LEN * 8];
__device__ __align__(1024) __nv_bfloat16 g_G[S_LEN * D_MODEL];
__device__ __align__(1024) __nv_bfloat16 g_H[S_LEN * F_DIM];
__device__ __align__(1024) __nv_bfloat16 g_O[S_LEN * D_MODEL];
__device__ __align__(1024) float g_kvmax[256];
__device__ __align__(1024) float2 g_rowstat[S_LEN];
__device__ __align__(1024) float g_colpart[8 * 16 * 320];

#define DEV_STAMP(k, e) do {} while (0)
__device__ __forceinline__ uint32_t smem_u32(const void* p) { return (uint32_t)__cvta_generic_to_shared(p); }
__device__ __forceinline__ void wg_fence() { asm volatile("wgmma.fence.sync.aligned;" ::: "memory"); }
__device__ __forceinline__ void wg_commit() { asm volatile("wgmma.commit_group.sync.aligned;" ::: "memory"); }
template <int N> __device__ __forceinline__ void wg_wait() { asm volatile("wgmma.wait_group.sync.aligned %0;" ::"n"(N) : "memory"); }
template <int N> __device__ __forceinline__ void fence_regs(float* r) {
#pragma unroll
    for (int i = 0; i < N; i++) asm volatile("" : "+f"(r[i])::"memory");
}
__device__ __forceinline__ void fence_proxy_async() { asm volatile("fence.proxy.async.shared::cta;" ::: "memory"); }
__device__ __forceinline__ void mbar_init(uint32_t bar, int cnt) { asm volatile("mbarrier.init.shared::cta.b64 [%0], %1;" ::"r"(bar), "r"(cnt) : "memory"); }
__device__ __forceinline__ void mbar_init_fence() { asm volatile("fence.mbarrier_init.release.cluster;" ::: "memory"); }
__device__ __forceinline__ void mbar_expect_tx(uint32_t bar, uint32_t bytes) {
    asm volatile("mbarrier.arrive.expect_tx.shared::cta.b64 _, [%0], %1;" ::"r"(bar), "r"(bytes) : "memory");
}
__device__ __forceinline__ void mbar_arrive(uint32_t bar) { asm volatile("mbarrier.arrive.shared::cta.b64 _, [%0];" ::"r"(bar) : "memory"); }
__device__ __forceinline__ bool mbar_try(uint32_t bar, uint32_t parity) {
    uint32_t ok;
    asm volatile("{\n.reg .pred p;\nmbarrier.try_wait.parity.shared::cta.b64 p, [%1], %2;\nselp.u32 %0, 1, 0, p;\n}\n"
                 : "=r"(ok) : "r"(bar), "r"(parity) : "memory");
    return ok != 0;
}
__device__ __forceinline__ void mbar_wait(uint32_t bar, uint32_t parity) {
    if (mbar_try(bar, parity)) return;
    const long long t0 = clock64();
#pragma unroll 1
    while (!mbar_try(bar, parity)) {
        if (clock64() - t0 > 20000000ll) {
            break;
        }
    }
}
__device__ __forceinline__ void bulk_g2s(uint32_t dst, const void* src, uint32_t bytes, uint32_t bar) {
    asm volatile("cp.async.bulk.shared::cluster.global.mbarrier::complete_tx::bytes [%0], [%1], %2, [%3];"
                 ::"r"(dst), "l"(src), "r"(bytes), "r"(bar) : "memory");
}
__device__ __forceinline__ void tma_load_2d(uint32_t dst, const CUtensorMap* tm, int c0, int c1, uint32_t bar) {
    asm volatile("cp.async.bulk.tensor.2d.shared::cluster.global.mbarrier::complete_tx::bytes [%0], [%1, {%3, %4}], [%2];"
                 ::"r"(dst), "l"((uint64_t)tm), "r"(bar), "r"(c0), "r"(c1) : "memory");
}
__device__ __forceinline__ void tma_load_2d_mc(uint32_t dst, const CUtensorMap* tm, int c0, int c1, uint32_t bar, uint16_t mask) {
    asm volatile("cp.async.bulk.tensor.2d.shared::cluster.global.mbarrier::complete_tx::bytes.multicast::cluster [%0], [%1, {%3, %4}], [%2], %5;"
                 ::"r"(dst), "l"((uint64_t)tm), "r"(bar), "r"(c0), "r"(c1), "h"(mask) : "memory");
}
__device__ __forceinline__ void mbar_arrive_remote(uint32_t bar, uint32_t cta) {
    asm volatile("{\n.reg .b32 ra;\nmapa.shared::cluster.u32 ra, %0, %1;\nmbarrier.arrive.shared::cluster.b64 _, [ra];\n}\n"
                 ::"r"(bar), "r"(cta) : "memory");
}
__device__ __forceinline__ uint2 ld_relaxed_v2(const void* p) {
    uint2 v; asm volatile("ld.relaxed.gpu.global.v2.b32 {%0,%1}, [%2];" : "=r"(v.x), "=r"(v.y) : "l"(p) : "memory"); return v;
}
constexpr uint32_t NOT_READY = 0u;
__device__ __forceinline__ float xch_enc(float v) { return __uint_as_float((v == 0.f ? 0u : __float_as_uint(v)) ^ 0x80000000u); }
__device__ __forceinline__ float xch_dec(uint32_t u) { return __uint_as_float(u ^ 0x80000000u); }
__device__ __forceinline__ void tma_store_2d(const CUtensorMap* tm, uint32_t src, int c0, int c1) {
    asm volatile("cp.async.bulk.tensor.2d.global.shared::cta.bulk_group [%0, {%2, %3}], [%1];"
                 ::"l"((uint64_t)tm), "r"(src), "r"(c0), "r"(c1) : "memory");
}
__device__ __forceinline__ void tma_store_commit() { asm volatile("cp.async.bulk.commit_group;" ::: "memory"); }
__device__ __forceinline__ void tma_store_wait() { asm volatile("cp.async.bulk.wait_group 0;" ::: "memory"); }
__device__ __forceinline__ void tma_prefetch_desc(const CUtensorMap* tm) { asm volatile("prefetch.tensormap [%0];" ::"l"((uint64_t)tm) : "memory"); }
__device__ __forceinline__ void named_bar_sync(int id, int n) { asm volatile("bar.sync %0, %1;" ::"r"(id), "r"(n) : "memory"); }
__device__ __forceinline__ void pdl_wait() { asm volatile("griddepcontrol.wait;" ::: "memory"); }
__device__ __forceinline__ void pdl_launch() { asm volatile("griddepcontrol.launch_dependents;" ::: "memory"); }
template <int N> __device__ __forceinline__ void reg_alloc() { asm volatile("setmaxnreg.inc.sync.aligned.u32 %0;" ::"n"(N)); }
template <int N> __device__ __forceinline__ void reg_dealloc() { asm volatile("setmaxnreg.dec.sync.aligned.u32 %0;" ::"n"(N)); }
__device__ __forceinline__ float ex2(float x) { float y; asm("ex2.approx.ftz.f32 %0, %1;" : "=f"(y) : "f"(x)); return y; }
__device__ __forceinline__ uint32_t pack_bf16(float lo, float hi) {
    uint32_t r; asm("cvt.rn.bf16x2.f32 %0, %1, %2;" : "=r"(r) : "f"(hi), "f"(lo)); return r;
}
__device__ __forceinline__ uint32_t pack_bf16_relu(float lo, float hi) {
    uint32_t r; asm("cvt.rn.relu.bf16x2.f32 %0, %1, %2;" : "=r"(r) : "f"(hi), "f"(lo)); return r;
}
__device__ __forceinline__ uint32_t mul_bf16x2(uint32_t a, uint32_t b) {
    uint32_t r; asm("mul.rn.bf16x2 %0, %1, %2;" : "=r"(r) : "r"(a), "r"(b)); return r;
}
__device__ __forceinline__ float bf_lo(uint32_t v) { return __uint_as_float(v << 16); }
__device__ __forceinline__ float bf_hi(uint32_t v) { return __uint_as_float(v & 0xFFFF0000u); }
__device__ __forceinline__ void stmatrix_x4(uint32_t addr, uint32_t r0, uint32_t r1, uint32_t r2, uint32_t r3) {
    asm volatile("stmatrix.sync.aligned.m8n8.x4.shared.b16 [%0], {%1,%2,%3,%4};" ::"r"(addr), "r"(r0), "r"(r1), "r"(r2), "r"(r3) : "memory");
}
__device__ __forceinline__ uint64_t make_desc(uint32_t addr, uint32_t lbo, uint32_t sbo, uint32_t swz) {
    return (uint64_t)((addr & 0x3FFFF) >> 4) | ((uint64_t)(lbo >> 4) << 16) | ((uint64_t)(sbo >> 4) << 32) | ((uint64_t)swz << 62);
}

__device__ __forceinline__ uint64_t desc64(uint32_t lo, uint32_t hi) {
    uint64_t d; asm("mov.b64 %0, {%1, %2};" : "=l"(d) : "r"(lo), "r"(hi)); return d;
}

__device__ __forceinline__ void wgmma_ss_n256_tb(float* d, uint64_t descA, uint64_t descB, int scaleD) {
    asm volatile("{\n.reg .pred p;\nsetp.ne.b32 p, %130, 0;\n"
      "wgmma.mma_async.sync.aligned.m64n256k16.f32.bf16.bf16 {%0,%1,%2,%3,%4,%5,%6,%7,%8,%9,%10,%11,%12,%13,%14,%15,%16,%17,%18,%19,%20,%21,%22,%23,%24,%25,%26,%27,%28,%29,%30,%31,%32,%33,%34,%35,%36,%37,%38,%39,%40,%41,%42,%43,%44,%45,%46,%47,%48,%49,%50,%51,%52,%53,%54,%55,%56,%57,%58,%59,%60,%61,%62,%63,%64,%65,%66,%67,%68,%69,%70,%71,%72,%73,%74,%75,%76,%77,%78,%79,%80,%81,%82,%83,%84,%85,%86,%87,%88,%89,%90,%91,%92,%93,%94,%95,%96,%97,%98,%99,%100,%101,%102,%103,%104,%105,%106,%107,%108,%109,%110,%111,%112,%113,%114,%115,%116,%117,%118,%119,%120,%121,%122,%123,%124,%125,%126,%127}, %128, %129, p, 1, 1, 0, 1;\n}\n"
      : "+f"(d[0]), "+f"(d[1]), "+f"(d[2]), "+f"(d[3]), "+f"(d[4]), "+f"(d[5]), "+f"(d[6]), "+f"(d[7]), "+f"(d[8]), "+f"(d[9]), "+f"(d[10]), "+f"(d[11]), "+f"(d[12]), "+f"(d[13]), "+f"(d[14]), "+f"(d[15]), "+f"(d[16]), "+f"(d[17]), "+f"(d[18]), "+f"(d[19]), "+f"(d[20]), "+f"(d[21]), "+f"(d[22]), "+f"(d[23]), "+f"(d[24]), "+f"(d[25]), "+f"(d[26]), "+f"(d[27]), "+f"(d[28]), "+f"(d[29]), "+f"(d[30]), "+f"(d[31]), "+f"(d[32]), "+f"(d[33]), "+f"(d[34]), "+f"(d[35]), "+f"(d[36]), "+f"(d[37]), "+f"(d[38]), "+f"(d[39]), "+f"(d[40]), "+f"(d[41]), "+f"(d[42]), "+f"(d[43]), "+f"(d[44]), "+f"(d[45]), "+f"(d[46]), "+f"(d[47]), "+f"(d[48]), "+f"(d[49]), "+f"(d[50]), "+f"(d[51]), "+f"(d[52]), "+f"(d[53]), "+f"(d[54]), "+f"(d[55]), "+f"(d[56]), "+f"(d[57]), "+f"(d[58]), "+f"(d[59]), "+f"(d[60]), "+f"(d[61]), "+f"(d[62]), "+f"(d[63]), "+f"(d[64]), "+f"(d[65]), "+f"(d[66]), "+f"(d[67]), "+f"(d[68]), "+f"(d[69]), "+f"(d[70]), "+f"(d[71]), "+f"(d[72]), "+f"(d[73]), "+f"(d[74]), "+f"(d[75]), "+f"(d[76]), "+f"(d[77]), "+f"(d[78]), "+f"(d[79]), "+f"(d[80]), "+f"(d[81]), "+f"(d[82]), "+f"(d[83]), "+f"(d[84]), "+f"(d[85]), "+f"(d[86]), "+f"(d[87]), "+f"(d[88]), "+f"(d[89]), "+f"(d[90]), "+f"(d[91]), "+f"(d[92]), "+f"(d[93]), "+f"(d[94]), "+f"(d[95]), "+f"(d[96]), "+f"(d[97]), "+f"(d[98]), "+f"(d[99]), "+f"(d[100]), "+f"(d[101]), "+f"(d[102]), "+f"(d[103]), "+f"(d[104]), "+f"(d[105]), "+f"(d[106]), "+f"(d[107]), "+f"(d[108]), "+f"(d[109]), "+f"(d[110]), "+f"(d[111]), "+f"(d[112]), "+f"(d[113]), "+f"(d[114]), "+f"(d[115]), "+f"(d[116]), "+f"(d[117]), "+f"(d[118]), "+f"(d[119]), "+f"(d[120]), "+f"(d[121]), "+f"(d[122]), "+f"(d[123]), "+f"(d[124]), "+f"(d[125]), "+f"(d[126]), "+f"(d[127])
      : "l"(descA), "l"(descB), "r"(scaleD));
}
__device__ __forceinline__ void wgmma_ss_n128_tb(float* d, uint64_t descA, uint64_t descB, int scaleD) {
    asm volatile("{\n.reg .pred p;\nsetp.ne.b32 p, %66, 0;\n"
      "wgmma.mma_async.sync.aligned.m64n128k16.f32.bf16.bf16 {%0,%1,%2,%3,%4,%5,%6,%7,%8,%9,%10,%11,%12,%13,%14,%15,%16,%17,%18,%19,%20,%21,%22,%23,%24,%25,%26,%27,%28,%29,%30,%31,%32,%33,%34,%35,%36,%37,%38,%39,%40,%41,%42,%43,%44,%45,%46,%47,%48,%49,%50,%51,%52,%53,%54,%55,%56,%57,%58,%59,%60,%61,%62,%63}, %64, %65, p, 1, 1, 0, 1;\n}\n"
      : "+f"(d[0]), "+f"(d[1]), "+f"(d[2]), "+f"(d[3]), "+f"(d[4]), "+f"(d[5]), "+f"(d[6]), "+f"(d[7]), "+f"(d[8]), "+f"(d[9]), "+f"(d[10]), "+f"(d[11]), "+f"(d[12]), "+f"(d[13]), "+f"(d[14]), "+f"(d[15]), "+f"(d[16]), "+f"(d[17]), "+f"(d[18]), "+f"(d[19]), "+f"(d[20]), "+f"(d[21]), "+f"(d[22]), "+f"(d[23]), "+f"(d[24]), "+f"(d[25]), "+f"(d[26]), "+f"(d[27]), "+f"(d[28]), "+f"(d[29]), "+f"(d[30]), "+f"(d[31]), "+f"(d[32]), "+f"(d[33]), "+f"(d[34]), "+f"(d[35]), "+f"(d[36]), "+f"(d[37]), "+f"(d[38]), "+f"(d[39]), "+f"(d[40]), "+f"(d[41]), "+f"(d[42]), "+f"(d[43]), "+f"(d[44]), "+f"(d[45]), "+f"(d[46]), "+f"(d[47]), "+f"(d[48]), "+f"(d[49]), "+f"(d[50]), "+f"(d[51]), "+f"(d[52]), "+f"(d[53]), "+f"(d[54]), "+f"(d[55]), "+f"(d[56]), "+f"(d[57]), "+f"(d[58]), "+f"(d[59]), "+f"(d[60]), "+f"(d[61]), "+f"(d[62]), "+f"(d[63])
      : "l"(descA), "l"(descB), "r"(scaleD));
}
__device__ __forceinline__ void wgmma_ss_n64_tb(float* d, uint64_t descA, uint64_t descB, int scaleD) {
    asm volatile("{\n.reg .pred p;\nsetp.ne.b32 p, %34, 0;\n"
      "wgmma.mma_async.sync.aligned.m64n64k16.f32.bf16.bf16 {%0,%1,%2,%3,%4,%5,%6,%7,%8,%9,%10,%11,%12,%13,%14,%15,%16,%17,%18,%19,%20,%21,%22,%23,%24,%25,%26,%27,%28,%29,%30,%31}, %32, %33, p, 1, 1, 0, 1;\n}\n"
      : "+f"(d[0]), "+f"(d[1]), "+f"(d[2]), "+f"(d[3]), "+f"(d[4]), "+f"(d[5]), "+f"(d[6]), "+f"(d[7]), "+f"(d[8]), "+f"(d[9]), "+f"(d[10]), "+f"(d[11]), "+f"(d[12]), "+f"(d[13]), "+f"(d[14]), "+f"(d[15]), "+f"(d[16]), "+f"(d[17]), "+f"(d[18]), "+f"(d[19]), "+f"(d[20]), "+f"(d[21]), "+f"(d[22]), "+f"(d[23]), "+f"(d[24]), "+f"(d[25]), "+f"(d[26]), "+f"(d[27]), "+f"(d[28]), "+f"(d[29]), "+f"(d[30]), "+f"(d[31])
      : "l"(descA), "l"(descB), "r"(scaleD));
}
__device__ __forceinline__ void wgmma_qk_acc_n64(float* d, const uint32_t* a, uint64_t descB) {
    asm volatile("wgmma.mma_async.sync.aligned.m64n64k16.f32.bf16.bf16 {%0,%1,%2,%3,%4,%5,%6,%7,%8,%9,%10,%11,%12,%13,%14,%15,%16,%17,%18,%19,%20,%21,%22,%23,%24,%25,%26,%27,%28,%29,%30,%31}, {%32,%33,%34,%35}, %36, 1, 1, 1, 0;\n"
      : "+f"(d[0]), "+f"(d[1]), "+f"(d[2]), "+f"(d[3]), "+f"(d[4]), "+f"(d[5]), "+f"(d[6]), "+f"(d[7]), "+f"(d[8]), "+f"(d[9]), "+f"(d[10]), "+f"(d[11]), "+f"(d[12]), "+f"(d[13]), "+f"(d[14]), "+f"(d[15]), "+f"(d[16]), "+f"(d[17]), "+f"(d[18]), "+f"(d[19]), "+f"(d[20]), "+f"(d[21]), "+f"(d[22]), "+f"(d[23]), "+f"(d[24]), "+f"(d[25]), "+f"(d[26]), "+f"(d[27]), "+f"(d[28]), "+f"(d[29]), "+f"(d[30]), "+f"(d[31])
      : "r"(a[0]), "r"(a[1]), "r"(a[2]), "r"(a[3]), "l"(descB));
}

__device__ __forceinline__ void wgmma_pv(float* d, uint32_t a0, uint32_t a1, uint32_t a2, uint32_t a3, uint64_t descB) {
    asm volatile("wgmma.mma_async.sync.aligned.m64n24k16.f32.bf16.bf16 {%0,%1,%2,%3,%4,%5,%6,%7,%8,%9,%10,%11}, {%12,%13,%14,%15}, %16, 1, 1, 1, 1;\n"
                 : "+f"(d[0]), "+f"(d[1]), "+f"(d[2]), "+f"(d[3]), "+f"(d[4]), "+f"(d[5]), "+f"(d[6]), "+f"(d[7]), "+f"(d[8]), "+f"(d[9]), "+f"(d[10]), "+f"(d[11])
                 : "r"(a0), "r"(a1), "r"(a2), "r"(a3), "l"(descB));
}

__device__ __forceinline__ void k1_panel(int g, int i, int& type, int& col) {
    if (g < 6) {
        int p = g * 5 + i;
        if (p < 8) { type = 0; col = p * 64; } else { type = 1; col = (p - 8) * 64; }
    } else {
        if (i < 3) { type = 1; col = (22 + (g - 6) * 3 + i) * 64; } else { type = 2 + (g - 6); col = 0; }
    }
}

constexpr int K1_STAGES = 4;
constexpr int K1_PANEL_BYTES = 64 * 128;
constexpr int K1_STAGE_BYTES = 16384 + 5 * K1_PANEL_BYTES;
constexpr int K1_SMEM = K1_STAGES * K1_STAGE_BYTES + 128 + 320 * 8;
constexpr float Q_SCALE = 0.25f * 1.4426950408889634f;

__global__ void __launch_bounds__(384, 1)
k1_proj(const __grid_constant__ CUtensorMap tm_x, const __grid_constant__ CUtensorMap tm_wq,
        const __grid_constant__ CUtensorMap tm_wk, const __grid_constant__ CUtensorMap tm_wv,
        const __grid_constant__ CUtensorMap tm_w1, const __grid_constant__ CUtensorMap tm_qo,
        const __grid_constant__ CUtensorMap tm_ho, const __nv_bfloat16* __restrict__ x, const __nv_bfloat16* __restrict__ b1,
        float2* rowstat, float* colpart,
        __nv_bfloat16* __restrict__ kv, float* __restrict__ kvmax) {
    extern __shared__ __align__(1024) uint8_t smem_raw[];
    const uint32_t sbase = smem_u32(smem_raw);
    const uint32_t bar_full = sbase + K1_STAGES * K1_STAGE_BYTES, bar_empty = bar_full + 8 * K1_STAGES, bar_col = bar_empty + 8 * K1_STAGES;
    const uint32_t sCol = bar_full + 128;
    const int tid = threadIdx.x, warp = __shfl_sync(0xffffffffu, tid >> 5, 0), lane = tid & 31;
    const int crank = blockIdx.x & 1, grp = (blockIdx.x >> 1) & 7, rb = (blockIdx.x >> 4) * 2 + crank;
    const int npanels = grp < 6 ? 5 : 4;
    if (tid == 0) DEV_STAMP(0, 0);

    if (tid == 288) {
        tma_prefetch_desc(&tm_x); tma_prefetch_desc(&tm_w1); tma_prefetch_desc(grp < 2 ? &tm_wq : grp == 6 ? &tm_wk : &tm_wv);
        tma_prefetch_desc(&tm_ho); tma_prefetch_desc(&tm_qo);
    }
    uint4 v[2][2];
    if (warp < 8) {
        const uint4* xp = reinterpret_cast<const uint4*>(x + (size_t)(rb * 128 + grp * 16 + warp * 2) * D_MODEL);
#pragma unroll
        for (int r = 0; r < 2; r++) { v[r][0] = __ldg(xp + r * 64 + lane); v[r][1] = __ldg(xp + r * 64 + 32 + lane); }
    }
    const int krot = rb & 8 ? 4 : 0, cstage = (rb >> 1) & 3;
    if (tid == 256) {
        for (int s = 0; s < K1_STAGES; s++) { mbar_init(bar_full + 8 * s, 1); mbar_init(bar_empty + 8 * s, s == cstage ? 18 : 16); }
        mbar_init(bar_col, 96);
        mbar_init_fence();
    }
    asm volatile("barrier.cluster.arrive.relaxed;" ::: "memory");
    if (warp != 8) asm volatile("barrier.cluster.wait;" ::: "memory");
    pdl_launch();

    if (warp >= 8) {
        reg_dealloc<88>();
        if (warp == 8) {
            const CUtensorMap* tms[5]; int cols[5];
#pragma unroll
            for (int i = 0; i < 5; i++) {
                int type, col; k1_panel(grp, i, type, col);
                tms[i] = type == 0 ? &tm_wq : type == 1 ? &tm_w1 : type == 2 ? &tm_wk : &tm_wv;
                cols[i] = col;
            }
            if (lane == 0) {
                mbar_expect_tx(bar_full, 16384 + npanels * K1_PANEL_BYTES);
                tma_load_2d(sbase, &tm_x, krot * 64, rb * 128, bar_full);
#pragma unroll
                for (int i = 0; i < 5; i++)
                    if (i < npanels) tma_load_2d(sbase + 16384 + i * K1_PANEL_BYTES, tms[i], cols[i], krot * 64, bar_full);
            }
            __syncwarp();
            asm volatile("barrier.cluster.wait;" ::: "memory");
            if (lane == 0) {
                for (int ks = 1; ks < 8; ks++) {
                    const int s = ks % K1_STAGES;
                    const uint32_t st = sbase + s * K1_STAGE_BYTES;
                    mbar_wait(bar_empty + 8 * s, ((ks / K1_STAGES) & 1) ^ 1);
                    const int k0 = ((ks + krot) & 7) * 64;
                    mbar_expect_tx(bar_full + 8 * s, 16384 + npanels * K1_PANEL_BYTES);
                    tma_load_2d(st, &tm_x, k0, rb * 128, bar_full + 8 * s);
#pragma unroll
                    for (int i = 0; i < 5; i++)
                        if (i < npanels && ((i + ks + crank) & 1) == 0)
                            tma_load_2d_mc(st + 16384 + i * K1_PANEL_BYTES, tms[i], cols[i], k0, bar_full + 8 * s, (uint16_t)3);
                }
            }
        } else {
            const int ht = tid - 288;
            mbar_wait(bar_full + 8 * cstage, 0);
            {
                const int pc = ht >> 1, half = ht & 1;
                float sacc[8];
#pragma unroll
                for (int c = 0; c < 8; c++) sacc[c] = 0.f;
                if (pc < npanels * 8) {
                    const uint32_t pb = sbase + cstage * K1_STAGE_BYTES + 16384 + (pc >> 3) * K1_PANEL_BYTES;
#pragma unroll
                    for (int i = 0; i < 16; i++) {
                        const int k = crank * 32 + 2 * i + half;
                        uint4 u;
                        asm volatile("ld.shared.v4.b32 {%0,%1,%2,%3}, [%4];" : "=r"(u.x), "=r"(u.y), "=r"(u.z), "=r"(u.w)
                                     : "r"(pb + k * 128 + (((pc & 7) ^ (k & 7)) << 4)));
                        sacc[0] += bf_lo(u.x); sacc[1] += bf_hi(u.x); sacc[2] += bf_lo(u.y); sacc[3] += bf_hi(u.y);
                        sacc[4] += bf_lo(u.z); sacc[5] += bf_hi(u.z); sacc[6] += bf_lo(u.w); sacc[7] += bf_hi(u.w);
                    }
                }
#pragma unroll
                for (int c = 0; c < 8; c++) sacc[c] += __shfl_xor_sync(0xffffffffu, sacc[c], 1);
                if (pc < npanels * 8) {
                    float4* dst = reinterpret_cast<float4*>(colpart + (grp * 16 + rb) * 320 + pc * 8) + half;
                    *dst = half ? make_float4(xch_enc(sacc[4]), xch_enc(sacc[5]), xch_enc(sacc[6]), xch_enc(sacc[7]))
                                : make_float4(xch_enc(sacc[0]), xch_enc(sacc[1]), xch_enc(sacc[2]), xch_enc(sacc[3]));
                }
                named_bar_sync(4, 96);
                if (ht < 2) mbar_arrive_remote(bar_empty + 8 * cstage, ht);
            }
            if (ht == 0) DEV_STAMP(0, 6);
            for (int c2 = ht; c2 < npanels * 32; c2 += 96) {
                int type, col; k1_panel(grp, c2 >> 5, type, col);
                uint32_t bb = 0;
                if (type == 1) bb = __ldg(reinterpret_cast<const uint32_t*>(b1 + col) + (c2 & 31));
                uint2 pv[16];
                bool okv = false;
#pragma unroll 1
                for (uint32_t n = 0; n < (1u << 14) && !okv; n++) {
                    okv = true;
#pragma unroll
                    for (int k = 0; k < 16; k++) pv[k] = ld_relaxed_v2(colpart + (grp * 16 + k) * 320 + c2 * 2);
#pragma unroll
                    for (int k = 0; k < 16; k++) okv = okv && pv[k].x != NOT_READY && pv[k].y != NOT_READY;
                }
                float s0 = 0.f, s1 = 0.f;
#pragma unroll
                for (int k = 0; k < 16; k++) { s0 += xch_dec(pv[k].x); s1 += xch_dec(pv[k].y); }
                asm volatile("st.shared.v4.f32 [%0], {%1,%2,%3,%4};" ::"r"(sCol + c2 * 16), "f"(s0), "f"(bf_lo(bb)), "f"(s1), "f"(bf_hi(bb)) : "memory");
            }
            mbar_arrive(bar_col);
            if (ht == 0) DEV_STAMP(0, 7);
        }
    } else {
        reg_alloc<208>();
        const int wg = warp >> 2;
        const int g = lane >> 2, t = lane & 3;
        const int wrow = (warp & 3) * 16;
        {
            float f[2][16], sum[2], sq[2];
#pragma unroll
            for (int r = 0; r < 2; r++) {
                const uint32_t w[8] = {v[r][0].x, v[r][0].y, v[r][0].z, v[r][0].w, v[r][1].x, v[r][1].y, v[r][1].z, v[r][1].w};
#pragma unroll
                for (int i = 0; i < 8; i++) { f[r][2 * i] = bf_lo(w[i]); f[r][2 * i + 1] = bf_hi(w[i]); }
                sum[r] = 0.f;
#pragma unroll
                for (int i = 0; i < 16; i++) sum[r] += f[r][i];
            }
#pragma unroll
            for (int o = 16; o > 0; o >>= 1) { sum[0] += __shfl_xor_sync(0xffffffffu, sum[0], o); sum[1] += __shfl_xor_sync(0xffffffffu, sum[1], o); }
#pragma unroll
            for (int r = 0; r < 2; r++) {
                sum[r] *= (1.0f / D_MODEL);
                sq[r] = 0.f;
#pragma unroll
                for (int i = 0; i < 16; i++) { const float d = f[r][i] - sum[r]; sq[r] += d * d; }
            }
#pragma unroll
            for (int o = 16; o > 0; o >>= 1) { sq[0] += __shfl_xor_sync(0xffffffffu, sq[0], o); sq[1] += __shfl_xor_sync(0xffffffffu, sq[1], o); }
            if (lane < 2) {
                const float rstd = rsqrtf((lane ? sq[1] : sq[0]) * (1.0f / D_MODEL) + 1e-5f);
                rowstat[rb * 128 + grp * 16 + warp * 2 + lane] = make_float2(xch_enc(rstd), (lane ? sum[1] : sum[0]) * rstd);
            }
            if (tid == 0) DEV_STAMP(0, 5);
        }
        float acc[160];
#pragma unroll
        for (int i = 0; i < 160; i++) acc[i] = 0.f;
        float2 rs0, rs1;
        const uint64_t dA0 = make_desc(sbase + wg * 8192, 16, 1024, 1);
        const uint64_t dB0 = make_desc(sbase + 16384, K1_PANEL_BYTES, 1024, 1);
#define K1_MAINLOOP(FIVE)                                                                                          \
        for (int ks = 0; ks < 8; ks++) {                                                                           \
            const int s = ks % K1_STAGES;                                                                          \
            mbar_wait(bar_full + 8 * s, (ks / K1_STAGES) & 1);                                                     \
            if (ks == 0 && tid == 0) DEV_STAMP(0, 1);                                                              \
            wg_fence();                                                                                            \
            _Pragma("unroll") for (int kk = 0; kk < 4; kk++) {                                                     \
                const uint64_t dA = dA0 + (uint64_t)((s * K1_STAGE_BYTES + kk * 32) >> 4);                         \
                const uint64_t dB = dB0 + (uint64_t)((s * K1_STAGE_BYTES + kk * 2048) >> 4);                       \
                wgmma_ss_n256_tb(acc, dA, dB, (ks | kk) != 0);                                                     \
                if (FIVE) wgmma_ss_n64_tb(acc + 128, dA, dB + (uint64_t)((4 * K1_PANEL_BYTES) >> 4), (ks | kk) != 0); \
            }                                                                                                      \
            wg_commit();                                                                                           \
            if (ks == 7) {                                                                                         \
                uint2 r0, r1;                                                                                      \
                uint32_t n = 0;                                                                                    \
                _Pragma("unroll 1") do {                                                                           \
                    r0 = ld_relaxed_v2(rowstat + rb * 128 + wg * 64 + wrow + g);                                   \
                    r1 = ld_relaxed_v2(rowstat + rb * 128 + wg * 64 + wrow + g + 8);                               \
                } while ((r0.x == NOT_READY || r1.x == NOT_READY) && ++n < (1u << 14));                            \
                rs0 = make_float2(xch_dec(r0.x), __uint_as_float(r0.y));                                           \
                rs1 = make_float2(xch_dec(r1.x), __uint_as_float(r1.y));                                           \
                mbar_wait(bar_col, 0);                                                                             \
            }                                                                                                      \
            if (ks > 0 && ks <= 4) {                                                                               \
                wg_wait<1>();                                                                                      \
                if (lane < 2) mbar_arrive_remote(bar_empty + 8 * ((ks - 1) % K1_STAGES), lane);                    \
            }                                                                                                      \
        }                                                                                                          \
        wg_wait<0>();
        const int srow = (lane & 7) + ((lane >> 3) & 1) * 8;
        if (npanels == 5) { K1_MAINLOOP(true) } else { K1_MAINLOOP(false) }
        fence_regs<160>(acc);
        if (tid == 0) DEV_STAMP(0, 2);
        named_bar_sync(1, 256);
#pragma unroll
        for (int p = 0; p < 5; p++) {
            if (p < npanels) {
                int type, col; k1_panel(grp, p, type, col);
                float* a = acc + p * 32;
                const int nj = type <= 1 ? 8 : 2;
                const float sc = type == 0 ? Q_SCALE : 1.0f;
                const float r0x = rs0.x * sc, r0y = -rs0.y * sc, r1x = rs1.x * sc, r1y = -rs1.y * sc;
#pragma unroll
                for (int j = 0; j < 8; j++) {
                    if (j < nj) {
                        float4 c;
                        asm volatile("ld.shared.v4.f32 {%0,%1,%2,%3}, [%4];" : "=f"(c.x), "=f"(c.y), "=f"(c.z), "=f"(c.w)
                                     : "r"(sCol + (p * 64 + j * 8 + 2 * t) * 8));
                        a[4 * j] = fmaf(a[4 * j], r0x, fmaf(r0y, c.x, c.y));
                        a[4 * j + 1] = fmaf(a[4 * j + 1], r0x, fmaf(r0y, c.z, c.w));
                        a[4 * j + 2] = fmaf(a[4 * j + 2], r1x, fmaf(r1y, c.x, c.y));
                        a[4 * j + 3] = fmaf(a[4 * j + 3], r1x, fmaf(r1y, c.z, c.w));
                    }
                }
                if (type <= 1) {
                    const uint32_t stg = sbase + (p * 8 + warp) * 2048;
                    uint32_t pk[16];
                    if (type == 0) {
#pragma unroll
                        for (int j = 0; j < 8; j++) {
                            pk[2 * j] = pack_bf16(a[4 * j], a[4 * j + 1]);
                            pk[2 * j + 1] = pack_bf16(a[4 * j + 2], a[4 * j + 3]);
                        }
                    } else {
#pragma unroll
                        for (int j = 0; j < 8; j++) {
                            const uint32_t h0 = pack_bf16_relu(a[4 * j], a[4 * j + 1]), h1 = pack_bf16_relu(a[4 * j + 2], a[4 * j + 3]);
                            pk[2 * j] = mul_bf16x2(h0, h0);
                            pk[2 * j + 1] = mul_bf16x2(h1, h1);
                        }
                    }
#pragma unroll
                    for (int j = 0; j < 8; j += 2) {
                        const int c16 = j + (lane >> 4);
                        stmatrix_x4(stg + srow * 128 + ((c16 ^ (srow & 7)) << 4), pk[2 * j], pk[2 * j + 1], pk[2 * j + 2], pk[2 * j + 3]);
                    }
                    fence_proxy_async();
                    __syncwarp();
                    if (lane == 0) {
                        tma_store_2d(type == 0 ? &tm_qo : &tm_ho, stg, col, rb * 128 + warp * 16);
                        tma_store_commit();
                    }
                } else if (type == 3) {
                    const int r = wg * 64 + wrow + g;
                    const int pos0 = (r >> 2) * 64 + rb * 4 + (r & 3), pos1 = pos0 + 128;
                    uint32_t* dst = reinterpret_cast<uint32_t*>(kv);
                    const uint32_t r00 = pack_bf16(a[0], a[1]), r01 = pack_bf16(a[4], a[5]);
                    const uint32_t r10 = pack_bf16(a[2], a[3]), r11 = pack_bf16(a[6], a[7]);
                    dst[(pos0 >> 4) * 128 + (pos0 & 15) * 4 + t] = r00;
                    dst[16384 + pos0 * 4 + t] = r01;
                    dst[(pos1 >> 4) * 128 + (pos1 & 15) * 4 + t] = r10;
                    dst[16384 + pos1 * 4 + t] = r11;
                    float m = fmaxf(fmaxf(fmaxf(fabsf(bf_lo(r00)), fabsf(bf_hi(r00))), fmaxf(fabsf(bf_lo(r01)), fabsf(bf_hi(r01)))),
                                    fmaxf(fmaxf(fabsf(bf_lo(r10)), fabsf(bf_hi(r10))), fmaxf(fabsf(bf_lo(r11)), fabsf(bf_hi(r11)))));
#pragma unroll
                    for (int o = 16; o > 0; o >>= 1) m = fmaxf(m, __shfl_xor_sync(0xffffffffu, m, o));
                    if (lane == 0) kvmax[128 + rb * 8 + warp] = m;
                } else {
                    float* kf = reinterpret_cast<float*>(smem_raw + 96 * 1024);
                    const int r = wg * 64 + wrow + g;
                    const int pos0 = (r >> 2) * 64 + rb * 4 + (r & 3), pos1 = pos0 + 128;
                    uint32_t* dst = reinterpret_cast<uint32_t*>(kv) + 32768;
                    dst[(pos0 >> 3) * 64 + (pos0 & 7) * 4 + t] = pack_bf16(a[0], a[1]);
                    dst[(pos0 >> 3) * 64 + 32 + (pos0 & 7) * 4 + t] = pack_bf16(a[4], a[5]);
                    dst[(pos1 >> 3) * 64 + (pos1 & 7) * 4 + t] = pack_bf16(a[2], a[3]);
                    dst[(pos1 >> 3) * 64 + 32 + (pos1 & 7) * 4 + t] = pack_bf16(a[6], a[7]);
                    kf[r * 17 + 2 * t] = a[0]; kf[r * 17 + 2 * t + 1] = a[1];
                    kf[r * 17 + 8 + 2 * t] = a[4]; kf[r * 17 + 8 + 2 * t + 1] = a[5];
                    kf[(r + 8) * 17 + 2 * t] = a[2]; kf[(r + 8) * 17 + 2 * t + 1] = a[3];
                    kf[(r + 8) * 17 + 8 + 2 * t] = a[6]; kf[(r + 8) * 17 + 8 + 2 * t + 1] = a[7];
                    named_bar_sync(1, 256);
                    if (tid < 64) {
                        const int i = tid >> 4, dim = tid & 15;
                        const int c = rb * 4 + i;
                        const int inner = (dim >> 3) * 64 + (c & 7) * 8 + (dim & 7);
                        float kt = 0.f;
#pragma unroll 8
                        for (int j = 0; j < 32; j++) {
                            const __nv_bfloat16 d = __float2bfloat16_rn(kf[(j * 4 + i) * 17 + dim] - kt);
                            kt += __bfloat162float(d);
                            kf[(j * 4 + i) * 17 + dim] = kt;
                            const int gi = (j >> 1) * 8 + (c >> 3);
                            kv[((j & 1) ? 49152 + gi * 128 : gi * 256 + 128) + inner] = d;
                        }
                    }
                    named_bar_sync(1, 256);
                    if (tid < 128) {
                        float n = 0.f;
#pragma unroll
                        for (int d = 0; d < 16; d++) { const float v = kf[tid * 17 + d]; n += v * v; }
                        if (!(n == n)) n = __int_as_float(0x7f800000);
#pragma unroll
                        for (int o = 8; o > 0; o >>= 1) n = fmaxf(n, __shfl_xor_sync(0xffffffffu, n, o));
                        if ((lane & 15) == 0) kvmax[rb * 8 + (tid >> 4)] = n;
                    }
                }
            }
        }
        if (tid == 0) DEV_STAMP(0, 3);
        if (lane == 0) tma_store_wait();
        if (tid == 0) DEV_STAMP(0, 4);
    }
}

constexpr int AT_KT = 64;
constexpr int AT_NCHUNK = 8;
constexpr int AT_NSTEP = S_LEN / AT_KT;
constexpr int AT_SPC = AT_NSTEP / AT_NCHUNK;
constexpr int AT_ONES = 131072;
constexpr int F2_STAGES = 4;
constexpr int F2_STAGE_BYTES = 8192 + 16384;
constexpr int F2_BASE = 132096;
constexpr int F2_NK = F_DIM / 64;
constexpr int AT_BAR = F2_BASE + F2_STAGES * F2_STAGE_BYTES;
constexpr int AT_SMEM = AT_BAR + 256;
#define AT_SWMASK_V 0xB6DB
constexpr uint32_t AT_SWMASK = AT_SWMASK_V;

#define AT_MAGIC 382.41765f
__device__ __forceinline__ uint32_t exp2_pair_alu(float t0, float t1) {
    uint32_t y;
    asm("prmt.b32 %0, %1, %2, 0x6521;" : "=r"(y) : "f"(t0), "f"(t1));
    const uint32_t e = y & 0x7F807F80u;
    uint32_t uh, p;
    asm("lop3.b32 %0, %1, %2, 0x3F003F00, 0xBE;" : "=r"(uh) : "r"(y), "r"(e));
    asm("fma.rn.bf16x2 %0, %1, %2, %3;" : "=r"(p) : "r"(uh), "r"(y), "r"(e));
    return p;
}

__device__ __forceinline__ void at_load_chunk(uint32_t sbase, const __nv_bfloat16* KV, uint32_t bar0, int c) {
    const uint8_t* src = reinterpret_cast<const uint8_t*>(KV);
    mbar_expect_tx(bar0 + 8 * c, 16384);
    bulk_g2s(sbase + c * 8192, src + c * 8192, 8192, bar0 + 8 * c);
    bulk_g2s(sbase + 98304 + c * 4096, src + 98304 + c * 4096, 4096, bar0 + 8 * c);
    bulk_g2s(sbase + 65536 + c * 4096, src + 65536 + c * 4096, 4096, bar0 + 8 * c);
}

__device__ __forceinline__ void at_store(const float* o, __nv_bfloat16* O, int row, int lane) {
    const float l0 = __shfl_sync(0xffffffffu, o[8], lane & ~3);
    const float l1 = __shfl_sync(0xffffffffu, o[10], lane & ~3);
    const float r0 = __fdividef(1.0f, l0), r1 = __fdividef(1.0f, l1);
    const int t = lane & 3;
    uint32_t* op = reinterpret_cast<uint32_t*>(O + (size_t)(row + (lane >> 2)) * 16);
    op[t] = pack_bf16(o[0] * r0, o[1] * r0);
    op[t + 4] = pack_bf16(o[4] * r0, o[5] * r0);
    op[64 + t] = pack_bf16(o[2] * r1, o[3] * r1);
    op[64 + t + 4] = pack_bf16(o[6] * r1, o[7] * r1);
}

__device__ __forceinline__ void mma16816(float* c, const uint32_t* a, uint32_t b0, uint32_t b1) {
    asm volatile("mma.sync.aligned.m16n8k16.row.col.f32.bf16.bf16.f32 {%0,%1,%2,%3}, {%4,%5,%6,%7}, {%8,%9}, {%0,%1,%2,%3};"
                 : "+f"(c[0]), "+f"(c[1]), "+f"(c[2]), "+f"(c[3]) : "r"(a[0]), "r"(a[1]), "r"(a[2]), "r"(a[3]), "r"(b0), "r"(b1));
}
__device__ __forceinline__ void attn_fallback(const __nv_bfloat16* Q, const __nv_bfloat16* KV, __nv_bfloat16* O, uint32_t sbase) {
    const int tid = threadIdx.x;
    const int lane = tid & 31, g = lane >> 2, t = lane & 3;
    const uint32_t* Kg = reinterpret_cast<const uint32_t*>(KV + 65536);
#pragma unroll 1
    for (int mt = 0; mt < 2; mt++) {
        const int row = blockIdx.x * 512 + (tid >> 7) * 128 + mt * 64 + ((tid >> 5) & 3) * 16;
        const uint32_t* qp = reinterpret_cast<const uint32_t*>(Q + (size_t)(row + g) * 16);
        const uint32_t q[4] = {qp[t], qp[64 + t], qp[t + 4], qp[64 + t + 4]};
        float o[12];
#pragma unroll
        for (int i = 0; i < 12; i++) o[i] = 0.f;
        float m0 = -INFINITY, m1 = -INFINITY;
#pragma unroll 1
        for (int kt = 0; kt < S_LEN / 16; kt++) {
            float s[8];
#pragma unroll
            for (int i = 0; i < 8; i++) s[i] = 0.f;
#pragma unroll
            for (int h = 0; h < 2; h++) {
                const uint32_t* kp = Kg + (kt * 2 + h) * 64 + g * 4 + t;
                mma16816(s + 4 * h, q, kp[0], kp[32]);
            }
            float x0 = fmaxf(fmaxf(s[0], s[1]), fmaxf(s[4], s[5])), x1 = fmaxf(fmaxf(s[2], s[3]), fmaxf(s[6], s[7]));
            x0 = fmaxf(x0, __shfl_xor_sync(0xffffffffu, x0, 1)); x0 = fmaxf(x0, __shfl_xor_sync(0xffffffffu, x0, 2));
            x1 = fmaxf(x1, __shfl_xor_sync(0xffffffffu, x1, 1)); x1 = fmaxf(x1, __shfl_xor_sync(0xffffffffu, x1, 2));
            x0 = fmaxf(x0, m0); x1 = fmaxf(x1, m1);
            const float f0 = ex2(m0 - x0), f1 = ex2(m1 - x1);
            m0 = x0; m1 = x1;
#pragma unroll
            for (int j = 0; j < 3; j++) { o[4 * j] *= f0; o[4 * j + 1] *= f0; o[4 * j + 2] *= f1; o[4 * j + 3] *= f1; }
            const uint32_t p[4] = {pack_bf16(ex2(s[0] - m0), ex2(s[1] - m0)), pack_bf16(ex2(s[2] - m1), ex2(s[3] - m1)),
                                   pack_bf16(ex2(s[4] - m0), ex2(s[5] - m0)), pack_bf16(ex2(s[6] - m1), ex2(s[7] - m1))};
#pragma unroll
            for (int j = 0; j < 3; j++) {
                const uint32_t base = sbase + (j == 0 ? kt * 512 : j == 1 ? 65536 + kt * 256 : AT_ONES) + (lane & 15) * 16;
                uint32_t b0, b1;
                asm volatile("ldmatrix.sync.aligned.m8n8.x2.trans.shared.b16 {%0,%1}, [%2];" : "=r"(b0), "=r"(b1) : "r"(base));
                mma16816(o + 4 * j, p, b0, b1);
            }
        }
        at_store(o, O, row, lane);
    }
}

__global__ void __launch_bounds__(640, 1)
k2_attn(const __grid_constant__ CUtensorMap tm_h, const __grid_constant__ CUtensorMap tm_w2,
        const __nv_bfloat16* __restrict__ Q, const __nv_bfloat16* __restrict__ KV, const float* __restrict__ kvmax,
        const __nv_bfloat16* __restrict__ b2, __nv_bfloat16* __restrict__ O, __nv_bfloat16* __restrict__ G,
        uint2* __restrict__ rowstat, uint2* __restrict__ colpart) {
    extern __shared__ __align__(1024) uint8_t smem_raw[];
    const uint32_t sbase = smem_u32(smem_raw);
    const uint32_t bar0 = sbase + AT_BAR, f2_full = bar0 + 64, f2_empty = f2_full + 32, bar_guard = f2_empty + 32, bar_first = bar_guard + 8, sGuard = bar0 + 192;
    const int tid = threadIdx.x;
    const int wg = __shfl_sync(0xffffffffu, tid >> 7, 0);
    const int warp = (tid >> 5) & 3, lane = tid & 31;
    const int g = lane >> 2, t = lane & 3;
    if (tid == 0) DEV_STAMP(1, 0);
    if (tid == 0) {
        for (int i = 0; i < AT_NCHUNK; i++) mbar_init(bar0 + 8 * i, 1);
        for (int i = 0; i < F2_STAGES; i++) { mbar_init(f2_full + 8 * i, 1); mbar_init(f2_empty + 8 * i, 4); }
        mbar_init(bar_guard, 4);
        mbar_init(bar_first, 1);
        mbar_init_fence();
    }
    if (tid < 16) asm volatile("st.shared.v4.b32 [%0], {%1,%2,%2,%2};" ::"r"(sbase + AT_ONES + tid * 16), "r"(0x00003F80u), "r"(0u) : "memory");
    fence_proxy_async();
    __syncthreads();

    if (wg == 4) {
        const int rb = blockIdx.x >> 2, cb = blockIdx.x & 3;
        const uint32_t fb = sbase + F2_BASE;
        const bool leader = tid == 512;
        if (leader) {
#pragma unroll
            for (int s = 0; s < F2_STAGES; s++) {
                mbar_expect_tx(f2_full + 8 * s, F2_STAGE_BYTES);
                tma_load_2d(fb + s * F2_STAGE_BYTES + 8192, &tm_w2, cb * 128, s * 64, f2_full + 8 * s);
                tma_load_2d(fb + s * F2_STAGE_BYTES + 16384, &tm_w2, cb * 128 + 64, s * 64, f2_full + 8 * s);
            }
        }
        pdl_wait();
        mbar_wait(bar0, 0);
        if (leader) {
#pragma unroll
            for (int s = 0; s < F2_STAGES; s++) tma_load_2d(fb + s * F2_STAGE_BYTES, &tm_h, s * 64, rb * 64, f2_full + 8 * s);
        }
        {
            float km = fmaxf(fmaxf(kvmax[lane], kvmax[lane + 32]), fmaxf(kvmax[lane + 64], kvmax[lane + 96]));
            float vm = fmaxf(fmaxf(kvmax[128 + lane], kvmax[160 + lane]), fmaxf(kvmax[192 + lane], kvmax[224 + lane]));
            uint4 qv[4][2];
#pragma unroll
            for (int i = 0; i < 4; i++) {
                const uint4* qr = reinterpret_cast<const uint4*>(Q + (size_t)(blockIdx.x * 512 + warp * 128 + i * 16 + (lane >> 4) * 64 + (lane & 15)) * 16);
                qv[i][0] = qr[0]; qv[i][1] = qr[1];
            }
#pragma unroll
            for (int o = 16; o > 0; o >>= 1) { km = fmaxf(km, __shfl_xor_sync(0xffffffffu, km, o)); vm = fmaxf(vm, __shfl_xor_sync(0xffffffffu, vm, o)); }
#pragma unroll
            for (int i = 0; i < 4; i++) {
                const uint32_t qw[8] = {qv[i][0].x, qv[i][0].y, qv[i][0].z, qv[i][0].w, qv[i][1].x, qv[i][1].y, qv[i][1].z, qv[i][1].w};
                float qn = 0.f;
#pragma unroll
                for (int j = 0; j < 8; j++) qn += bf_lo(qw[j]) * bf_lo(qw[j]) + bf_hi(qw[j]) * bf_hi(qw[j]);
                const bool ok = (qn * km <= 3600.0f) && (vm <= 1.0e12f);
                const uint32_t bad = __any_sync(0xffffffffu, !ok);
                if (lane == 0) asm volatile("st.shared.u32 [%0], %1;" ::"r"(sGuard + (warp * 4 + i) * 4), "r"(bad) : "memory");
            }
            if (lane == 0) mbar_arrive(bar_guard);
        }
        __syncwarp();
        const uint64_t dA0 = make_desc(fb, 16, 1024, 1);
        const uint64_t dB0 = make_desc(fb + 8192, 8192, 1024, 1);
        float acc[64];
#pragma unroll
        for (int i = 0; i < 64; i++) asm volatile("mov.f32 %0, 0f00000000;" : "=f"(acc[i]));
#pragma unroll 1
        for (int ks = 0; ks < F2_NK; ks++) {
            const int s = ks % F2_STAGES;
            mbar_wait(f2_full + 8 * s, (ks / F2_STAGES) & 1);
            wg_fence();
#pragma unroll
            for (int kk = 0; kk < 4; kk++)
                wgmma_ss_n128_tb(acc, dA0 + (uint64_t)((s * F2_STAGE_BYTES + kk * 32) >> 4),
                                 dB0 + (uint64_t)((s * F2_STAGE_BYTES + kk * 2048) >> 4), 1);
            wg_commit();
            wg_wait<1>();
            if (ks > 0 && ks - 1 + F2_STAGES < F2_NK) {
                const int ps = (ks - 1) % F2_STAGES, k0 = (ks - 1 + F2_STAGES) * 64;
                if (lane == 0) mbar_arrive(f2_empty + 8 * ps);
                if (leader) {
                    mbar_wait(f2_empty + 8 * ps, ((ks - 1) / F2_STAGES) & 1);
                    mbar_expect_tx(f2_full + 8 * ps, F2_STAGE_BYTES);
                    tma_load_2d(fb + ps * F2_STAGE_BYTES, &tm_h, k0, rb * 64, f2_full + 8 * ps);
                    tma_load_2d(fb + ps * F2_STAGE_BYTES + 8192, &tm_w2, cb * 128, k0, f2_full + 8 * ps);
                    tma_load_2d(fb + ps * F2_STAGE_BYTES + 16384, &tm_w2, cb * 128 + 64, k0, f2_full + 8 * ps);
                }
                __syncwarp();
            }
        }
        wg_wait<0>();
        fence_regs<64>(acc);
        uint32_t* gp = reinterpret_cast<uint32_t*>(G + (size_t)(rb * 64 + warp * 16 + g) * D_MODEL + cb * 128) + t;
#pragma unroll
        for (int j = 0; j < 16; j++) {
            const uint32_t bb = __ldg(reinterpret_cast<const uint32_t*>(b2 + cb * 128 + j * 8) + t);
            const float b0 = bf_lo(bb), b1v = bf_hi(bb);
            const float z0 = acc[4 * j] + b0, z1 = acc[4 * j + 1] + b1v, z2 = acc[4 * j + 2] + b0, z3 = acc[4 * j + 3] + b1v;
            gp[j * 4] = pack_bf16(__fdividef(z0, 1.0f + __expf(-z0)), __fdividef(z1, 1.0f + __expf(-z1)));
            gp[j * 4 + 8 * (D_MODEL / 2)] = pack_bf16(__fdividef(z2, 1.0f + __expf(-z2)), __fdividef(z3, 1.0f + __expf(-z3)));
        }
        if (leader) DEV_STAMP(1, 5);
        return;
    }

    pdl_wait();
    pdl_launch();
    if (tid == 0) DEV_STAMP(1, 1);
    if (tid == 0) {
        const uint8_t* src = reinterpret_cast<const uint8_t*>(KV);
        mbar_expect_tx(bar_first, 4096);
        bulk_g2s(sbase, src, 4096, bar_first);
        mbar_expect_tx(bar0, 12288);
        bulk_g2s(sbase + 98304, src + 98304, 4096, bar0);
        bulk_g2s(sbase + 65536, src + 65536, 4096, bar0);
        bulk_g2s(sbase + 4096, src + 4096, 4096, bar0);
        at_load_chunk(sbase, KV, bar0, 1); at_load_chunk(sbase, KV, bar0, 2);
    }
    if (tid >= 128 && tid < 288) colpart[blockIdx.x * 160 + tid - 128] = make_uint2(NOT_READY, NOT_READY);
    if (tid >= 288 && tid < 304) rowstat[blockIdx.x * 16 + tid - 288] = make_uint2(NOT_READY, NOT_READY);
    const int rowA = blockIdx.x * 512 + wg * 128 + warp * 16;
    const uint32_t* qp = reinterpret_cast<const uint32_t*>(Q + (size_t)(rowA + g) * 16);
    const uint32_t lo0 = ((sbase & 0x3FFFF) >> 4) | (8u << 16);

#define AT_EXP(P) _Pragma("unroll") for (int i = 0; i < AT_KT / 4; i++) {                       \
                if ((AT_SWMASK >> (i & 15)) & 1) P[i] = exp2_pair_alu(s[2 * i], s[2 * i + 1]);  \
                else P[i] = pack_bf16(ex2(s[2 * i]), ex2(s[2 * i + 1])); }
    uint64_t vstep = 32ull - (16ull << 32);
    asm volatile("" : "+l"(vstep));
#define AT_PV1(P, j) { wgmma_pv(o, P[4 * (j)], P[4 * (j) + 1], P[4 * (j) + 2], P[4 * (j) + 3], dV); dV += vstep; }
#define AT_EXPH(P, h) _Pragma("unroll") for (int i = (h) * 8; i < (h) * 8 + 8; i++) {           \
                if ((AT_SWMASK >> (i & 15)) & 1) P[i] = exp2_pair_alu(s[2 * i], s[2 * i + 1]);  \
                else P[i] = pack_bf16(ex2(s[2 * i]), ex2(s[2 * i + 1])); }
#define AT_STEP(st, DK, INC) {                                                                  \
                wg_wait<0>();                                                                   \
                fence_regs<AT_KT / 2>(s);                                                       \
                AT_EXPH(p0, 0);                                                                 \
                wg_fence();                                                                     \
                AT_PV1(p0, 0); AT_PV1(p0, 1);                                                   \
                wg_commit();                                                                    \
                AT_EXPH(p0, 1);                                                                 \
                if (st == AT_SPC - 1 && mt == 0) mbar_wait(bar0 + 8 * (c + 1), 0);              \
                wg_wait<0>();                                                                   \
                wg_fence();                                                                     \
                wgmma_qk_acc_n64(s, q, DK); DK += INC;                                          \
                AT_PV1(p0, 2); AT_PV1(p0, 3);                                                   \
                wg_commit(); }

#pragma unroll 1
    for (int mt = 0; mt < 2; mt++) {
        uint32_t q[4];
        q[0] = qp[mt * 512 + t]; q[2] = qp[mt * 512 + t + 4]; q[1] = qp[mt * 512 + 64 + t]; q[3] = qp[mt * 512 + 64 + t + 4];
        float o[12];
#pragma unroll
        for (int i = 0; i < 12; i++) asm volatile("mov.f32 %0, 0f00000000;" : "=f"(o[i]));
        float s[AT_KT / 2];
        uint32_t p0[AT_KT / 4];
#pragma unroll
        for (int i = 0; i < AT_KT / 2; i++) {
            if ((AT_SWMASK >> ((i >> 1) & 15)) & 1) asm volatile("mov.f32 %0, %1;" : "=f"(s[i]) : "f"(AT_MAGIC));
            else asm volatile("mov.f32 %0, 0f00000000;" : "=f"(s[i]));
        }
        if (mt == 0) mbar_wait(bar_first, 0);
        if (tid == 0) DEV_STAMP(1, 2 + mt);
        uint64_t dV = desc64(lo0, 4096), dX = desc64(lo0 + 16, 32), dY = desc64(lo0 + (98304 >> 4), 16);
        wg_fence();
        wgmma_qk_acc_n64(s, q, dX); dX += 256;
        wg_commit();
        if (mt == 0) mbar_wait(bar0, 0);
#pragma unroll 1
        for (int c = 0; c < AT_NCHUNK - 1; c++) {
            if (tid == 0 && mt == 0 && c + 3 < AT_NCHUNK) at_load_chunk(sbase, KV, bar0, c + 3);
            AT_STEP(0, dY, 128); AT_STEP(1, dX, 256); AT_STEP(2, dY, 128); AT_STEP(3, dX, 256);
        }
        {
            const int c = 0; (void)c;
            AT_STEP(0, dY, 128); AT_STEP(1, dX, 256); AT_STEP(2, dY, 128);
            wg_wait<0>();
            fence_regs<AT_KT / 2>(s);
            AT_EXP(p0);
            wg_fence();
            AT_PV1(p0, 0); AT_PV1(p0, 1); AT_PV1(p0, 2); AT_PV1(p0, 3);
            wg_commit();
            wg_wait<0>();
            fence_regs<12>(o);
        }
        at_store(o, O, rowA + mt * 64, lane);
    }
    if (tid == 0) DEV_STAMP(1, 4);

    mbar_wait(bar_guard, 0);
    uint32_t bad;
    asm volatile("ld.shared.u32 %0, [%1];" : "=r"(bad) : "r"(sGuard + (tid >> 5) * 4) : "memory");
    if (__any_sync(0xffffffffu, bad != 0) == 0) return;
    attn_fallback(Q, KV, O, sbase);
}

constexpr int K3_STAGE_BYTES = 16384 + 8192;
constexpr int K3_X = 8 * K3_STAGE_BYTES;
constexpr int K3_G = K3_X + 16384;
constexpr int K3_SMEM = K3_G + 16384 + 256;

__global__ void __launch_bounds__(256, 1)
k3_out(const __grid_constant__ CUtensorMap tm_o, const __grid_constant__ CUtensorMap tm_wo,
       const __grid_constant__ CUtensorMap tm_x, const __grid_constant__ CUtensorMap tm_g,
       const __grid_constant__ CUtensorMap tm_out) {
    extern __shared__ __align__(1024) uint8_t smem_raw[];
    const uint32_t sbase = smem_u32(smem_raw);
    const uint32_t sX = sbase + K3_X, sG = sbase + K3_G;
    const uint32_t bar_full = sG + 16384, bar_x = bar_full + 64;
    const int tid = threadIdx.x, warp = __shfl_sync(0xffffffffu, tid >> 5, 0), lane = tid & 31;
    const int rb = blockIdx.x >> 3, cb = blockIdx.x & 7;
    if (tid == 0) {
        DEV_STAMP(2, 0);
        for (int s = 0; s < 8; s++) mbar_init(bar_full + 8 * s, 1);
        mbar_init(bar_x, 1);
        mbar_init_fence();
        for (int s = 0; s < 8; s++) {
            mbar_expect_tx(bar_full + 8 * s, K3_STAGE_BYTES);
            tma_load_2d(sbase + s * K3_STAGE_BYTES + 16384, &tm_wo, cb * 64, s * 64, bar_full + 8 * s);
        }
        mbar_expect_tx(bar_x, 32768);
        tma_load_2d(sX, &tm_x, cb * 64, rb * 128, bar_x);
        pdl_wait();
        DEV_STAMP(2, 1);
        for (int s = 0; s < 8; s++) tma_load_2d(sbase + s * K3_STAGE_BYTES, &tm_o, s * 64, rb * 128, bar_full + 8 * s);
        tma_load_2d(sG, &tm_g, cb * 64, rb * 128, bar_x);
    }
    __syncthreads();
    const int wg = warp >> 2;
    float acc[32];
#pragma unroll
    for (int i = 0; i < 32; i++) asm volatile("mov.f32 %0, 0f00000000;" : "=f"(acc[i]));
    const uint64_t dA0 = make_desc(sbase + wg * 8192, 16, 1024, 1);
    const uint64_t dB0 = make_desc(sbase + 16384, 8192, 1024, 1);
#pragma unroll 1
    for (int ks = 0; ks < 8; ks++) {
        mbar_wait(bar_full + 8 * ks, 0);
        wg_fence();
#pragma unroll
        for (int kk = 0; kk < 4; kk++)
            wgmma_ss_n64_tb(acc, dA0 + (uint64_t)((ks * K3_STAGE_BYTES + kk * 32) >> 4),
                            dB0 + (uint64_t)((ks * K3_STAGE_BYTES + kk * 2048) >> 4), 1);
        wg_commit();
    }
    wg_wait<0>();
    fence_regs<32>(acc);
    if (tid == 0) DEV_STAMP(2, 2);
    mbar_wait(bar_x, 0);
    const int g = lane >> 2, t = lane & 3;
    const int row0 = warp * 16 + g;
#pragma unroll
    for (int j = 0; j < 8; j++) {
#pragma unroll
        for (int h = 0; h < 2; h++) {
            const int row = row0 + h * 8;
            const uint32_t off = row * 128 + ((j ^ (row & 7)) << 4) + t * 4;
            uint32_t xv, gv;
            asm volatile("ld.shared.b32 %0, [%1];" : "=r"(xv) : "r"(sX + off) : "memory");
            asm volatile("ld.shared.b32 %0, [%1];" : "=r"(gv) : "r"(sG + off) : "memory");
            const uint32_t ov = pack_bf16(fmaf(acc[4 * j + 2 * h], bf_lo(gv), bf_lo(xv)), fmaf(acc[4 * j + 2 * h + 1], bf_hi(gv), bf_hi(xv)));
            asm volatile("st.shared.b32 [%0], %1;" ::"r"(sX + off), "r"(ov) : "memory");
        }
    }
    fence_proxy_async();
    __syncwarp();
    if (lane == 0) {
        tma_store_2d(&tm_out, sX + warp * 2048, cb * 64, rb * 128 + warp * 16);
        tma_store_commit();
        if (tid == 0) DEV_STAMP(2, 3);
        tma_store_wait();
        if (tid == 0) DEV_STAMP(2, 4);
    }
}

typedef CUresult (*EncodeFn)(CUtensorMap*, CUtensorMapDataType, cuuint32_t, void*, const cuuint64_t*, const cuuint64_t*,
                             const cuuint32_t*, const cuuint32_t*, CUtensorMapInterleave, CUtensorMapSwizzle,
                             CUtensorMapL2promotion, CUtensorMapFloatOOBfill);

struct HostState {
    bool ready;
    const void* key[11];
    CUtensorMap wq, wk, wv, w1, qo, ho, hi, oi, w2, wo, xi, gi, out;
    void *pQ, *pKV, *pH, *pO, *pMax, *pRow, *pCol, *pFlag, *pG;
};
HostState g_hs;

void make_map(EncodeFn fn, CUtensorMap* m, const void* ptr, uint64_t inner, uint64_t outer, uint32_t box_in, uint32_t box_out) {
    cuuint64_t dims[2] = {inner, outer};
    cuuint64_t strides[1] = {inner * 2};
    cuuint32_t box[2] = {box_in, box_out};
    cuuint32_t es[2] = {1, 1};
    fn(m, CU_TENSOR_MAP_DATA_TYPE_BFLOAT16, 2, const_cast<void*>(ptr), dims, strides, box, es, CU_TENSOR_MAP_INTERLEAVE_NONE,
       CU_TENSOR_MAP_SWIZZLE_128B, CU_TENSOR_MAP_L2_PROMOTION_L2_256B, CU_TENSOR_MAP_FLOAT_OOB_FILL_NONE);
}

template <typename... KArgs, typename... Args>
void launch(void (*kern)(KArgs...), int grid, int block, int smem, bool pdl, int cluster, Args... args) {
    cudaLaunchConfig_t cfg = {};
    cfg.gridDim = dim3(grid); cfg.blockDim = dim3(block); cfg.dynamicSmemBytes = smem; cfg.stream = cudaStreamPerThread;
    cudaLaunchAttribute at[2];
    int n = 0;
    if (pdl) { at[n].id = cudaLaunchAttributeProgrammaticStreamSerialization; at[n].val.programmaticStreamSerializationAllowed = 1; n++; }
    if (cluster > 1) { at[n].id = cudaLaunchAttributeClusterDimension; at[n].val.clusterDim.x = cluster; at[n].val.clusterDim.y = 1; at[n].val.clusterDim.z = 1; n++; }
    cfg.attrs = at; cfg.numAttrs = n;
    cudaLaunchKernelEx(&cfg, kern, KArgs(args)...);
}

}

extern "C" void kernel_launch(void* const* d_in, const int* in_sizes, int n_in, void* d_out, int out_size) {
    (void)in_sizes; (void)n_in; (void)out_size;
    HostState& hs = g_hs;
    bool same = hs.ready;
    for (int i = 0; i < 10 && same; i++) same = hs.key[i] == d_in[i];
    same = same && hs.key[10] == d_out;
    if (!same) {
        void* fp = nullptr;
        cudaDriverEntryPointQueryResult qr;
        cudaGetDriverEntryPoint("cuTensorMapEncodeTiled", &fp, cudaEnableDefault, &qr);
        EncodeFn fn = (EncodeFn)fp;
        cudaGetSymbolAddress(&hs.pQ, g_Q); cudaGetSymbolAddress(&hs.pKV, g_KV); cudaGetSymbolAddress(&hs.pH, g_H);
        cudaGetSymbolAddress(&hs.pO, g_O); cudaGetSymbolAddress(&hs.pMax, g_kvmax);
        cudaGetSymbolAddress(&hs.pRow, g_rowstat); cudaGetSymbolAddress(&hs.pCol, g_colpart); cudaGetSymbolAddress(&hs.pG, g_G);
        make_map(fn, &hs.wq, d_in[1], 512, 512, 64, 64);
        make_map(fn, &hs.wk, d_in[2], 16, 512, 64, 64);
        make_map(fn, &hs.wv, d_in[3], 16, 512, 64, 64);
        make_map(fn, &hs.w1, d_in[6], F_DIM, 512, 64, 64);
        make_map(fn, &hs.qo, hs.pQ, 512, S_LEN, 64, 16);
        make_map(fn, &hs.ho, hs.pH, F_DIM, S_LEN, 64, 16);
        make_map(fn, &hs.hi, hs.pH, F_DIM, S_LEN, 64, 64);
        make_map(fn, &hs.gi, hs.pG, 512, S_LEN, 64, 128);
        make_map(fn, &hs.oi, hs.pO, 512, S_LEN, 64, 128);
        make_map(fn, &hs.w2, d_in[8], 512, F_DIM, 64, 64);
        make_map(fn, &hs.wo, d_in[4], 512, 512, 64, 64);
        make_map(fn, &hs.xi, d_in[0], 512, S_LEN, 64, 128);
        make_map(fn, &hs.out, d_out, 512, S_LEN, 64, 16);
        cudaFuncSetAttribute(k1_proj, cudaFuncAttributeMaxDynamicSharedMemorySize, K1_SMEM);
        cudaFuncSetAttribute(k2_attn, cudaFuncAttributeMaxDynamicSharedMemorySize, AT_SMEM);
        cudaFuncSetAttribute(k3_out, cudaFuncAttributeMaxDynamicSharedMemorySize, K3_SMEM);
        for (int i = 0; i < 10; i++) hs.key[i] = d_in[i];
        hs.key[10] = d_out;
        hs.ready = true;
    }
    launch(k1_proj, 128, 384, K1_SMEM, false, 2, hs.xi, hs.wq, hs.wk, hs.wv, hs.w1, hs.qo, hs.ho, (const __nv_bfloat16*)d_in[0],
           (const __nv_bfloat16*)d_in[7], (float2*)hs.pRow, (float*)hs.pCol, (__nv_bfloat16*)hs.pKV, (float*)hs.pMax);
    launch(k2_attn, 128, 640, AT_SMEM, true, 1, hs.hi, hs.w2, (const __nv_bfloat16*)hs.pQ, (const __nv_bfloat16*)hs.pKV,
           (const float*)hs.pMax, (const __nv_bfloat16*)d_in[9], (__nv_bfloat16*)hs.pO, (__nv_bfloat16*)hs.pG, (uint2*)hs.pRow, (uint2*)hs.pCol);
    launch(k3_out, 128, 256, K3_SMEM, true, 1, hs.oi, hs.wo, hs.xi, hs.gi, hs.out);
}
```

```cpp
#include <cuda_runtime.h>
#include <cuda_bf16.h>
#include <cuda.h>
#include <stdint.h>

namespace {

constexpr int S_LEN = 2048, D_MODEL = 512, F_DIM = 1792;

__device__ __align__(1024) __nv_bfloat16 g_Q[S_LEN * D_MODEL];
__device__ __align__(1024) __nv_bfloat16 g_KV[6 * S_LEN * 8];
__device__ __align__(1024) __nv_bfloat16 g_G[S_LEN * D_MODEL];
__device__ __align__(1024) __nv_bfloat16 g_H[S_LEN * F_DIM];
__device__ __align__(1024) __nv_bfloat16 g_O[S_LEN * D_MODEL];
__device__ __align__(1024) float g_kvmax[256];
__device__ __align__(1024) float2 g_rowstat[S_LEN];
__device__ __align__(1024) float g_colpart[8 * 16 * 320];

#define DEV_STAMP(k, e) do {} while (0)
__device__ __forceinline__ uint32_t smem_u32(const void* p) { return (uint32_t)__cvta_generic_to_shared(p); }
__device__ __forceinline__ void wg_fence() { asm volatile("wgmma.fence.sync.aligned;" ::: "memory"); }
__device__ __forceinline__ void wg_commit() { asm volatile("wgmma.commit_group.sync.aligned;" ::: "memory"); }
template <int N> __device__ __forceinline__ void wg_wait() { asm volatile("wgmma.wait_group.sync.aligned %0;" ::"n"(N) : "memory"); }
template <int N> __device__ __forceinline__ void fence_regs(float* r) {
#pragma unroll
    for (int i = 0; i < N; i++) asm volatile("" : "+f"(r[i])::"memory");
}
__device__ __forceinline__ void fence_proxy_async() { asm volatile("fence.proxy.async.shared::cta;" ::: "memory"); }
__device__ __forceinline__ void mbar_init(uint32_t bar, int cnt) { asm volatile("mbarrier.init.shared::cta.b64 [%0], %1;" ::"r"(bar), "r"(cnt) : "memory"); }
__device__ __forceinline__ void mbar_init_fence() { asm volatile("fence.mbarrier_init.release.cluster;" ::: "memory"); }
__device__ __forceinline__ void mbar_expect_tx(uint32_t bar, uint32_t bytes) {
    asm volatile("mbarrier.arrive.expect_tx.shared::cta.b64 _, [%0], %1;" ::"r"(bar), "r"(bytes) : "memory");
}
__device__ __forceinline__ void mbar_arrive(uint32_t bar) { asm volatile("mbarrier.arrive.shared::cta.b64 _, [%0];" ::"r"(bar) : "memory"); }
__device__ __forceinline__ bool mbar_try(uint32_t bar, uint32_t parity) {
    uint32_t ok;
    asm volatile("{\n.reg .pred p;\nmbarrier.try_wait.parity.shared::cta.b64 p, [%1], %2;\nselp.u32 %0, 1, 0, p;\n}\n"
                 : "=r"(ok) : "r"(bar), "r"(parity) : "memory");
    return ok != 0;
}
__device__ __forceinline__ void mbar_wait(uint32_t bar, uint32_t parity) {
    if (mbar_try(bar, parity)) return;
    const long long t0 = clock64();
#pragma unroll 1
    while (!mbar_try(bar, parity)) {
        if (clock64() - t0 > 20000000ll) {
            break;
        }
    }
}
__device__ __forceinline__ void bulk_g2s(uint32_t dst, const void* src, uint32_t bytes, uint32_t bar) {
    asm volatile("cp.async.bulk.shared::cluster.global.mbarrier::complete_tx::bytes [%0], [%1], %2, [%3];"
                 ::"r"(dst), "l"(src), "r"(bytes), "r"(bar) : "memory");
}
__device__ __forceinline__ void tma_load_2d(uint32_t dst, const CUtensorMap* tm, int c0, int c1, uint32_t bar) {
    asm volatile("cp.async.bulk.tensor.2d.shared::cluster.global.mbarrier::complete_tx::bytes [%0], [%1, {%3, %4}], [%2];"
                 ::"r"(dst), "l"((uint64_t)tm), "r"(bar), "r"(c0), "r"(c1) : "memory");
}
__device__ __forceinline__ void tma_load_2d_mc(uint32_t dst, const CUtensorMap* tm, int c0, int c1, uint32_t bar, uint16_t mask) {
    asm volatile("cp.async.bulk.tensor.2d.shared::cluster.global.mbarrier::complete_tx::bytes.multicast::cluster [%0], [%1, {%3, %4}], [%2], %5;"
                 ::"r"(dst), "l"((uint64_t)tm), "r"(bar), "r"(c0), "r"(c1), "h"(mask) : "memory");
}
__device__ __forceinline__ void mbar_arrive_remote(uint32_t bar, uint32_t cta) {
    asm volatile("{\n.reg .b32 ra;\nmapa.shared::cluster.u32 ra, %0, %1;\nmbarrier.arrive.shared::cluster.b64 _, [ra];\n}\n"
                 ::"r"(bar), "r"(cta) : "memory");
}
__device__ __forceinline__ uint2 ld_relaxed_v2(const void* p) {
    uint2 v; asm volatile("ld.relaxed.gpu.global.v2.b32 {%0,%1}, [%2];" : "=r"(v.x), "=r"(v.y) : "l"(p) : "memory"); return v;
}
constexpr uint32_t NOT_READY = 0u;
__device__ __forceinline__ float xch_enc(float v) { return __uint_as_float((v == 0.f ? 0u : __float_as_uint(v)) ^ 0x80000000u); }
__device__ __forceinline__ float xch_dec(uint32_t u) { return __uint_as_float(u ^ 0x80000000u); }
__device__ __forceinline__ void tma_store_2d(const CUtensorMap* tm, uint32_t src, int c0, int c1) {
    asm volatile("cp.async.bulk.tensor.2d.global.shared::cta.bulk_group [%0, {%2, %3}], [%1];"
                 ::"l"((uint64_t)tm), "r"(src), "r"(c0), "r"(c1) : "memory");
}
__device__ __forceinline__ void tma_store_commit() { asm volatile("cp.async.bulk.commit_group;" ::: "memory"); }
__device__ __forceinline__ void tma_store_wait() { asm volatile("cp.async.bulk.wait_group 0;" ::: "memory"); }
__device__ __forceinline__ void tma_prefetch_desc(const CUtensorMap* tm) { asm volatile("prefetch.tensormap [%0];" ::"l"((uint64_t)tm) : "memory"); }
__device__ __forceinline__ void named_bar_sync(int id, int n) { asm volatile("bar.sync %0, %1;" ::"r"(id), "r"(n) : "memory"); }
__device__ __forceinline__ void pdl_wait() { asm volatile("griddepcontrol.wait;" ::: "memory"); }
__device__ __forceinline__ void pdl_launch() { asm volatile("griddepcontrol.launch_dependents;" ::: "memory"); }
template <int N> __device__ __forceinline__ void reg_alloc() { asm volatile("setmaxnreg.inc.sync.aligned.u32 %0;" ::"n"(N)); }
template <int N> __device__ __forceinline__ void reg_dealloc() { asm volatile("setmaxnreg.dec.sync.aligned.u32 %0;" ::"n"(N)); }
__device__ __forceinline__ float ex2(float x) { float y; asm("ex2.approx.ftz.f32 %0, %1;" : "=f"(y) : "f"(x)); return y; }
__device__ __forceinline__ uint32_t pack_bf16(float lo, float hi) {
    uint32_t r; asm("cvt.rn.bf16x2.f32 %0, %1, %2;" : "=r"(r) : "f"(hi), "f"(lo)); return r;
}
__device__ __forceinline__ uint32_t pack_bf16_relu(float lo, float hi) {
    uint32_t r; asm("cvt.rn.relu.bf16x2.f32 %0, %1, %2;" : "=r"(r) : "f"(hi), "f"(lo)); return r;
}
__device__ __forceinline__ uint32_t mul_bf16x2(uint32_t a, uint32_t b) {
    uint32_t r; asm("mul.rn.bf16x2 %0, %1, %2;" : "=r"(r) : "r"(a), "r"(b)); return r;
}
__device__ __forceinline__ float bf_lo(uint32_t v) { return __uint_as_float(v << 16); }
__device__ __forceinline__ float bf_hi(uint32_t v) { return __uint_as_float(v & 0xFFFF0000u); }
__device__ __forceinline__ void stmatrix_x4(uint32_t addr, uint32_t r0, uint32_t r1, uint32_t r2, uint32_t r3) {
    asm volatile("stmatrix.sync.aligned.m8n8.x4.shared.b16 [%0], {%1,%2,%3,%4};" ::"r"(addr), "r"(r0), "r"(r1), "r"(r2), "r"(r3) : "memory");
}
__device__ __forceinline__ uint64_t make_desc(uint32_t addr, uint32_t lbo, uint32_t sbo, uint32_t swz) {
    return (uint64_t)((addr & 0x3FFFF) >> 4) | ((uint64_t)(lbo >> 4) << 16) | ((uint64_t)(sbo >> 4) << 32) | ((uint64_t)swz << 62);
}

__device__ __forceinline__ uint64_t desc64(uint32_t lo, uint32_t hi) {
    uint64_t d; asm("mov.b64 %0, {%1, %2};" : "=l"(d) : "r"(lo), "r"(hi)); return d;
}

__device__ __forceinline__ void wgmma_ss_n256_tb(float* d, uint64_t descA, uint64_t descB, int scaleD) {
    asm volatile("{\n.reg .pred p;\nsetp.ne.b32 p, %130, 0;\n"
      "wgmma.mma_async.sync.aligned.m64n256k16.f32.bf16.bf16 {%0,%1,%2,%3,%4,%5,%6,%7,%8,%9,%10,%11,%12,%13,%14,%15,%16,%17,%18,%19,%20,%21,%22,%23,%24,%25,%26,%27,%28,%29,%30,%31,%32,%33,%34,%35,%36,%37,%38,%39,%40,%41,%42,%43,%44,%45,%46,%47,%48,%49,%50,%51,%52,%53,%54,%55,%56,%57,%58,%59,%60,%61,%62,%63,%64,%65,%66,%67,%68,%69,%70,%71,%72,%73,%74,%75,%76,%77,%78,%79,%80,%81,%82,%83,%84,%85,%86,%87,%88,%89,%90,%91,%92,%93,%94,%95,%96,%97,%98,%99,%100,%101,%102,%103,%104,%105,%106,%107,%108,%109,%110,%111,%112,%113,%114,%115,%116,%117,%118,%119,%120,%121,%122,%123,%124,%125,%126,%127}, %128, %129, p, 1, 1, 0, 1;\n}\n"
      : "+f"(d[0]), "+f"(d[1]), "+f"(d[2]), "+f"(d[3]), "+f"(d[4]), "+f"(d[5]), "+f"(d[6]), "+f"(d[7]), "+f"(d[8]), "+f"(d[9]), "+f"(d[10]), "+f"(d[11]), "+f"(d[12]), "+f"(d[13]), "+f"(d[14]), "+f"(d[15]), "+f"(d[16]), "+f"(d[17]), "+f"(d[18]), "+f"(d[19]), "+f"(d[20]), "+f"(d[21]), "+f"(d[22]), "+f"(d[23]), "+f"(d[24]), "+f"(d[25]), "+f"(d[26]), "+f"(d[27]), "+f"(d[28]), "+f"(d[29]), "+f"(d[30]), "+f"(d[31]), "+f"(d[32]), "+f"(d[33]), "+f"(d[34]), "+f"(d[35]), "+f"(d[36]), "+f"(d[37]), "+f"(d[38]), "+f"(d[39]), "+f"(d[40]), "+f"(d[41]), "+f"(d[42]), "+f"(d[43]), "+f"(d[44]), "+f"(d[45]), "+f"(d[46]), "+f"(d[47]), "+f"(d[48]), "+f"(d[49]), "+f"(d[50]), "+f"(d[51]), "+f"(d[52]), "+f"(d[53]), "+f"(d[54]), "+f"(d[55]), "+f"(d[56]), "+f"(d[57]), "+f"(d[58]), "+f"(d[59]), "+f"(d[60]), "+f"(d[61]), "+f"(d[62]), "+f"(d[63]), "+f"(d[64]), "+f"(d[65]), "+f"(d[66]), "+f"(d[67]), "+f"(d[68]), "+f"(d[69]), "+f"(d[70]), "+f"(d[71]), "+f"(d[72]), "+f"(d[73]), "+f"(d[74]), "+f"(d[75]), "+f"(d[76]), "+f"(d[77]), "+f"(d[78]), "+f"(d[79]), "+f"(d[80]), "+f"(d[81]), "+f"(d[82]), "+f"(d[83]), "+f"(d[84]), "+f"(d[85]), "+f"(d[86]), "+f"(d[87]), "+f"(d[88]), "+f"(d[89]), "+f"(d[90]), "+f"(d[91]), "+f"(d[92]), "+f"(d[93]), "+f"(d[94]), "+f"(d[95]), "+f"(d[96]), "+f"(d[97]), "+f"(d[98]), "+f"(d[99]), "+f"(d[100]), "+f"(d[101]), "+f"(d[102]), "+f"(d[103]), "+f"(d[104]), "+f"(d[105]), "+f"(d[106]), "+f"(d[107]), "+f"(d[108]), "+f"(d[109]), "+f"(d[110]), "+f"(d[111]), "+f"(d[112]), "+f"(d[113]), "+f"(d[114]), "+f"(d[115]), "+f"(d[116]), "+f"(d[117]), "+f"(d[118]), "+f"(d[119]), "+f"(d[120]), "+f"(d[121]), "+f"(d[122]), "+f"(d[123]), "+f"(d[124]), "+f"(d[125]), "+f"(d[126]), "+f"(d[127])
      : "l"(descA), "l"(descB), "r"(scaleD));
}
__device__ __forceinline__ void wgmma_ss_n128_tb(float* d, uint64_t descA, uint64_t descB, int scaleD) {
    asm volatile("{\n.reg .pred p;\nsetp.ne.b32 p, %66, 0;\n"
      "wgmma.mma_async.sync.aligned.m64n128k16.f32.bf16.bf16 {%0,%1,%2,%3,%4,%5,%6,%7,%8,%9,%10,%11,%12,%13,%14,%15,%16,%17,%18,%19,%20,%21,%22,%23,%24,%25,%26,%27,%28,%29,%30,%31,%32,%33,%34,%35,%36,%37,%38,%39,%40,%41,%42,%43,%44,%45,%46,%47,%48,%49,%50,%51,%52,%53,%54,%55,%56,%57,%58,%59,%60,%61,%62,%63}, %64, %65, p, 1, 1, 0, 1;\n}\n"
      : "+f"(d[0]), "+f"(d[1]), "+f"(d[2]), "+f"(d[3]), "+f"(d[4]), "+f"(d[5]), "+f"(d[6]), "+f"(d[7]), "+f"(d[8]), "+f"(d[9]), "+f"(d[10]), "+f"(d[11]), "+f"(d[12]), "+f"(d[13]), "+f"(d[14]), "+f"(d[15]), "+f"(d[16]), "+f"(d[17]), "+f"(d[18]), "+f"(d[19]), "+f"(d[20]), "+f"(d[21]), "+f"(d[22]), "+f"(d[23]), "+f"(d[24]), "+f"(d[25]), "+f"(d[26]), "+f"(d[27]), "+f"(d[28]), "+f"(d[29]), "+f"(d[30]), "+f"(d[31]), "+f"(d[32]), "+f"(d[33]), "+f"(d[34]), "+f"(d[35]), "+f"(d[36]), "+f"(d[37]), "+f"(d[38]), "+f"(d[39]), "+f"(d[40]), "+f"(d[41]), "+f"(d[42]), "+f"(d[43]), "+f"(d[44]), "+f"(d[45]), "+f"(d[46]), "+f"(d[47]), "+f"(d[48]), "+f"(d[49]), "+f"(d[50]), "+f"(d[51]), "+f"(d[52]), "+f"(d[53]), "+f"(d[54]), "+f"(d[55]), "+f"(d[56]), "+f"(d[57]), "+f"(d[58]), "+f"(d[59]), "+f"(d[60]), "+f"(d[61]), "+f"(d[62]), "+f"(d[63])
      : "l"(descA), "l"(descB), "r"(scaleD));
}
__device__ __forceinline__ void wgmma_ss_n64_tb(float* d, uint64_t descA, uint64_t descB, int scaleD) {
    asm volatile("{\n.reg .pred p;\nsetp.ne.b32 p, %34, 0;\n"
      "wgmma.mma_async.sync.aligned.m64n64k16.f32.bf16.bf16 {%0,%1,%2,%3,%4,%5,%6,%7,%8,%9,%10,%11,%12,%13,%14,%15,%16,%17,%18,%19,%20,%21,%22,%23,%24,%25,%26,%27,%28,%29,%30,%31}, %32, %33, p, 1, 1, 0, 1;\n}\n"
      : "+f"(d[0]), "+f"(d[1]), "+f"(d[2]), "+f"(d[3]), "+f"(d[4]), "+f"(d[5]), "+f"(d[6]), "+f"(d[7]), "+f"(d[8]), "+f"(d[9]), "+f"(d[10]), "+f"(d[11]), "+f"(d[12]), "+f"(d[13]), "+f"(d[14]), "+f"(d[15]), "+f"(d[16]), "+f"(d[17]), "+f"(d[18]), "+f"(d[19]), "+f"(d[20]), "+f"(d[21]), "+f"(d[22]), "+f"(d[23]), "+f"(d[24]), "+f"(d[25]), "+f"(d[26]), "+f"(d[27]), "+f"(d[28]), "+f"(d[29]), "+f"(d[30]), "+f"(d[31])
      : "l"(descA), "l"(descB), "r"(scaleD));
}
__device__ __forceinline__ void wgmma_qk_acc_n64(float* d, const uint32_t* a, uint64_t descB) {
    asm volatile("wgmma.mma_async.sync.aligned.m64n64k16.f32.bf16.bf16 {%0,%1,%2,%3,%4,%5,%6,%7,%8,%9,%10,%11,%12,%13,%14,%15,%16,%17,%18,%19,%20,%21,%22,%23,%24,%25,%26,%27,%28,%29,%30,%31}, {%32,%33,%34,%35}, %36, 1, 1, 1, 0;\n"
      : "+f"(d[0]), "+f"(d[1]), "+f"(d[2]), "+f"(d[3]), "+f"(d[4]), "+f"(d[5]), "+f"(d[6]), "+f"(d[7]), "+f"(d[8]), "+f"(d[9]), "+f"(d[10]), "+f"(d[11]), "+f"(d[12]), "+f"(d[13]), "+f"(d[14]), "+f"(d[15]), "+f"(d[16]), "+f"(d[17]), "+f"(d[18]), "+f"(d[19]), "+f"(d[20]), "+f"(d[21]), "+f"(d[22]), "+f"(d[23]), "+f"(d[24]), "+f"(d[25]), "+f"(d[26]), "+f"(d[27]), "+f"(d[28]), "+f"(d[29]), "+f"(d[30]), "+f"(d[31])
      : "r"(a[0]), "r"(a[1]), "r"(a[2]), "r"(a[3]), "l"(descB));
}

__device__ __forceinline__ void wgmma_pv(float* d, uint32_t a0, uint32_t a1, uint32_t a2, uint32_t a3, uint64_t descB) {
    asm volatile("wgmma.mma_async.sync.aligned.m64n24k16.f32.bf16.bf16 {%0,%1,%2,%3,%4,%5,%6,%7,%8,%9,%10,%11}, {%12,%13,%14,%15}, %16, 1, 1, 1, 1;\n"
                 : "+f"(d[0]), "+f"(d[1]), "+f"(d[2]), "+f"(d[3]), "+f"(d[4]), "+f"(d[5]), "+f"(d[6]), "+f"(d[7]), "+f"(d[8]), "+f"(d[9]), "+f"(d[10]), "+f"(d[11])
                 : "r"(a0), "r"(a1), "r"(a2), "r"(a3), "l"(descB));
}

__device__ __forceinline__ void k1_panel(int g, int i, int& type, int& col) {
    if (g < 6) {
        int p = g * 5 + i;
        if (p < 8) { type = 0; col = p * 64; } else { type = 1; col = (p - 8) * 64; }
    } else {
        if (i < 3) { type = 1; col = (22 + (g - 6) * 3 + i) * 64; } else { type = 2 + (g - 6); col = 0; }
    }
}

constexpr int K1_STAGES = 4;
constexpr int K1_PANEL_BYTES = 64 * 128;
constexpr int K1_STAGE_BYTES = 16384 + 5 * K1_PANEL_BYTES;
constexpr int K1_SMEM = K1_STAGES * K1_STAGE_BYTES + 128 + 320 * 8;
constexpr float Q_SCALE = 0.25f * 1.4426950408889634f;

__global__ void __launch_bounds__(384, 1)
k1_proj(const __grid_constant__ CUtensorMap tm_x, const __grid_constant__ CUtensorMap tm_wq,
        const __grid_constant__ CUtensorMap tm_wk, const __grid_constant__ CUtensorMap tm_wv,
        const __grid_constant__ CUtensorMap tm_w1, const __grid_constant__ CUtensorMap tm_qo,
        const __grid_constant__ CUtensorMap tm_ho, const __nv_bfloat16* __restrict__ x, const __nv_bfloat16* __restrict__ b1,
        float2* rowstat, float* colpart,
        __nv_bfloat16* __restrict__ kv, float* __restrict__ kvmax) {
    extern __shared__ __align__(1024) uint8_t smem_raw[];
    const uint32_t sbase = smem_u32(smem_raw);
    const uint32_t bar_full = sbase + K1_STAGES * K1_STAGE_BYTES, bar_empty = bar_full + 8 * K1_STAGES, bar_col = bar_empty + 8 * K1_STAGES;
    const uint32_t sCol = bar_full + 128;
    const int tid = threadIdx.x, warp = __shfl_sync(0xffffffffu, tid >> 5, 0), lane = tid & 31;
    const int crank = blockIdx.x & 1, grp = (blockIdx.x >> 1) & 7, rb = (blockIdx.x >> 4) * 2 + crank;
    const int npanels = grp < 6 ? 5 : 4;
    if (tid == 0) DEV_STAMP(0, 0);

    if (tid == 288) {
        tma_prefetch_desc(&tm_x); tma_prefetch_desc(&tm_w1); tma_prefetch_desc(grp < 2 ? &tm_wq : grp == 6 ? &tm_wk : &tm_wv);
        tma_prefetch_desc(&tm_ho); tma_prefetch_desc(&tm_qo);
    }
    uint4 v[2][2];
    if (warp < 8) {
        const uint4* xp = reinterpret_cast<const uint4*>(x + (size_t)(rb * 128 + grp * 16 + warp * 2) * D_MODEL);
#pragma unroll
        for (int r = 0; r < 2; r++) { v[r][0] = __ldg(xp + r * 64 + lane); v[r][1] = __ldg(xp + r * 64 + 32 + lane); }
    }
    const int krot = rb & 8 ? 4 : 0, cstage = (rb >> 1) & 3;
    if (tid == 256) {
        for (int s = 0; s < K1_STAGES; s++) { mbar_init(bar_full + 8 * s, 1); mbar_init(bar_empty + 8 * s, s == cstage ? 18 : 16); }
        mbar_init(bar_col, 96);
        mbar_init_fence();
    }
    asm volatile("barrier.cluster.arrive.relaxed;" ::: "memory");
    if (warp != 8) asm volatile("barrier.cluster.wait;" ::: "memory");
    pdl_launch();

    if (warp >= 8) {
        reg_dealloc<88>();
        if (warp == 8) {
            const CUtensorMap* tms[5]; int cols[5];
#pragma unroll
            for (int i = 0; i < 5; i++) {
                int type, col; k1_panel(grp, i, type, col);
                tms[i] = type == 0 ? &tm_wq : type == 1 ? &tm_w1 : type == 2 ? &tm_wk : &tm_wv;
                cols[i] = col;
            }
            if (lane == 0) {
                mbar_expect_tx(bar_full, 16384 + npanels * K1_PANEL_BYTES);
                tma_load_2d(sbase, &tm_x, krot * 64, rb * 128, bar_full);
#pragma unroll
                for (int i = 0; i < 5; i++)
                    if (i < npanels) tma_load_2d(sbase + 16384 + i * K1_PANEL_BYTES, tms[i], cols[i], krot * 64, bar_full);
            }
            __syncwarp();
            asm volatile("barrier.cluster.wait;" ::: "memory");
            if (lane == 0) {
                for (int ks = 1; ks < 8; ks++) {
                    const int s = ks % K1_STAGES;
                    const uint32_t st = sbase + s * K1_STAGE_BYTES;
                    mbar_wait(bar_empty + 8 * s, ((ks / K1_STAGES) & 1) ^ 1);
                    const int k0 = ((ks + krot) & 7) * 64;
                    mbar_expect_tx(bar_full + 8 * s, 16384 + npanels * K1_PANEL_BYTES);
                    tma_load_2d(st, &tm_x, k0, rb * 128, bar_full + 8 * s);
#pragma unroll
                    for (int i = 0; i < 5; i++)
                        if (i < npanels && ((i + ks + crank) & 1) == 0)
                            tma_load_2d_mc(st + 16384 + i * K1_PANEL_BYTES, tms[i], cols[i], k0, bar_full + 8 * s, (uint16_t)3);
                }
            }
        } else {
            const int ht = tid - 288;
            mbar_wait(bar_full + 8 * cstage, 0);
            {
                const int pc = ht >> 1, half = ht & 1;
                float sacc[8];
#pragma unroll
                for (int c = 0; c < 8; c++) sacc[c] = 0.f;
                if (pc < npanels * 8) {
                    const uint32_t pb = sbase + cstage * K1_STAGE_BYTES + 16384 + (pc >> 3) * K1_PANEL_BYTES;
#pragma unroll
                    for (int i = 0; i < 16; i++) {
                        const int k = crank * 32 + 2 * i + half;
                        uint4 u;
                        asm volatile("ld.shared.v4.b32 {%0,%1,%2,%3}, [%4];" : "=r"(u.x), "=r"(u.y), "=r"(u.z), "=r"(u.w)
                                     : "r"(pb + k * 128 + (((pc & 7) ^ (k & 7)) << 4)));
                        sacc[0] += bf_lo(u.x); sacc[1] += bf_hi(u.x); sacc[2] += bf_lo(u.y); sacc[3] += bf_hi(u.y);
                        sacc[4] += bf_lo(u.z); sacc[5] += bf_hi(u.z); sacc[6] += bf_lo(u.w); sacc[7] += bf_hi(u.w);
                    }
                }
#pragma unroll
                for (int c = 0; c < 8; c++) sacc[c] += __shfl_xor_sync(0xffffffffu, sacc[c], 1);
                if (pc < npanels * 8) {
                    float4* dst = reinterpret_cast<float4*>(colpart + (grp * 16 + rb) * 320 + pc * 8) + half;
                    *dst = half ? make_float4(xch_enc(sacc[4]), xch_enc(sacc[5]), xch_enc(sacc[6]), xch_enc(sacc[7]))
                                : make_float4(xch_enc(sacc[0]), xch_enc(sacc[1]), xch_enc(sacc[2]), xch_enc(sacc[3]));
                }
                named_bar_sync(4, 96);
                if (ht < 2) mbar_arrive_remote(bar_empty + 8 * cstage, ht);
            }
            if (ht == 0) DEV_STAMP(0, 6);
            for (int c2 = ht; c2 < npanels * 32; c2 += 96) {
                int type, col; k1_panel(grp, c2 >> 5, type, col);
                uint32_t bb = 0;
                if (type == 1) bb = __ldg(reinterpret_cast<const uint32_t*>(b1 + col) + (c2 & 31));
                uint2 pv[16];
                bool okv = false;
#pragma unroll 1
                for (uint32_t n = 0; n < (1u << 14) && !okv; n++) {
                    okv = true;
#pragma unroll
                    for (int k = 0; k < 16; k++) pv[k] = ld_relaxed_v2(colpart + (grp * 16 + k) * 320 + c2 * 2);
#pragma unroll
                    for (int k = 0; k < 16; k++) okv = okv && pv[k].x != NOT_READY && pv[k].y != NOT_READY;
                }
                float s0 = 0.f, s1 = 0.f;
#pragma unroll
                for (int k = 0; k < 16; k++) { s0 += xch_dec(pv[k].x); s1 += xch_dec(pv[k].y); }
                asm volatile("st.shared.v4.f32 [%0], {%1,%2,%3,%4};" ::"r"(sCol + c2 * 16), "f"(s0), "f"(bf_lo(bb)), "f"(s1), "f"(bf_hi(bb)) : "memory");
            }
            mbar_arrive(bar_col);
            if (ht == 0) DEV_STAMP(0, 7);
        }
    } else {
        reg_alloc<208>();
        const int wg = warp >> 2;
        const int g = lane >> 2, t = lane & 3;
        const int wrow = (warp & 3) * 16;
        {
            float f[2][16], sum[2], sq[2];
#pragma unroll
            for (int r = 0; r < 2; r++) {
                const uint32_t w[8] = {v[r][0].x, v[r][0].y, v[r][0].z, v[r][0].w, v[r][1].x, v[r][1].y, v[r][1].z, v[r][1].w};
#pragma unroll
                for (int i = 0; i < 8; i++) { f[r][2 * i] = bf_lo(w[i]); f[r][2 * i + 1] = bf_hi(w[i]); }
                sum[r] = 0.f;
#pragma unroll
                for (int i = 0; i < 16; i++) sum[r] += f[r][i];
            }
#pragma unroll
            for (int o = 16; o > 0; o >>= 1) { sum[0] += __shfl_xor_sync(0xffffffffu, sum[0], o); sum[1] += __shfl_xor_sync(0xffffffffu, sum[1], o); }
#pragma unroll
            for (int r = 0; r < 2; r++) {
                sum[r] *= (1.0f / D_MODEL);
                sq[r] = 0.f;
#pragma unroll
                for (int i = 0; i < 16; i++) { const float d = f[r][i] - sum[r]; sq[r] += d * d; }
            }
#pragma unroll
            for (int o = 16; o > 0; o >>= 1) { sq[0] += __shfl_xor_sync(0xffffffffu, sq[0], o); sq[1] += __shfl_xor_sync(0xffffffffu, sq[1], o); }
            if (lane < 2) {
                const float rstd = rsqrtf((lane ? sq[1] : sq[0]) * (1.0f / D_MODEL) + 1e-5f);
                rowstat[rb * 128 + grp * 16 + warp * 2 + lane] = make_float2(xch_enc(rstd), xch_enc((lane ? sum[1] : sum[0]) * rstd));
            }
            if (tid == 0) DEV_STAMP(0, 5);
        }
        float acc[160];
#pragma unroll
        for (int i = 0; i < 160; i++) acc[i] = 0.f;
        float2 rs0, rs1;
        const uint64_t dA0 = make_desc(sbase + wg * 8192, 16, 1024, 1);
        const uint64_t dB0 = make_desc(sbase + 16384, K1_PANEL_BYTES, 1024, 1);
#define K1_MAINLOOP(FIVE)                                                                                          \
        for (int ks = 0; ks < 8; ks++) {                                                                           \
            const int s = ks % K1_STAGES;                                                                          \
            mbar_wait(bar_full + 8 * s, (ks / K1_STAGES) & 1);                                                     \
            if (ks == 0 && tid == 0) DEV_STAMP(0, 1);                                                              \
            wg_fence();                                                                                            \
            _Pragma("unroll") for (int kk = 0; kk < 4; kk++) {                                                     \
                const uint64_t dA = dA0 + (uint64_t)((s * K1_STAGE_BYTES + kk * 32) >> 4);                         \
                const uint64_t dB = dB0 + (uint64_t)((s * K1_STAGE_BYTES + kk * 2048) >> 4);                       \
                wgmma_ss_n256_tb(acc, dA, dB, (ks | kk) != 0);                                                     \
                if (FIVE) wgmma_ss_n64_tb(acc + 128, dA, dB + (uint64_t)((4 * K1_PANEL_BYTES) >> 4), (ks | kk) != 0); \
            }                                                                                                      \
            wg_commit();                                                                                           \
            if (ks == 7) {                                                                                         \
                uint2 r0, r1;                                                                                      \
                uint32_t n = 0;                                                                                    \
                _Pragma("unroll 1") do {                                                                           \
                    r0 = ld_relaxed_v2(rowstat + rb * 128 + wg * 64 + wrow + g);                                   \
                    r1 = ld_relaxed_v2(rowstat + rb * 128 + wg * 64 + wrow + g + 8);                               \
                } while ((r0.x == NOT_READY || r0.y == NOT_READY || r1.x == NOT_READY || r1.y == NOT_READY) && ++n < (1u << 14)); \
                rs0 = make_float2(xch_dec(r0.x), xch_dec(r0.y));                                                   \
                rs1 = make_float2(xch_dec(r1.x), xch_dec(r1.y));                                                   \
                mbar_wait(bar_col, 0);                                                                             \
            }                                                                                                      \
            if (ks > 0 && ks <= 4) {                                                                               \
                wg_wait<1>();                                                                                      \
                if (lane < 2) mbar_arrive_remote(bar_empty + 8 * ((ks - 1) % K1_STAGES), lane);                    \
            }                                                                                                      \
        }                                                                                                          \
        wg_wait<0>();
        const int srow = (lane & 7) + ((lane >> 3) & 1) * 8;
        if (npanels == 5) { K1_MAINLOOP(true) } else { K1_MAINLOOP(false) }
        fence_regs<160>(acc);
        if (tid == 0) DEV_STAMP(0, 2);
        named_bar_sync(1, 256);
#pragma unroll
        for (int p = 0; p < 5; p++) {
            if (p < npanels) {
                int type, col; k1_panel(grp, p, type, col);
                float* a = acc + p * 32;
                const int nj = type <= 1 ? 8 : 2;
                const float sc = type == 0 ? Q_SCALE : 1.0f;
                const float r0x = rs0.x * sc, r0y = -rs0.y * sc, r1x = rs1.x * sc, r1y = -rs1.y * sc;
#pragma unroll
                for (int j = 0; j < 8; j++) {
                    if (j < nj) {
                        float4 c;
                        asm volatile("ld.shared.v4.f32 {%0,%1,%2,%3}, [%4];" : "=f"(c.x), "=f"(c.y), "=f"(c.z), "=f"(c.w)
                                     : "r"(sCol + (p * 64 + j * 8 + 2 * t) * 8));
                        a[4 * j] = fmaf(a[4 * j], r0x, fmaf(r0y, c.x, c.y));
                        a[4 * j + 1] = fmaf(a[4 * j + 1], r0x, fmaf(r0y, c.z, c.w));
                        a[4 * j + 2] = fmaf(a[4 * j + 2], r1x, fmaf(r1y, c.x, c.y));
                        a[4 * j + 3] = fmaf(a[4 * j + 3], r1x, fmaf(r1y, c.z, c.w));
                    }
                }
                if (type <= 1) {
                    const uint32_t stg = sbase + (p * 8 + warp) * 2048;
                    uint32_t pk[16];
                    if (type == 0) {
#pragma unroll
                        for (int j = 0; j < 8; j++) {
                            pk[2 * j] = pack_bf16(a[4 * j], a[4 * j + 1]);
                            pk[2 * j + 1] = pack_bf16(a[4 * j + 2], a[4 * j + 3]);
                        }
                    } else {
#pragma unroll
                        for (int j = 0; j < 8; j++) {
                            const uint32_t h0 = pack_bf16_relu(a[4 * j], a[4 * j + 1]), h1 = pack_bf16_relu(a[4 * j + 2], a[4 * j + 3]);
                            pk[2 * j] = mul_bf16x2(h0, h0);
                            pk[2 * j + 1] = mul_bf16x2(h1, h1);
                        }
                    }
#pragma unroll
                    for (int j = 0; j < 8; j += 2) {
                        const int c16 = j + (lane >> 4);
                        stmatrix_x4(stg + srow * 128 + ((c16 ^ (srow & 7)) << 4), pk[2 * j], pk[2 * j + 1], pk[2 * j + 2], pk[2 * j + 3]);
                    }
                    fence_proxy_async();
                    __syncwarp();
                    if (lane == 0) {
                        tma_store_2d(type == 0 ? &tm_qo : &tm_ho, stg, col, rb * 128 + warp * 16);
                        tma_store_commit();
                    }
                } else if (type == 3) {
                    const int r = wg * 64 + wrow + g;
                    const int pos0 = (r >> 2) * 64 + rb * 4 + (r & 3), pos1 = pos0 + 128;
                    uint32_t* dst = reinterpret_cast<uint32_t*>(kv);
                    const uint32_t r00 = pack_bf16(a[0], a[1]), r01 = pack_bf16(a[4], a[5]);
                    const uint32_t r10 = pack_bf16(a[2], a[3]), r11 = pack_bf16(a[6], a[7]);
                    dst[(pos0 >> 4) * 128 + (pos0 & 15) * 4 + t] = r00;
                    dst[16384 + pos0 * 4 + t] = r01;
                    dst[(pos1 >> 4) * 128 + (pos1 & 15) * 4 + t] = r10;
                    dst[16384 + pos1 * 4 + t] = r11;
                    float m = fmaxf(fmaxf(fmaxf(fabsf(bf_lo(r00)), fabsf(bf_hi(r00))), fmaxf(fabsf(bf_lo(r01)), fabsf(bf_hi(r01)))),
                                    fmaxf(fmaxf(fabsf(bf_lo(r10)), fabsf(bf_hi(r10))), fmaxf(fabsf(bf_lo(r11)), fabsf(bf_hi(r11)))));
#pragma unroll
                    for (int o = 16; o > 0; o >>= 1) m = fmaxf(m, __shfl_xor_sync(0xffffffffu, m, o));
                    if (lane == 0) kvmax[128 + rb * 8 + warp] = m;
                } else {
                    float* kf = reinterpret_cast<float*>(smem_raw + 96 * 1024);
                    const int r = wg * 64 + wrow + g;
                    const int pos0 = (r >> 2) * 64 + rb * 4 + (r & 3), pos1 = pos0 + 128;
                    uint32_t* dst = reinterpret_cast<uint32_t*>(kv) + 32768;
                    dst[(pos0 >> 3) * 64 + (pos0 & 7) * 4 + t] = pack_bf16(a[0], a[1]);
                    dst[(pos0 >> 3) * 64 + 32 + (pos0 & 7) * 4 + t] = pack_bf16(a[4], a[5]);
                    dst[(pos1 >> 3) * 64 + (pos1 & 7) * 4 + t] = pack_bf16(a[2], a[3]);
                    dst[(pos1 >> 3) * 64 + 32 + (pos1 & 7) * 4 + t] = pack_bf16(a[6], a[7]);
                    kf[r * 17 + 2 * t] = a[0]; kf[r * 17 + 2 * t + 1] = a[1];
                    kf[r * 17 + 8 + 2 * t] = a[4]; kf[r * 17 + 8 + 2 * t + 1] = a[5];
                    kf[(r + 8) * 17 + 2 * t] = a[2]; kf[(r + 8) * 17 + 2 * t + 1] = a[3];
                    kf[(r + 8) * 17 + 8 + 2 * t] = a[6]; kf[(r + 8) * 17 + 8 + 2 * t + 1] = a[7];
                    named_bar_sync(1, 256);
                    if (tid < 64) {
                        const int i = tid >> 4, dim = tid & 15;
                        const int c = rb * 4 + i;
                        const int inner = (dim >> 3) * 64 + (c & 7) * 8 + (dim & 7);
                        float kt = 0.f;
#pragma unroll 8
                        for (int j = 0; j < 32; j++) {
                            const __nv_bfloat16 d = __float2bfloat16_rn(kf[(j * 4 + i) * 17 + dim] - kt);
                            kt += __bfloat162float(d);
                            kf[(j * 4 + i) * 17 + dim] = kt;
                            const int gi = (j >> 1) * 8 + (c >> 3);
                            kv[((j & 1) ? 49152 + gi * 128 : gi * 256 + 128) + inner] = d;
                        }
                    }
                    named_bar_sync(1, 256);
                    if (tid < 128) {
                        float n = 0.f;
#pragma unroll
                        for (int d = 0; d < 16; d++) { const float v = kf[tid * 17 + d]; n += v * v; }
                        if (!(n == n)) n = __int_as_float(0x7f800000);
#pragma unroll
                        for (int o = 8; o > 0; o >>= 1) n = fmaxf(n, __shfl_xor_sync(0xffffffffu, n, o));
                        if ((lane & 15) == 0) kvmax[rb * 8 + (tid >> 4)] = n;
                    }
                }
            }
        }
        if (tid == 0) DEV_STAMP(0, 3);
        if (lane == 0) tma_store_wait();
        if (tid == 0) DEV_STAMP(0, 4);
    }
}

constexpr int AT_KT = 64;
constexpr int AT_NCHUNK = 8;
constexpr int AT_NSTEP = S_LEN / AT_KT;
constexpr int AT_SPC = AT_NSTEP / AT_NCHUNK;
constexpr int AT_ONES = 131072;
constexpr int F2_STAGES = 4;
constexpr int F2_STAGE_BYTES = 8192 + 16384;
constexpr int F2_BASE = 132096;
constexpr int F2_NK = F_DIM / 64;
constexpr int AT_BAR = F2_BASE + F2_STAGES * F2_STAGE_BYTES;
constexpr int AT_SMEM = AT_BAR + 256;
#define AT_SWMASK_V 0xB6DB
constexpr uint32_t AT_SWMASK = AT_SWMASK_V;

#define AT_MAGIC 382.41765f
__device__ __forceinline__ uint32_t exp2_pair_alu(float t0, float t1) {
    uint32_t y;
    asm("prmt.b32 %0, %1, %2, 0x6521;" : "=r"(y) : "f"(t0), "f"(t1));
    const uint32_t e = y & 0x7F807F80u;
    uint32_t uh, p;
    asm("lop3.b32 %0, %1, %2, 0x3F003F00, 0xBE;" : "=r"(uh) : "r"(y), "r"(e));
    asm("fma.rn.bf16x2 %0, %1, %2, %3;" : "=r"(p) : "r"(uh), "r"(y), "r"(e));
    return p;
}

__device__ __forceinline__ void at_load_chunk(uint32_t sbase, const __nv_bfloat16* KV, uint32_t bar0, int c) {
    const uint8_t* src = reinterpret_cast<const uint8_t*>(KV);
    mbar_expect_tx(bar0 + 8 * c, 16384);
    bulk_g2s(sbase + c * 8192, src + c * 8192, 8192, bar0 + 8 * c);
    bulk_g2s(sbase + 98304 + c * 4096, src + 98304 + c * 4096, 4096, bar0 + 8 * c);
    bulk_g2s(sbase + 65536 + c * 4096, src + 65536 + c * 4096, 4096, bar0 + 8 * c);
}

__device__ __forceinline__ void at_store(const float* o, __nv_bfloat16* O, int row, int lane) {
    const float l0 = __shfl_sync(0xffffffffu, o[8], lane & ~3);
    const float l1 = __shfl_sync(0xffffffffu, o[10], lane & ~3);
    const float r0 = __fdividef(1.0f, l0), r1 = __fdividef(1.0f, l1);
    const int t = lane & 3;
    uint32_t* op = reinterpret_cast<uint32_t*>(O + (size_t)(row + (lane >> 2)) * 16);
    op[t] = pack_bf16(o[0] * r0, o[1] * r0);
    op[t + 4] = pack_bf16(o[4] * r0, o[5] * r0);
    op[64 + t] = pack_bf16(o[2] * r1, o[3] * r1);
    op[64 + t + 4] = pack_bf16(o[6] * r1, o[7] * r1);
}

__device__ __forceinline__ void mma16816(float* c, const uint32_t* a, uint32_t b0, uint32_t b1) {
    asm volatile("mma.sync.aligned.m16n8k16.row.col.f32.bf16.bf16.f32 {%0,%1,%2,%3}, {%4,%5,%6,%7}, {%8,%9}, {%0,%1,%2,%3};"
                 : "+f"(c[0]), "+f"(c[1]), "+f"(c[2]), "+f"(c[3]) : "r"(a[0]), "r"(a[1]), "r"(a[2]), "r"(a[3]), "r"(b0), "r"(b1));
}
__device__ __forceinline__ void attn_fallback(const __nv_bfloat16* Q, const __nv_bfloat16* KV, __nv_bfloat16* O, uint32_t sbase) {
    const int tid = threadIdx.x;
    const int lane = tid & 31, g = lane >> 2, t = lane & 3;
    const uint32_t* Kg = reinterpret_cast<const uint32_t*>(KV + 65536);
#pragma unroll 1
    for (int mt = 0; mt < 2; mt++) {
        const int row = blockIdx.x * 512 + (tid >> 7) * 128 + mt * 64 + ((tid >> 5) & 3) * 16;
        const uint32_t* qp = reinterpret_cast<const uint32_t*>(Q + (size_t)(row + g) * 16);
        const uint32_t q[4] = {qp[t], qp[64 + t], qp[t + 4], qp[64 + t + 4]};
        float o[12];
#pragma unroll
        for (int i = 0; i < 12; i++) o[i] = 0.f;
        float m0 = -INFINITY, m1 = -INFINITY;
#pragma unroll 1
        for (int kt = 0; kt < S_LEN / 16; kt++) {
            float s[8];
#pragma unroll
            for (int i = 0; i < 8; i++) s[i] = 0.f;
#pragma unroll
            for (int h = 0; h < 2; h++) {
                const uint32_t* kp = Kg + (kt * 2 + h) * 64 + g * 4 + t;
                mma16816(s + 4 * h, q, kp[0], kp[32]);
            }
            float x0 = fmaxf(fmaxf(s[0], s[1]), fmaxf(s[4], s[5])), x1 = fmaxf(fmaxf(s[2], s[3]), fmaxf(s[6], s[7]));
            x0 = fmaxf(x0, __shfl_xor_sync(0xffffffffu, x0, 1)); x0 = fmaxf(x0, __shfl_xor_sync(0xffffffffu, x0, 2));
            x1 = fmaxf(x1, __shfl_xor_sync(0xffffffffu, x1, 1)); x1 = fmaxf(x1, __shfl_xor_sync(0xffffffffu, x1, 2));
            x0 = fmaxf(x0, m0); x1 = fmaxf(x1, m1);
            const float f0 = ex2(m0 - x0), f1 = ex2(m1 - x1);
            m0 = x0; m1 = x1;
#pragma unroll
            for (int j = 0; j < 3; j++) { o[4 * j] *= f0; o[4 * j + 1] *= f0; o[4 * j + 2] *= f1; o[4 * j + 3] *= f1; }
            const uint32_t p[4] = {pack_bf16(ex2(s[0] - m0), ex2(s[1] - m0)), pack_bf16(ex2(s[2] - m1), ex2(s[3] - m1)),
                                   pack_bf16(ex2(s[4] - m0), ex2(s[5] - m0)), pack_bf16(ex2(s[6] - m1), ex2(s[7] - m1))};
#pragma unroll
            for (int j = 0; j < 3; j++) {
                const uint32_t base = sbase + (j == 0 ? kt * 512 : j == 1 ? 65536 + kt * 256 : AT_ONES) + (lane & 15) * 16;
                uint32_t b0, b1;
                asm volatile("ldmatrix.sync.aligned.m8n8.x2.trans.shared.b16 {%0,%1}, [%2];" : "=r"(b0), "=r"(b1) : "r"(base));
                mma16816(o + 4 * j, p, b0, b1);
            }
        }
        at_store(o, O, row, lane);
    }
}

__global__ void __launch_bounds__(640, 1)
k2_attn(const __grid_constant__ CUtensorMap tm_h, const __grid_constant__ CUtensorMap tm_w2,
        const __nv_bfloat16* __restrict__ Q, const __nv_bfloat16* __restrict__ KV, const float* __restrict__ kvmax,
        const __nv_bfloat16* __restrict__ b2, __nv_bfloat16* __restrict__ O, __nv_bfloat16* __restrict__ G,
        uint2* __restrict__ rowstat, uint2* __restrict__ colpart) {
    extern __shared__ __align__(1024) uint8_t smem_raw[];
    const uint32_t sbase = smem_u32(smem_raw);
    const uint32_t bar0 = sbase + AT_BAR, f2_full = bar0 + 64, f2_empty = f2_full + 32, bar_guard = f2_empty + 32, bar_first = bar_guard + 8, sGuard = bar0 + 192;
    const int tid = threadIdx.x;
    const int wg = __shfl_sync(0xffffffffu, tid >> 7, 0);
    const int warp = (tid >> 5) & 3, lane = tid & 31;
    const int g = lane >> 2, t = lane & 3;
    if (tid == 0) DEV_STAMP(1, 0);
    if (tid == 0) {
        for (int i = 0; i < AT_NCHUNK; i++) mbar_init(bar0 + 8 * i, 1);
        for (int i = 0; i < F2_STAGES; i++) { mbar_init(f2_full + 8 * i, 1); mbar_init(f2_empty + 8 * i, 4); }
        mbar_init(bar_guard, 4);
        mbar_init(bar_first, 1);
        mbar_init_fence();
    }
    if (tid < 16) asm volatile("st.shared.v4.b32 [%0], {%1,%2,%2,%2};" ::"r"(sbase + AT_ONES + tid * 16), "r"(0x00003F80u), "r"(0u) : "memory");
    fence_proxy_async();
    __syncthreads();

    if (wg == 4) {
        const int rb = blockIdx.x >> 2, cb = blockIdx.x & 3;
        const uint32_t fb = sbase + F2_BASE;
        const bool leader = tid == 512;
        if (leader) {
#pragma unroll
            for (int s = 0; s < F2_STAGES; s++) {
                mbar_expect_tx(f2_full + 8 * s, F2_STAGE_BYTES);
                tma_load_2d(fb + s * F2_STAGE_BYTES + 8192, &tm_w2, cb * 128, s * 64, f2_full + 8 * s);
                tma_load_2d(fb + s * F2_STAGE_BYTES + 16384, &tm_w2, cb * 128 + 64, s * 64, f2_full + 8 * s);
            }
        }
        pdl_wait();
        mbar_wait(bar0, 0);
        if (leader) {
#pragma unroll
            for (int s = 0; s < F2_STAGES; s++) tma_load_2d(fb + s * F2_STAGE_BYTES, &tm_h, s * 64, rb * 64, f2_full + 8 * s);
        }
        {
            float km = fmaxf(fmaxf(kvmax[lane], kvmax[lane + 32]), fmaxf(kvmax[lane + 64], kvmax[lane + 96]));
            float vm = fmaxf(fmaxf(kvmax[128 + lane], kvmax[160 + lane]), fmaxf(kvmax[192 + lane], kvmax[224 + lane]));
            uint4 qv[4][2];
#pragma unroll
            for (int i = 0; i < 4; i++) {
                const uint4* qr = reinterpret_cast<const uint4*>(Q + (size_t)(blockIdx.x * 512 + warp * 128 + i * 16 + (lane >> 4) * 64 + (lane & 15)) * 16);
                qv[i][0] = qr[0]; qv[i][1] = qr[1];
            }
#pragma unroll
            for (int o = 16; o > 0; o >>= 1) { km = fmaxf(km, __shfl_xor_sync(0xffffffffu, km, o)); vm = fmaxf(vm, __shfl_xor_sync(0xffffffffu, vm, o)); }
#pragma unroll
            for (int i = 0; i < 4; i++) {
                const uint32_t qw[8] = {qv[i][0].x, qv[i][0].y, qv[i][0].z, qv[i][0].w, qv[i][1].x, qv[i][1].y, qv[i][1].z, qv[i][1].w};
                float qn = 0.f;
#pragma unroll
                for (int j = 0; j < 8; j++) qn += bf_lo(qw[j]) * bf_lo(qw[j]) + bf_hi(qw[j]) * bf_hi(qw[j]);
                const bool ok = (qn * km <= 3600.0f) && (vm <= 1.0e12f);
                const uint32_t bad = __any_sync(0xffffffffu, !ok);
                if (lane == 0) asm volatile("st.shared.u32 [%0], %1;" ::"r"(sGuard + (warp * 4 + i) * 4), "r"(bad) : "memory");
            }
            if (lane == 0) mbar_arrive(bar_guard);
        }
        __syncwarp();
        const uint64_t dA0 = make_desc(fb, 16, 1024, 1);
        const uint64_t dB0 = make_desc(fb + 8192, 8192, 1024, 1);
        float acc[64];
#pragma unroll
        for (int i = 0; i < 64; i++) asm volatile("mov.f32 %0, 0f00000000;" : "=f"(acc[i]));
#pragma unroll 1
        for (int ks = 0; ks < F2_NK; ks++) {
            const int s = ks % F2_STAGES;
            mbar_wait(f2_full + 8 * s, (ks / F2_STAGES) & 1);
            wg_fence();
#pragma unroll
            for (int kk = 0; kk < 4; kk++)
                wgmma_ss_n128_tb(acc, dA0 + (uint64_t)((s * F2_STAGE_BYTES + kk * 32) >> 4),
                                 dB0 + (uint64_t)((s * F2_STAGE_BYTES + kk * 2048) >> 4), 1);
            wg_commit();
            wg_wait<1>();
            if (ks > 0 && ks - 1 + F2_STAGES < F2_NK) {
                const int ps = (ks - 1) % F2_STAGES, k0 = (ks - 1 + F2_STAGES) * 64;
                if (lane == 0) mbar_arrive(f2_empty + 8 * ps);
                if (leader) {
                    mbar_wait(f2_empty + 8 * ps, ((ks - 1) / F2_STAGES) & 1);
                    mbar_expect_tx(f2_full + 8 * ps, F2_STAGE_BYTES);
                    tma_load_2d(fb + ps * F2_STAGE_BYTES, &tm_h, k0, rb * 64, f2_full + 8 * ps);
                    tma_load_2d(fb + ps * F2_STAGE_BYTES + 8192, &tm_w2, cb * 128, k0, f2_full + 8 * ps);
                    tma_load_2d(fb + ps * F2_STAGE_BYTES + 16384, &tm_w2, cb * 128 + 64, k0, f2_full + 8 * ps);
                }
                __syncwarp();
            }
        }
        wg_wait<0>();
        fence_regs<64>(acc);
        uint32_t* gp = reinterpret_cast<uint32_t*>(G + (size_t)(rb * 64 + warp * 16 + g) * D_MODEL + cb * 128) + t;
#pragma unroll
        for (int j = 0; j < 16; j++) {
            const uint32_t bb = __ldg(reinterpret_cast<const uint32_t*>(b2 + cb * 128 + j * 8) + t);
            const float b0 = bf_lo(bb), b1v = bf_hi(bb);
            const float z0 = acc[4 * j] + b0, z1 = acc[4 * j + 1] + b1v, z2 = acc[4 * j + 2] + b0, z3 = acc[4 * j + 3] + b1v;
            gp[j * 4] = pack_bf16(__fdividef(z0, 1.0f + __expf(-z0)), __fdividef(z1, 1.0f + __expf(-z1)));
            gp[j * 4 + 8 * (D_MODEL / 2)] = pack_bf16(__fdividef(z2, 1.0f + __expf(-z2)), __fdividef(z3, 1.0f + __expf(-z3)));
        }
        if (leader) DEV_STAMP(1, 5);
        return;
    }

    pdl_wait();
    pdl_launch();
    if (tid == 0) DEV_STAMP(1, 1);
    if (tid == 0) {
        const uint8_t* src = reinterpret_cast<const uint8_t*>(KV);
        mbar_expect_tx(bar_first, 4096);
        bulk_g2s(sbase, src, 4096, bar_first);
        mbar_expect_tx(bar0, 12288);
        bulk_g2s(sbase + 98304, src + 98304, 4096, bar0);
        bulk_g2s(sbase + 65536, src + 65536, 4096, bar0);
        bulk_g2s(sbase + 4096, src + 4096, 4096, bar0);
        at_load_chunk(sbase, KV, bar0, 1); at_load_chunk(sbase, KV, bar0, 2);
    }
    if (tid >= 128 && tid < 288) colpart[blockIdx.x * 160 + tid - 128] = make_uint2(NOT_READY, NOT_READY);
    if (tid >= 288 && tid < 304) rowstat[blockIdx.x * 16 + tid - 288] = make_uint2(NOT_READY, NOT_READY);
    const int rowA = blockIdx.x * 512 + wg * 128 + warp * 16;
    const uint32_t* qp = reinterpret_cast<const uint32_t*>(Q + (size_t)(rowA + g) * 16);
    const uint32_t lo0 = ((sbase & 0x3FFFF) >> 4) | (8u << 16);

#define AT_EXP(P) _Pragma("unroll") for (int i = 0; i < AT_KT / 4; i++) {                       \
                if ((AT_SWMASK >> (i & 15)) & 1) P[i] = exp2_pair_alu(s[2 * i], s[2 * i + 1]);  \
                else P[i] = pack_bf16(ex2(s[2 * i]), ex2(s[2 * i + 1])); }
    uint64_t vstep = 32ull - (16ull << 32);
    asm volatile("" : "+l"(vstep));
#define AT_PV1(P, j) { wgmma_pv(o, P[4 * (j)], P[4 * (j) + 1], P[4 * (j) + 2], P[4 * (j) + 3], dV); dV += vstep; }
#define AT_EXPH(P, h) _Pragma("unroll") for (int i = (h) * 8; i < (h) * 8 + 8; i++) {           \
                if ((AT_SWMASK >> (i & 15)) & 1) P[i] = exp2_pair_alu(s[2 * i], s[2 * i + 1]);  \
                else P[i] = pack_bf16(ex2(s[2 * i]), ex2(s[2 * i + 1])); }
#define AT_STEP(st, DK, INC) {                                                                  \
                wg_wait<0>();                                                                   \
                fence_regs<AT_KT / 2>(s);                                                       \
                AT_EXPH(p0, 0);                                                                 \
                wg_fence();                                                                     \
                AT_PV1(p0, 0); AT_PV1(p0, 1);                                                   \
                wg_commit();                                                                    \
                AT_EXPH(p0, 1);                                                                 \
                if (st == AT_SPC - 1 && mt == 0) mbar_wait(bar0 + 8 * (c + 1), 0);              \
                wg_wait<0>();                                                                   \
                wg_fence();                                                                     \
                wgmma_qk_acc_n64(s, q, DK); DK += INC;                                          \
                AT_PV1(p0, 2); AT_PV1(p0, 3);                                                   \
                wg_commit(); }

#pragma unroll 1
    for (int mt = 0; mt < 2; mt++) {
        uint32_t q[4];
        q[0] = qp[mt * 512 + t]; q[2] = qp[mt * 512 + t + 4]; q[1] = qp[mt * 512 + 64 + t]; q[3] = qp[mt * 512 + 64 + t + 4];
        float o[12];
#pragma unroll
        for (int i = 0; i < 12; i++) asm volatile("mov.f32 %0, 0f00000000;" : "=f"(o[i]));
        float s[AT_KT / 2];
        uint32_t p0[AT_KT / 4];
#pragma unroll
        for (int i = 0; i < AT_KT / 2; i++) {
            if ((AT_SWMASK >> ((i >> 1) & 15)) & 1) asm volatile("mov.f32 %0, %1;" : "=f"(s[i]) : "f"(AT_MAGIC));
            else asm volatile("mov.f32 %0, 0f00000000;" : "=f"(s[i]));
        }
        if (mt == 0) mbar_wait(bar_first, 0);
        if (tid == 0) DEV_STAMP(1, 2 + mt);
        uint64_t dV = desc64(lo0, 4096), dX = desc64(lo0 + 16, 32), dY = desc64(lo0 + (98304 >> 4), 16);
        wg_fence();
        wgmma_qk_acc_n64(s, q, dX); dX += 256;
        wg_commit();
        if (mt == 0) mbar_wait(bar0, 0);
#pragma unroll 1
        for (int c = 0; c < AT_NCHUNK - 1; c++) {
            if (tid == 0 && mt == 0 && c + 3 < AT_NCHUNK) at_load_chunk(sbase, KV, bar0, c + 3);
            AT_STEP(0, dY, 128); AT_STEP(1, dX, 256); AT_STEP(2, dY, 128); AT_STEP(3, dX, 256);
        }
        {
            const int c = 0; (void)c;
            AT_STEP(0, dY, 128); AT_STEP(1, dX, 256); AT_STEP(2, dY, 128);
            wg_wait<0>();
            fence_regs<AT_KT / 2>(s);
            AT_EXP(p0);
            wg_fence();
            AT_PV1(p0, 0); AT_PV1(p0, 1); AT_PV1(p0, 2); AT_PV1(p0, 3);
            wg_commit();
            wg_wait<0>();
            fence_regs<12>(o);
        }
        at_store(o, O, rowA + mt * 64, lane);
    }
    if (tid == 0) DEV_STAMP(1, 4);

    mbar_wait(bar_guard, 0);
    uint32_t bad;
    asm volatile("ld.shared.u32 %0, [%1];" : "=r"(bad) : "r"(sGuard + (tid >> 5) * 4) : "memory");
    if (__any_sync(0xffffffffu, bad != 0) == 0) return;
    attn_fallback(Q, KV, O, sbase);
}

constexpr int K3_STAGE_BYTES = 16384 + 8192;
constexpr int K3_X = 8 * K3_STAGE_BYTES;
constexpr int K3_G = K3_X + 16384;
constexpr int K3_SMEM = K3_G + 16384 + 256;

__global__ void __launch_bounds__(256, 1)
k3_out(const __grid_constant__ CUtensorMap tm_o, const __grid_constant__ CUtensorMap tm_wo,
       const __grid_constant__ CUtensorMap tm_x, const __grid_constant__ CUtensorMap tm_g,
       const __grid_constant__ CUtensorMap tm_out) {
    extern __shared__ __align__(1024) uint8_t smem_raw[];
    const uint32_t sbase = smem_u32(smem_raw);
    const uint32_t sX = sbase + K3_X, sG = sbase + K3_G;
    const uint32_t bar_full = sG + 16384, bar_x = bar_full + 64;
    const int tid = threadIdx.x, warp = __shfl_sync(0xffffffffu, tid >> 5, 0), lane = tid & 31;
    const int rb = blockIdx.x >> 3, cb = blockIdx.x & 7;
    if (tid == 0) {
        DEV_STAMP(2, 0);
        for (int s = 0; s < 8; s++) mbar_init(bar_full + 8 * s, 1);
        mbar_init(bar_x, 1);
        mbar_init_fence();
        for (int s = 0; s < 8; s++) {
            mbar_expect_tx(bar_full + 8 * s, K3_STAGE_BYTES);
            tma_load_2d(sbase + s * K3_STAGE_BYTES + 16384, &tm_wo, cb * 64, s * 64, bar_full + 8 * s);
        }
        mbar_expect_tx(bar_x, 32768);
        tma_load_2d(sX, &tm_x, cb * 64, rb * 128, bar_x);
        pdl_wait();
        DEV_STAMP(2, 1);
        for (int s = 0; s < 8; s++) tma_load_2d(sbase + s * K3_STAGE_BYTES, &tm_o, s * 64, rb * 128, bar_full + 8 * s);
        tma_load_2d(sG, &tm_g, cb * 64, rb * 128, bar_x);
    }
    __syncthreads();
    const int wg = warp >> 2;
    float acc[32];
#pragma unroll
    for (int i = 0; i < 32; i++) asm volatile("mov.f32 %0, 0f00000000;" : "=f"(acc[i]));
    const uint64_t dA0 = make_desc(sbase + wg * 8192, 16, 1024, 1);
    const uint64_t dB0 = make_desc(sbase + 16384, 8192, 1024, 1);
#pragma unroll 1
    for (int ks = 0; ks < 8; ks++) {
        mbar_wait(bar_full + 8 * ks, 0);
        wg_fence();
#pragma unroll
        for (int kk = 0; kk < 4; kk++)
            wgmma_ss_n64_tb(acc, dA0 + (uint64_t)((ks * K3_STAGE_BYTES + kk * 32) >> 4),
                            dB0 + (uint64_t)((ks * K3_STAGE_BYTES + kk * 2048) >> 4), 1);
        wg_commit();
    }
    wg_wait<0>();
    fence_regs<32>(acc);
    if (tid == 0) DEV_STAMP(2, 2);
    mbar_wait(bar_x, 0);
    const int g = lane >> 2, t = lane & 3;
    const int row0 = warp * 16 + g;
#pragma unroll
    for (int j = 0; j < 8; j++) {
#pragma unroll
        for (int h = 0; h < 2; h++) {
            const int row = row0 + h * 8;
            const uint32_t off = row * 128 + ((j ^ (row & 7)) << 4) + t * 4;
            uint32_t xv, gv;
            asm volatile("ld.shared.b32 %0, [%1];" : "=r"(xv) : "r"(sX + off) : "memory");
            asm volatile("ld.shared.b32 %0, [%1];" : "=r"(gv) : "r"(sG + off) : "memory");
            const uint32_t ov = pack_bf16(fmaf(acc[4 * j + 2 * h], bf_lo(gv), bf_lo(xv)), fmaf(acc[4 * j + 2 * h + 1], bf_hi(gv), bf_hi(xv)));
            asm volatile("st.shared.b32 [%0], %1;" ::"r"(sX + off), "r"(ov) : "memory");
        }
    }
    fence_proxy_async();
    __syncwarp();
    if (lane == 0) {
        tma_store_2d(&tm_out, sX + warp * 2048, cb * 64, rb * 128 + warp * 16);
        tma_store_commit();
        if (tid == 0) DEV_STAMP(2, 3);
        tma_store_wait();
        if (tid == 0) DEV_STAMP(2, 4);
    }
}

typedef CUresult (*EncodeFn)(CUtensorMap*, CUtensorMapDataType, cuuint32_t, void*, const cuuint64_t*, const cuuint64_t*,
                             const cuuint32_t*, const cuuint32_t*, CUtensorMapInterleave, CUtensorMapSwizzle,
                             CUtensorMapL2promotion, CUtensorMapFloatOOBfill);

struct HostState {
    bool ready;
    const void* key[11];
    CUtensorMap wq, wk, wv, w1, qo, ho, hi, oi, w2, wo, xi, gi, out;
    void *pQ, *pKV, *pH, *pO, *pMax, *pRow, *pCol, *pFlag, *pG;
};
HostState g_hs;

void make_map(EncodeFn fn, CUtensorMap* m, const void* ptr, uint64_t inner, uint64_t outer, uint32_t box_in, uint32_t box_out) {
    cuuint64_t dims[2] = {inner, outer};
    cuuint64_t strides[1] = {inner * 2};
    cuuint32_t box[2] = {box_in, box_out};
    cuuint32_t es[2] = {1, 1};
    fn(m, CU_TENSOR_MAP_DATA_TYPE_BFLOAT16, 2, const_cast<void*>(ptr), dims, strides, box, es, CU_TENSOR_MAP_INTERLEAVE_NONE,
       CU_TENSOR_MAP_SWIZZLE_128B, CU_TENSOR_MAP_L2_PROMOTION_L2_256B, CU_TENSOR_MAP_FLOAT_OOB_FILL_NONE);
}

template <typename... KArgs, typename... Args>
void launch(void (*kern)(KArgs...), int grid, int block, int smem, bool pdl, int cluster, Args... args) {
    cudaLaunchConfig_t cfg = {};
    cfg.gridDim = dim3(grid); cfg.blockDim = dim3(block); cfg.dynamicSmemBytes = smem; cfg.stream = cudaStreamPerThread;
    cudaLaunchAttribute at[2];
    int n = 0;
    if (pdl) { at[n].id = cudaLaunchAttributeProgrammaticStreamSerialization; at[n].val.programmaticStreamSerializationAllowed = 1; n++; }
    if (cluster > 1) { at[n].id = cudaLaunchAttributeClusterDimension; at[n].val.clusterDim.x = cluster; at[n].val.clusterDim.y = 1; at[n].val.clusterDim.z = 1; n++; }
    cfg.attrs = at; cfg.numAttrs = n;
    cudaLaunchKernelEx(&cfg, kern, KArgs(args)...);
}

}

extern "C" void kernel_launch(void* const* d_in, const int* in_sizes, int n_in, void* d_out, int out_size) {
    (void)in_sizes; (void)n_in; (void)out_size;
    HostState& hs = g_hs;
    bool same = hs.ready;
    for (int i = 0; i < 10 && same; i++) same = hs.key[i] == d_in[i];
    same = same && hs.key[10] == d_out;
    if (!same) {
        void* fp = nullptr;
        cudaDriverEntryPointQueryResult qr;
        cudaGetDriverEntryPoint("cuTensorMapEncodeTiled", &fp, cudaEnableDefault, &qr);
        EncodeFn fn = (EncodeFn)fp;
        cudaGetSymbolAddress(&hs.pQ, g_Q); cudaGetSymbolAddress(&hs.pKV, g_KV); cudaGetSymbolAddress(&hs.pH, g_H);
        cudaGetSymbolAddress(&hs.pO, g_O); cudaGetSymbolAddress(&hs.pMax, g_kvmax);
        cudaGetSymbolAddress(&hs.pRow, g_rowstat); cudaGetSymbolAddress(&hs.pCol, g_colpart); cudaGetSymbolAddress(&hs.pG, g_G);
        make_map(fn, &hs.wq, d_in[1], 512, 512, 64, 64);
        make_map(fn, &hs.wk, d_in[2], 16, 512, 64, 64);
        make_map(fn, &hs.wv, d_in[3], 16, 512, 64, 64);
        make_map(fn, &hs.w1, d_in[6], F_DIM, 512, 64, 64);
        make_map(fn, &hs.qo, hs.pQ, 512, S_LEN, 64, 16);
        make_map(fn, &hs.ho, hs.pH, F_DIM, S_LEN, 64, 16);
        make_map(fn, &hs.hi, hs.pH, F_DIM, S_LEN, 64, 64);
        make_map(fn, &hs.gi, hs.pG, 512, S_LEN, 64, 128);
        make_map(fn, &hs.oi, hs.pO, 512, S_LEN, 64, 128);
        make_map(fn, &hs.w2, d_in[8], 512, F_DIM, 64, 64);
        make_map(fn, &hs.wo, d_in[4], 512, 512, 64, 64);
        make_map(fn, &hs.xi, d_in[0], 512, S_LEN, 64, 128);
        make_map(fn, &hs.out, d_out, 512, S_LEN, 64, 16);
        cudaFuncSetAttribute(k1_proj, cudaFuncAttributeMaxDynamicSharedMemorySize, K1_SMEM);
        cudaFuncSetAttribute(k2_attn, cudaFuncAttributeMaxDynamicSharedMemorySize, AT_SMEM);
        cudaFuncSetAttribute(k3_out, cudaFuncAttributeMaxDynamicSharedMemorySize, K3_SMEM);
        for (int i = 0; i < 10; i++) hs.key[i] = d_in[i];
        hs.key[10] = d_out;
        hs.ready = true;
    }
    launch(k1_proj, 128, 384, K1_SMEM, false, 2, hs.xi, hs.wq, hs.wk, hs.wv, hs.w1, hs.qo, hs.ho, (const __nv_bfloat16*)d_in[0],
           (const __nv_bfloat16*)d_in[7], (float2*)hs.pRow, (float*)hs.pCol, (__nv_bfloat16*)hs.pKV, (float*)hs.pMax);
    launch(k2_attn, 128, 640, AT_SMEM, true, 1, hs.hi, hs.w2, (const __nv_bfloat16*)hs.pQ, (const __nv_bfloat16*)hs.pKV,
           (const float*)hs.pMax, (const __nv_bfloat16*)d_in[9], (__nv_bfloat16*)hs.pO, (__nv_bfloat16*)hs.pG, (uint2*)hs.pRow, (uint2*)hs.pCol);
    launch(k3_out, 128, 256, K3_SMEM, true, 1, hs.oi, hs.wo, hs.xi, hs.gi, hs.out);
}
```

```cpp
#include <cuda_runtime.h>
#include <cuda_bf16.h>
#include <cuda.h>
#include <stdint.h>

namespace {

constexpr int S_LEN = 2048, D_MODEL = 512, F_DIM = 1792;

__device__ __align__(1024) __nv_bfloat16 g_Q[S_LEN * D_MODEL];
__device__ __align__(1024) __nv_bfloat16 g_KV[6 * S_LEN * 8];
__device__ __align__(1024) __nv_bfloat16 g_G[S_LEN * D_MODEL];
__device__ __align__(1024) __nv_bfloat16 g_H[S_LEN * F_DIM];
__device__ __align__(1024) __nv_bfloat16 g_O[S_LEN * D_MODEL];
__device__ __align__(1024) float g_kvmax[256];
__device__ __align__(1024) float2 g_rowstat[S_LEN];
__device__ __align__(1024) float g_colpart[8 * 16 * 320];

#define DEV_STAMP(k, e) do {} while (0)
__device__ __forceinline__ uint32_t smem_u32(const void* p) { return (uint32_t)__cvta_generic_to_shared(p); }
__device__ __forceinline__ void wg_fence() { asm volatile("wgmma.fence.sync.aligned;" ::: "memory"); }
__device__ __forceinline__ void wg_commit() { asm volatile("wgmma.commit_group.sync.aligned;" ::: "memory"); }
template <int N> __device__ __forceinline__ void wg_wait() { asm volatile("wgmma.wait_group.sync.aligned %0;" ::"n"(N) : "memory"); }
template <int N> __device__ __forceinline__ void fence_regs(float* r) {
#pragma unroll
    for (int i = 0; i < N; i++) asm volatile("" : "+f"(r[i])::"memory");
}
__device__ __forceinline__ void fence_proxy_async() { asm volatile("fence.proxy.async.shared::cta;" ::: "memory"); }
__device__ __forceinline__ void mbar_init(uint32_t bar, int cnt) { asm volatile("mbarrier.init.shared::cta.b64 [%0], %1;" ::"r"(bar), "r"(cnt) : "memory"); }
__device__ __forceinline__ void mbar_init_fence() { asm volatile("fence.mbarrier_init.release.cluster;" ::: "memory"); }
__device__ __forceinline__ void mbar_expect_tx(uint32_t bar, uint32_t bytes) {
    asm volatile("mbarrier.arrive.expect_tx.shared::cta.b64 _, [%0], %1;" ::"r"(bar), "r"(bytes) : "memory");
}
__device__ __forceinline__ void mbar_arrive(uint32_t bar) { asm volatile("mbarrier.arrive.shared::cta.b64 _, [%0];" ::"r"(bar) : "memory"); }
__device__ __forceinline__ bool mbar_try(uint32_t bar, uint32_t parity) {
    uint32_t ok;
    asm volatile("{\n.reg .pred p;\nmbarrier.try_wait.parity.shared::cta.b64 p, [%1], %2;\nselp.u32 %0, 1, 0, p;\n}\n"
                 : "=r"(ok) : "r"(bar), "r"(parity) : "memory");
    return ok != 0;
}
__device__ __forceinline__ void mbar_wait(uint32_t bar, uint32_t parity) {
    if (mbar_try(bar, parity)) return;
    const long long t0 = clock64();
#pragma unroll 1
    while (!mbar_try(bar, parity)) {
        if (clock64() - t0 > 20000000ll) {
            break;
        }
    }
}
__device__ __forceinline__ void bulk_g2s(uint32_t dst, const void* src, uint32_t bytes, uint32_t bar) {
    asm volatile("cp.async.bulk.shared::cluster.global.mbarrier::complete_tx::bytes [%0], [%1], %2, [%3];"
                 ::"r"(dst), "l"(src), "r"(bytes), "r"(bar) : "memory");
}
__device__ __forceinline__ void tma_load_2d(uint32_t dst, const CUtensorMap* tm, int c0, int c1, uint32_t bar) {
    asm volatile("cp.async.bulk.tensor.2d.shared::cluster.global.mbarrier::complete_tx::bytes [%0], [%1, {%3, %4}], [%2];"
                 ::"r"(dst), "l"((uint64_t)tm), "r"(bar), "r"(c0), "r"(c1) : "memory");
}
__device__ __forceinline__ uint2 ld_relaxed_v2(const void* p) {
    uint2 v; asm volatile("ld.relaxed.gpu.global.v2.b32 {%0,%1}, [%2];" : "=r"(v.x), "=r"(v.y) : "l"(p) : "memory"); return v;
}
constexpr uint32_t NOT_READY = 0u;
__device__ __forceinline__ float xch_enc(float v) { return __uint_as_float((v == 0.f ? 0u : __float_as_uint(v)) ^ 0x80000000u); }
__device__ __forceinline__ float xch_dec(uint32_t u) { return __uint_as_float(u ^ 0x80000000u); }
__device__ __forceinline__ void tma_store_2d(const CUtensorMap* tm, uint32_t src, int c0, int c1) {
    asm volatile("cp.async.bulk.tensor.2d.global.shared::cta.bulk_group [%0, {%2, %3}], [%1];"
                 ::"l"((uint64_t)tm), "r"(src), "r"(c0), "r"(c1) : "memory");
}
__device__ __forceinline__ void tma_store_commit() { asm volatile("cp.async.bulk.commit_group;" ::: "memory"); }
__device__ __forceinline__ void tma_store_wait() { asm volatile("cp.async.bulk.wait_group 0;" ::: "memory"); }
__device__ __forceinline__ void tma_prefetch_desc(const CUtensorMap* tm) { asm volatile("prefetch.tensormap [%0];" ::"l"((uint64_t)tm) : "memory"); }
__device__ __forceinline__ void named_bar_sync(int id, int n) { asm volatile("bar.sync %0, %1;" ::"r"(id), "r"(n) : "memory"); }
__device__ __forceinline__ void pdl_wait() { asm volatile("griddepcontrol.wait;" ::: "memory"); }
__device__ __forceinline__ void pdl_launch() { asm volatile("griddepcontrol.launch_dependents;" ::: "memory"); }
template <int N> __device__ __forceinline__ void reg_alloc() { asm volatile("setmaxnreg.inc.sync.aligned.u32 %0;" ::"n"(N)); }
template <int N> __device__ __forceinline__ void reg_dealloc() { asm volatile("setmaxnreg.dec.sync.aligned.u32 %0;" ::"n"(N)); }
__device__ __forceinline__ float ex2(float x) { float y; asm("ex2.approx.ftz.f32 %0, %1;" : "=f"(y) : "f"(x)); return y; }
__device__ __forceinline__ uint32_t pack_bf16(float lo, float hi) {
    uint32_t r; asm("cvt.rn.bf16x2.f32 %0, %1, %2;" : "=r"(r) : "f"(hi), "f"(lo)); return r;
}
__device__ __forceinline__ uint32_t pack_bf16_relu(float lo, float hi) {
    uint32_t r; asm("cvt.rn.relu.bf16x2.f32 %0, %1, %2;" : "=r"(r) : "f"(hi), "f"(lo)); return r;
}
__device__ __forceinline__ uint32_t mul_bf16x2(uint32_t a, uint32_t b) {
    uint32_t r; asm("mul.rn.bf16x2 %0, %1, %2;" : "=r"(r) : "r"(a), "r"(b)); return r;
}
__device__ __forceinline__ float bf_lo(uint32_t v) { return __uint_as_float(v << 16); }
__device__ __forceinline__ float bf_hi(uint32_t v) { return __uint_as_float(v & 0xFFFF0000u); }
__device__ __forceinline__ void stmatrix_x4(uint32_t addr, uint32_t r0, uint32_t r1, uint32_t r2, uint32_t r3) {
    asm volatile("stmatrix.sync.aligned.m8n8.x4.shared.b16 [%0], {%1,%2,%3,%4};" ::"r"(addr), "r"(r0), "r"(r1), "r"(r2), "r"(r3) : "memory");
}
__device__ __forceinline__ uint64_t make_desc(uint32_t addr, uint32_t lbo, uint32_t sbo, uint32_t swz) {
    return (uint64_t)((addr & 0x3FFFF) >> 4) | ((uint64_t)(lbo >> 4) << 16) | ((uint64_t)(sbo >> 4) << 32) | ((uint64_t)swz << 62);
}

__device__ __forceinline__ uint64_t desc64(uint32_t lo, uint32_t hi) {
    uint64_t d; asm("mov.b64 %0, {%1, %2};" : "=l"(d) : "r"(lo), "r"(hi)); return d;
}

__device__ __forceinline__ void wgmma_ss_n256_tb(float* d, uint64_t descA, uint64_t descB, int scaleD) {
    asm volatile("{\n.reg .pred p;\nsetp.ne.b32 p, %130, 0;\n"
      "wgmma.mma_async.sync.aligned.m64n256k16.f32.bf16.bf16 {%0,%1,%2,%3,%4,%5,%6,%7,%8,%9,%10,%11,%12,%13,%14,%15,%16,%17,%18,%19,%20,%21,%22,%23,%24,%25,%26,%27,%28,%29,%30,%31,%32,%33,%34,%35,%36,%37,%38,%39,%40,%41,%42,%43,%44,%45,%46,%47,%48,%49,%50,%51,%52,%53,%54,%55,%56,%57,%58,%59,%60,%61,%62,%63,%64,%65,%66,%67,%68,%69,%70,%71,%72,%73,%74,%75,%76,%77,%78,%79,%80,%81,%82,%83,%84,%85,%86,%87,%88,%89,%90,%91,%92,%93,%94,%95,%96,%97,%98,%99,%100,%101,%102,%103,%104,%105,%106,%107,%108,%109,%110,%111,%112,%113,%114,%115,%116,%117,%118,%119,%120,%121,%122,%123,%124,%125,%126,%127}, %128, %129, p, 1, 1, 0, 1;\n}\n"
      : "+f"(d[0]), "+f"(d[1]), "+f"(d[2]), "+f"(d[3]), "+f"(d[4]), "+f"(d[5]), "+f"(d[6]), "+f"(d[7]), "+f"(d[8]), "+f"(d[9]), "+f"(d[10]), "+f"(d[11]), "+f"(d[12]), "+f"(d[13]), "+f"(d[14]), "+f"(d[15]), "+f"(d[16]), "+f"(d[17]), "+f"(d[18]), "+f"(d[19]), "+f"(d[20]), "+f"(d[21]), "+f"(d[22]), "+f"(d[23]), "+f"(d[24]), "+f"(d[25]), "+f"(d[26]), "+f"(d[27]), "+f"(d[28]), "+f"(d[29]), "+f"(d[30]), "+f"(d[31]), "+f"(d[32]), "+f"(d[33]), "+f"(d[34]), "+f"(d[35]), "+f"(d[36]), "+f"(d[37]), "+f"(d[38]), "+f"(d[39]), "+f"(d[40]), "+f"(d[41]), "+f"(d[42]), "+f"(d[43]), "+f"(d[44]), "+f"(d[45]), "+f"(d[46]), "+f"(d[47]), "+f"(d[48]), "+f"(d[49]), "+f"(d[50]), "+f"(d[51]), "+f"(d[52]), "+f"(d[53]), "+f"(d[54]), "+f"(d[55]), "+f"(d[56]), "+f"(d[57]), "+f"(d[58]), "+f"(d[59]), "+f"(d[60]), "+f"(d[61]), "+f"(d[62]), "+f"(d[63]), "+f"(d[64]), "+f"(d[65]), "+f"(d[66]), "+f"(d[67]), "+f"(d[68]), "+f"(d[69]), "+f"(d[70]), "+f"(d[71]), "+f"(d[72]), "+f"(d[73]), "+f"(d[74]), "+f"(d[75]), "+f"(d[76]), "+f"(d[77]), "+f"(d[78]), "+f"(d[79]), "+f"(d[80]), "+f"(d[81]), "+f"(d[82]), "+f"(d[83]), "+f"(d[84]), "+f"(d[85]), "+f"(d[86]), "+f"(d[87]), "+f"(d[88]), "+f"(d[89]), "+f"(d[90]), "+f"(d[91]), "+f"(d[92]), "+f"(d[93]), "+f"(d[94]), "+f"(d[95]), "+f"(d[96]), "+f"(d[97]), "+f"(d[98]), "+f"(d[99]), "+f"(d[100]), "+f"(d[101]), "+f"(d[102]), "+f"(d[103]), "+f"(d[104]), "+f"(d[105]), "+f"(d[106]), "+f"(d[107]), "+f"(d[108]), "+f"(d[109]), "+f"(d[110]), "+f"(d[111]), "+f"(d[112]), "+f"(d[113]), "+f"(d[114]), "+f"(d[115]), "+f"(d[116]), "+f"(d[117]), "+f"(d[118]), "+f"(d[119]), "+f"(d[120]), "+f"(d[121]), "+f"(d[122]), "+f"(d[123]), "+f"(d[124]), "+f"(d[125]), "+f"(d[126]), "+f"(d[127])
      : "l"(descA), "l"(descB), "r"(scaleD));
}
__device__ __forceinline__ void wgmma_ss_n128_tb(float* d, uint64_t descA, uint64_t descB, int scaleD) {
    asm volatile("{\n.reg .pred p;\nsetp.ne.b32 p, %66, 0;\n"
      "wgmma.mma_async.sync.aligned.m64n128k16.f32.bf16.bf16 {%0,%1,%2,%3,%4,%5,%6,%7,%8,%9,%10,%11,%12,%13,%14,%15,%16,%17,%18,%19,%20,%21,%22,%23,%24,%25,%26,%27,%28,%29,%30,%31,%32,%33,%34,%35,%36,%37,%38,%39,%40,%41,%42,%43,%44,%45,%46,%47,%48,%49,%50,%51,%52,%53,%54,%55,%56,%57,%58,%59,%60,%61,%62,%63}, %64, %65, p, 1, 1, 0, 1;\n}\n"
      : "+f"(d[0]), "+f"(d[1]), "+f"(d[2]), "+f"(d[3]), "+f"(d[4]), "+f"(d[5]), "+f"(d[6]), "+f"(d[7]), "+f"(d[8]), "+f"(d[9]), "+f"(d[10]), "+f"(d[11]), "+f"(d[12]), "+f"(d[13]), "+f"(d[14]), "+f"(d[15]), "+f"(d[16]), "+f"(d[17]), "+f"(d[18]), "+f"(d[19]), "+f"(d[20]), "+f"(d[21]), "+f"(d[22]), "+f"(d[23]), "+f"(d[24]), "+f"(d[25]), "+f"(d[26]), "+f"(d[27]), "+f"(d[28]), "+f"(d[29]), "+f"(d[30]), "+f"(d[31]), "+f"(d[32]), "+f"(d[33]), "+f"(d[34]), "+f"(d[35]), "+f"(d[36]), "+f"(d[37]), "+f"(d[38]), "+f"(d[39]), "+f"(d[40]), "+f"(d[41]), "+f"(d[42]), "+f"(d[43]), "+f"(d[44]), "+f"(d[45]), "+f"(d[46]), "+f"(d[47]), "+f"(d[48]), "+f"(d[49]), "+f"(d[50]), "+f"(d[51]), "+f"(d[52]), "+f"(d[53]), "+f"(d[54]), "+f"(d[55]), "+f"(d[56]), "+f"(d[57]), "+f"(d[58]), "+f"(d[59]), "+f"(d[60]), "+f"(d[61]), "+f"(d[62]), "+f"(d[63])
      : "l"(descA), "l"(descB), "r"(scaleD));
}
__device__ __forceinline__ void wgmma_ss_n64_tb(float* d, uint64_t descA, uint64_t descB, int scaleD) {
    asm volatile("{\n.reg .pred p;\nsetp.ne.b32 p, %34, 0;\n"
      "wgmma.mma_async.sync.aligned.m64n64k16.f32.bf16.bf16 {%0,%1,%2,%3,%4,%5,%6,%7,%8,%9,%10,%11,%12,%13,%14,%15,%16,%17,%18,%19,%20,%21,%22,%23,%24,%25,%26,%27,%28,%29,%30,%31}, %32, %33, p, 1, 1, 0, 1;\n}\n"
      : "+f"(d[0]), "+f"(d[1]), "+f"(d[2]), "+f"(d[3]), "+f"(d[4]), "+f"(d[5]), "+f"(d[6]), "+f"(d[7]), "+f"(d[8]), "+f"(d[9]), "+f"(d[10]), "+f"(d[11]), "+f"(d[12]), "+f"(d[13]), "+f"(d[14]), "+f"(d[15]), "+f"(d[16]), "+f"(d[17]), "+f"(d[18]), "+f"(d[19]), "+f"(d[20]), "+f"(d[21]), "+f"(d[22]), "+f"(d[23]), "+f"(d[24]), "+f"(d[25]), "+f"(d[26]), "+f"(d[27]), "+f"(d[28]), "+f"(d[29]), "+f"(d[30]), "+f"(d[31])
      : "l"(descA), "l"(descB), "r"(scaleD));
}
__device__ __forceinline__ void wgmma_qk_acc_n64(float* d, const uint32_t* a, uint64_t descB) {
    asm volatile("wgmma.mma_async.sync.aligned.m64n64k16.f32.bf16.bf16 {%0,%1,%2,%3,%4,%5,%6,%7,%8,%9,%10,%11,%12,%13,%14,%15,%16,%17,%18,%19,%20,%21,%22,%23,%24,%25,%26,%27,%28,%29,%30,%31}, {%32,%33,%34,%35}, %36, 1, 1, 1, 0;\n"
      : "+f"(d[0]), "+f"(d[1]), "+f"(d[2]), "+f"(d[3]), "+f"(d[4]), "+f"(d[5]), "+f"(d[6]), "+f"(d[7]), "+f"(d[8]), "+f"(d[9]), "+f"(d[10]), "+f"(d[11]), "+f"(d[12]), "+f"(d[13]), "+f"(d[14]), "+f"(d[15]), "+f"(d[16]), "+f"(d[17]), "+f"(d[18]), "+f"(d[19]), "+f"(d[20]), "+f"(d[21]), "+f"(d[22]), "+f"(d[23]), "+f"(d[24]), "+f"(d[25]), "+f"(d[26]), "+f"(d[27]), "+f"(d[28]), "+f"(d[29]), "+f"(d[30]), "+f"(d[31])
      : "r"(a[0]), "r"(a[1]), "r"(a[2]), "r"(a[3]), "l"(descB));
}

__device__ __forceinline__ void wgmma_pv(float* d, uint32_t a0, uint32_t a1, uint32_t a2, uint32_t a3, uint64_t descB) {
    asm volatile("wgmma.mma_async.sync.aligned.m64n24k16.f32.bf16.bf16 {%0,%1,%2,%3,%4,%5,%6,%7,%8,%9,%10,%11}, {%12,%13,%14,%15}, %16, 1, 1, 1, 1;\n"
                 : "+f"(d[0]), "+f"(d[1]), "+f"(d[2]), "+f"(d[3]), "+f"(d[4]), "+f"(d[5]), "+f"(d[6]), "+f"(d[7]), "+f"(d[8]), "+f"(d[9]), "+f"(d[10]), "+f"(d[11])
                 : "r"(a0), "r"(a1), "r"(a2), "r"(a3), "l"(descB));
}

__device__ __forceinline__ void k1_panel(int g, int i, int& type, int& col) {
    if (g < 6) {
        int p = g * 5 + i;
        if (p < 8) { type = 0; col = p * 64; } else { type = 1; col = (p - 8) * 64; }
    } else {
        if (i < 3) { type = 1; col = (22 + (g - 6) * 3 + i) * 64; } else { type = 2 + (g - 6); col = 0; }
    }
}

constexpr int K1_STAGES = 4;
constexpr int K1_PANEL_BYTES = 64 * 128;
constexpr int K1_STAGE_BYTES = 16384 + 5 * K1_PANEL_BYTES;
constexpr int K1_SMEM = K1_STAGES * K1_STAGE_BYTES + 128 + 320 * 8;
constexpr float Q_SCALE = 0.25f * 1.4426950408889634f;

__global__ void __launch_bounds__(384, 1)
k1_proj(const __grid_constant__ CUtensorMap tm_x, const __grid_constant__ CUtensorMap tm_wq,
        const __grid_constant__ CUtensorMap tm_wk, const __grid_constant__ CUtensorMap tm_wv,
        const __grid_constant__ CUtensorMap tm_w1, const __grid_constant__ CUtensorMap tm_qo,
        const __grid_constant__ CUtensorMap tm_ho, const __nv_bfloat16* __restrict__ x, const __nv_bfloat16* __restrict__ b1,
        float2* rowstat, float* colpart,
        __nv_bfloat16* __restrict__ kv, float* __restrict__ kvmax) {
    extern __shared__ __align__(1024) uint8_t smem_raw[];
    const uint32_t sbase = smem_u32(smem_raw);
    const uint32_t bar_full = sbase + K1_STAGES * K1_STAGE_BYTES, bar_empty = bar_full + 8 * K1_STAGES, bar_col = bar_empty + 8 * K1_STAGES;
    const uint32_t sCol = bar_full + 128;
    const int tid = threadIdx.x, warp = __shfl_sync(0xffffffffu, tid >> 5, 0), lane = tid & 31;
    const int grp = blockIdx.x & 7, rb = blockIdx.x >> 3;
    const int npanels = grp < 6 ? 5 : 4;
    if (tid == 0) DEV_STAMP(0, 0);

    if (tid == 288) {
        tma_prefetch_desc(&tm_x); tma_prefetch_desc(&tm_w1); tma_prefetch_desc(grp < 2 ? &tm_wq : grp == 6 ? &tm_wk : &tm_wv);
        tma_prefetch_desc(&tm_ho); tma_prefetch_desc(&tm_qo);
    }
    uint4 v[2][2];
    if (warp < 8) {
        const uint4* xp = reinterpret_cast<const uint4*>(x + (size_t)(rb * 128 + grp * 16 + warp * 2) * D_MODEL);
#pragma unroll
        for (int r = 0; r < 2; r++) { v[r][0] = __ldg(xp + r * 64 + lane); v[r][1] = __ldg(xp + r * 64 + 32 + lane); }
    }
    const int krot = rb & 8 ? 4 : 0, cstage = (rb >> 1) & 3;
    if (tid == 256) {
        for (int s = 0; s < K1_STAGES; s++) { mbar_init(bar_full + 8 * s, 1); mbar_init(bar_empty + 8 * s, s == cstage ? 9 : 8); }
        mbar_init(bar_col, 96);
        mbar_init_fence();
    }
    __syncthreads();
    pdl_launch();

    if (warp >= 8) {
        reg_dealloc<88>();
        if (warp == 8) {
            const CUtensorMap* tms[5]; int cols[5];
#pragma unroll
            for (int i = 0; i < 5; i++) {
                int type, col; k1_panel(grp, i, type, col);
                tms[i] = type == 0 ? &tm_wq : type == 1 ? &tm_w1 : type == 2 ? &tm_wk : &tm_wv;
                cols[i] = col;
            }
            if (lane == 0) {
                for (int ks = 0; ks < 8; ks++) {
                    const int s = ks % K1_STAGES;
                    const uint32_t st = sbase + s * K1_STAGE_BYTES;
                    if (ks >= K1_STAGES) mbar_wait(bar_empty + 8 * s, 0);
                    const int k0 = ((ks + krot) & 7) * 64;
                    mbar_expect_tx(bar_full + 8 * s, 16384 + npanels * K1_PANEL_BYTES);
                    tma_load_2d(st, &tm_x, k0, rb * 128, bar_full + 8 * s);
#pragma unroll
                    for (int i = 0; i < 5; i++)
                        if (i < npanels) tma_load_2d(st + 16384 + i * K1_PANEL_BYTES, tms[i], cols[i], k0, bar_full + 8 * s);
                }
            }
        } else {
            const int ht = tid - 288;
            mbar_wait(bar_full + 8 * cstage, 0);
            {
                const int pc = ht >> 1, half = ht & 1;
                float sacc[8];
#pragma unroll
                for (int c = 0; c < 8; c++) sacc[c] = 0.f;
                if (pc < npanels * 8) {
                    const uint32_t pb = sbase + cstage * K1_STAGE_BYTES + 16384 + (pc >> 3) * K1_PANEL_BYTES;
#pragma unroll
                    for (int i = 0; i < 16; i++) {
                        const int k = (rb & 1) * 32 + 2 * i + half;
                        uint4 u;
                        asm volatile("ld.shared.v4.b32 {%0,%1,%2,%3}, [%4];" : "=r"(u.x), "=r"(u.y), "=r"(u.z), "=r"(u.w)
                                     : "r"(pb + k * 128 + (((pc & 7) ^ (k & 7)) << 4)));
                        sacc[0] += bf_lo(u.x); sacc[1] += bf_hi(u.x); sacc[2] += bf_lo(u.y); sacc[3] += bf_hi(u.y);
                        sacc[4] += bf_lo(u.z); sacc[5] += bf_hi(u.z); sacc[6] += bf_lo(u.w); sacc[7] += bf_hi(u.w);
                    }
                }
#pragma unroll
                for (int c = 0; c < 8; c++) sacc[c] += __shfl_xor_sync(0xffffffffu, sacc[c], 1);
                if (pc < npanels * 8) {
                    float4* dst = reinterpret_cast<float4*>(colpart + (grp * 16 + rb) * 320 + pc * 8) + half;
                    *dst = half ? make_float4(xch_enc(sacc[4]), xch_enc(sacc[5]), xch_enc(sacc[6]), xch_enc(sacc[7]))
                                : make_float4(xch_enc(sacc[0]), xch_enc(sacc[1]), xch_enc(sacc[2]), xch_enc(sacc[3]));
                }
                named_bar_sync(4, 96);
                if (ht == 0) mbar_arrive(bar_empty + 8 * cstage);
            }
            if (ht == 0) DEV_STAMP(0, 6);
            for (int c2 = ht; c2 < npanels * 32; c2 += 96) {
                int type, col; k1_panel(grp, c2 >> 5, type, col);
                uint32_t bb = 0;
                if (type == 1) bb = __ldg(reinterpret_cast<const uint32_t*>(b1 + col) + (c2 & 31));
                uint2 pv[16];
                bool okv = false;
#pragma unroll 1
                for (uint32_t n = 0; n < (1u << 14) && !okv; n++) {
                    okv = true;
#pragma unroll
                    for (int k = 0; k < 16; k++) pv[k] = ld_relaxed_v2(colpart + (grp * 16 + k) * 320 + c2 * 2);
#pragma unroll
                    for (int k = 0; k < 16; k++) okv = okv && pv[k].x != NOT_READY && pv[k].y != NOT_READY;
                }
                float s0 = 0.f, s1 = 0.f;
#pragma unroll
                for (int k = 0; k < 16; k++) { s0 += xch_dec(pv[k].x); s1 += xch_dec(pv[k].y); }
                asm volatile("st.shared.v4.f32 [%0], {%1,%2,%3,%4};" ::"r"(sCol + c2 * 16), "f"(s0), "f"(bf_lo(bb)), "f"(s1), "f"(bf_hi(bb)) : "memory");
            }
            mbar_arrive(bar_col);
            if (ht == 0) DEV_STAMP(0, 7);
        }
    } else {
        reg_alloc<208>();
        const int wg = warp >> 2;
        const int g = lane >> 2, t = lane & 3;
        const int wrow = (warp & 3) * 16;
        {
            float f[2][16], sum[2], sq[2];
#pragma unroll
            for (int r = 0; r < 2; r++) {
                const uint32_t w[8] = {v[r][0].x, v[r][0].y, v[r][0].z, v[r][0].w, v[r][1].x, v[r][1].y, v[r][1].z, v[r][1].w};
#pragma unroll
                for (int i = 0; i < 8; i++) { f[r][2 * i] = bf_lo(w[i]); f[r][2 * i + 1] = bf_hi(w[i]); }
                sum[r] = 0.f;
#pragma unroll
                for (int i = 0; i < 16; i++) sum[r] += f[r][i];
            }
#pragma unroll
            for (int o = 16; o > 0; o >>= 1) { sum[0] += __shfl_xor_sync(0xffffffffu, sum[0], o); sum[1] += __shfl_xor_sync(0xffffffffu, sum[1], o); }
#pragma unroll
            for (int r = 0; r < 2; r++) {
                sum[r] *= (1.0f / D_MODEL);
                sq[r] = 0.f;
#pragma unroll
                for (int i = 0; i < 16; i++) { const float d = f[r][i] - sum[r]; sq[r] += d * d; }
            }
#pragma unroll
            for (int o = 16; o > 0; o >>= 1) { sq[0] += __shfl_xor_sync(0xffffffffu, sq[0], o); sq[1] += __shfl_xor_sync(0xffffffffu, sq[1], o); }
            if (lane < 2) {
                const float rstd = rsqrtf((lane ? sq[1] : sq[0]) * (1.0f / D_MODEL) + 1e-5f);
                rowstat[rb * 128 + grp * 16 + warp * 2 + lane] = make_float2(xch_enc(rstd), xch_enc((lane ? sum[1] : sum[0]) * rstd));
            }
            if (tid == 0) DEV_STAMP(0, 5);
        }
        float acc[160];
#pragma unroll
        for (int i = 0; i < 160; i++) acc[i] = 0.f;
        float2 rs0, rs1;
        const uint64_t dA0 = make_desc(sbase + wg * 8192, 16, 1024, 1);
        const uint64_t dB0 = make_desc(sbase + 16384, K1_PANEL_BYTES, 1024, 1);
#define K1_MAINLOOP(FIVE)                                                                                          \
        for (int ks = 0; ks < 8; ks++) {                                                                           \
            const int s = ks % K1_STAGES;                                                                          \
            mbar_wait(bar_full + 8 * s, (ks / K1_STAGES) & 1);                                                     \
            if (ks == 0 && tid == 0) DEV_STAMP(0, 1);                                                              \
            wg_fence();                                                                                            \
            _Pragma("unroll") for (int kk = 0; kk < 4; kk++) {                                                     \
                const uint64_t dA = dA0 + (uint64_t)((s * K1_STAGE_BYTES + kk * 32) >> 4);                         \
                const uint64_t dB = dB0 + (uint64_t)((s * K1_STAGE_BYTES + kk * 2048) >> 4);                       \
                wgmma_ss_n256_tb(acc, dA, dB, (ks | kk) != 0);                                                     \
                if (FIVE) wgmma_ss_n64_tb(acc + 128, dA, dB + (uint64_t)((4 * K1_PANEL_BYTES) >> 4), (ks | kk) != 0); \
            }                                                                                                      \
            wg_commit();                                                                                           \
            if (ks == 7) {                                                                                         \
                uint2 r0, r1;                                                                                      \
                uint32_t n = 0;                                                                                    \
                _Pragma("unroll 1") do {                                                                           \
                    r0 = ld_relaxed_v2(rowstat + rb * 128 + wg * 64 + wrow + g);                                   \
                    r1 = ld_relaxed_v2(rowstat + rb * 128 + wg * 64 + wrow + g + 8);                               \
                } while ((r0.x == NOT_READY || r0.y == NOT_READY || r1.x == NOT_READY || r1.y == NOT_READY) && ++n < (1u << 14)); \
                rs0 = make_float2(xch_dec(r0.x), xch_dec(r0.y));                                                   \
                rs1 = make_float2(xch_dec(r1.x), xch_dec(r1.y));                                                   \
                mbar_wait(bar_col, 0);                                                                             \
            }                                                                                                      \
            if (ks > 0 && ks <= 4) {                                                                               \
                wg_wait<1>();                                                                                      \
                if (lane == 0) mbar_arrive(bar_empty + 8 * ((ks - 1) % K1_STAGES));                                \
            }                                                                                                      \
        }                                                                                                          \
        wg_wait<0>();
        const int srow = (lane & 7) + ((lane >> 3) & 1) * 8;
        if (npanels == 5) { K1_MAINLOOP(true) } else { K1_MAINLOOP(false) }
        fence_regs<160>(acc);
        if (tid == 0) DEV_STAMP(0, 2);
        named_bar_sync(1, 256);
#pragma unroll
        for (int p = 0; p < 5; p++) {
            if (p < npanels) {
                int type, col; k1_panel(grp, p, type, col);
                float* a = acc + p * 32;
                const int nj = type <= 1 ? 8 : 2;
                const float sc = type == 0 ? Q_SCALE : 1.0f;
                const float r0x = rs0.x * sc, r0y = -rs0.y * sc, r1x = rs1.x * sc, r1y = -rs1.y * sc;
#pragma unroll
                for (int j = 0; j < 8; j++) {
                    if (j < nj) {
                        float4 c;
                        asm volatile("ld.shared.v4.f32 {%0,%1,%2,%3}, [%4];" : "=f"(c.x), "=f"(c.y), "=f"(c.z), "=f"(c.w)
                                     : "r"(sCol + (p * 64 + j * 8 + 2 * t) * 8));
                        a[4 * j] = fmaf(a[4 * j], r0x, fmaf(r0y, c.x, c.y));
                        a[4 * j + 1] = fmaf(a[4 * j + 1], r0x, fmaf(r0y, c.z, c.w));
                        a[4 * j + 2] = fmaf(a[4 * j + 2], r1x, fmaf(r1y, c.x, c.y));
                        a[4 * j + 3] = fmaf(a[4 * j + 3], r1x, fmaf(r1y, c.z, c.w));
                    }
                }
                if (type <= 1) {
                    const uint32_t stg = sbase + (p * 8 + warp) * 2048;
                    uint32_t pk[16];
                    if (type == 0) {
#pragma unroll
                        for (int j = 0; j < 8; j++) {
                            pk[2 * j] = pack_bf16(a[4 * j], a[4 * j + 1]);
                            pk[2 * j + 1] = pack_bf16(a[4 * j + 2], a[4 * j + 3]);
                        }
                    } else {
#pragma unroll
                        for (int j = 0; j < 8; j++) {
                            const uint32_t h0 = pack_bf16_relu(a[4 * j], a[4 * j + 1]), h1 = pack_bf16_relu(a[4 * j + 2], a[4 * j + 3]);
                            pk[2 * j] = mul_bf16x2(h0, h0);
                            pk[2 * j + 1] = mul_bf16x2(h1, h1);
                        }
                    }
#pragma unroll
                    for (int j = 0; j < 8; j += 2) {
                        const int c16 = j + (lane >> 4);
                        stmatrix_x4(stg + srow * 128 + ((c16 ^ (srow & 7)) << 4), pk[2 * j], pk[2 * j + 1], pk[2 * j + 2], pk[2 * j + 3]);
                    }
                    fence_proxy_async();
                    __syncwarp();
                    if (lane == 0) {
                        tma_store_2d(type == 0 ? &tm_qo : &tm_ho, stg, col, rb * 128 + warp * 16);
                        tma_store_commit();
                    }
                } else if (type == 3) {
                    const int r = wg * 64 + wrow + g;
                    const int pos0 = (r >> 2) * 64 + rb * 4 + (r & 3), pos1 = pos0 + 128;
                    uint32_t* dst = reinterpret_cast<uint32_t*>(kv);
                    const uint32_t r00 = pack_bf16(a[0], a[1]), r01 = pack_bf16(a[4], a[5]);
                    const uint32_t r10 = pack_bf16(a[2], a[3]), r11 = pack_bf16(a[6], a[7]);
                    dst[(pos0 >> 4) * 128 + (pos0 & 15) * 4 + t] = r00;
                    dst[16384 + pos0 * 4 + t] = r01;
                    dst[(pos1 >> 4) * 128 + (pos1 & 15) * 4 + t] = r10;
                    dst[16384 + pos1 * 4 + t] = r11;
                    float m = fmaxf(fmaxf(fmaxf(fabsf(bf_lo(r00)), fabsf(bf_hi(r00))), fmaxf(fabsf(bf_lo(r01)), fabsf(bf_hi(r01)))),
                                    fmaxf(fmaxf(fabsf(bf_lo(r10)), fabsf(bf_hi(r10))), fmaxf(fabsf(bf_lo(r11)), fabsf(bf_hi(r11)))));
#pragma unroll
                    for (int o = 16; o > 0; o >>= 1) m = fmaxf(m, __shfl_xor_sync(0xffffffffu, m, o));
                    if (lane == 0) kvmax[128 + rb * 8 + warp] = m;
                } else {
                    float* kf = reinterpret_cast<float*>(smem_raw + 96 * 1024);
                    const int r = wg * 64 + wrow + g;
                    const int pos0 = (r >> 2) * 64 + rb * 4 + (r & 3), pos1 = pos0 + 128;
                    uint32_t* dst = reinterpret_cast<uint32_t*>(kv) + 32768;
                    dst[(pos0 >> 3) * 64 + (pos0 & 7) * 4 + t] = pack_bf16(a[0], a[1]);
                    dst[(pos0 >> 3) * 64 + 32 + (pos0 & 7) * 4 + t] = pack_bf16(a[4], a[5]);
                    dst[(pos1 >> 3) * 64 + (pos1 & 7) * 4 + t] = pack_bf16(a[2], a[3]);
                    dst[(pos1 >> 3) * 64 + 32 + (pos1 & 7) * 4 + t] = pack_bf16(a[6], a[7]);
                    kf[r * 17 + 2 * t] = a[0]; kf[r * 17 + 2 * t + 1] = a[1];
                    kf[r * 17 + 8 + 2 * t] = a[4]; kf[r * 17 + 8 + 2 * t + 1] = a[5];
                    kf[(r + 8) * 17 + 2 * t] = a[2]; kf[(r + 8) * 17 + 2 * t + 1] = a[3];
                    kf[(r + 8) * 17 + 8 + 2 * t] = a[6]; kf[(r + 8) * 17 + 8 + 2 * t + 1] = a[7];
                    named_bar_sync(1, 256);
                    if (tid < 64) {
                        const int i = tid >> 4, dim = tid & 15;
                        const int c = rb * 4 + i;
                        const int inner = (dim >> 3) * 64 + (c & 7) * 8 + (dim & 7);
                        float kt = 0.f;
#pragma unroll 8
                        for (int j = 0; j < 32; j++) {
                            const __nv_bfloat16 d = __float2bfloat16_rn(kf[(j * 4 + i) * 17 + dim] - kt);
                            kt += __bfloat162float(d);
                            kf[(j * 4 + i) * 17 + dim] = kt;
                            const int gi = (j >> 1) * 8 + (c >> 3);
                            kv[((j & 1) ? 49152 + gi * 128 : gi * 256 + 128) + inner] = d;
                        }
                    }
                    named_bar_sync(1, 256);
                    if (tid < 128) {
                        float n = 0.f;
#pragma unroll
                        for (int d = 0; d < 16; d++) { const float v = kf[tid * 17 + d]; n += v * v; }
                        if (!(n == n)) n = __int_as_float(0x7f800000);
#pragma unroll
                        for (int o = 8; o > 0; o >>= 1) n = fmaxf(n, __shfl_xor_sync(0xffffffffu, n, o));
                        if ((lane & 15) == 0) kvmax[rb * 8 + (tid >> 4)] = n;
                    }
                }
            }
        }
        if (tid == 0) DEV_STAMP(0, 3);
        if (lane == 0) tma_store_wait();
        if (tid == 0) DEV_STAMP(0, 4);
    }
}

constexpr int AT_KT = 64;
constexpr int AT_NCHUNK = 8;
constexpr int AT_NSTEP = S_LEN / AT_KT;
constexpr int AT_SPC = AT_NSTEP / AT_NCHUNK;
constexpr int AT_ONES = 131072;
constexpr int F2_STAGES = 4;
constexpr int F2_STAGE_BYTES = 8192 + 16384;
constexpr int F2_BASE = 132096;
constexpr int F2_NK = F_DIM / 64;
constexpr int AT_BAR = F2_BASE + F2_STAGES * F2_STAGE_BYTES;
constexpr int AT_SMEM = AT_BAR + 256;
#define AT_SWMASK_V 0xB6DB
constexpr uint32_t AT_SWMASK = AT_SWMASK_V;

#define AT_MAGIC 382.41765f
__device__ __forceinline__ uint32_t exp2_pair_alu(float t0, float t1) {
    uint32_t y;
    asm("prmt.b32 %0, %1, %2, 0x6521;" : "=r"(y) : "f"(t0), "f"(t1));
    const uint32_t e = y & 0x7F807F80u;
    uint32_t uh, p;
    asm("lop3.b32 %0, %1, %2, 0x3F003F00, 0xBE;" : "=r"(uh) : "r"(y), "r"(e));
    asm("fma.rn.bf16x2 %0, %1, %2, %3;" : "=r"(p) : "r"(uh), "r"(y), "r"(e));
    return p;
}

__device__ __forceinline__ void at_load_chunk(uint32_t sbase, const __nv_bfloat16* KV, uint32_t bar0, int c) {
    const uint8_t* src = reinterpret_cast<const uint8_t*>(KV);
    mbar_expect_tx(bar0 + 8 * c, 16384);
    bulk_g2s(sbase + c * 8192, src + c * 8192, 8192, bar0 + 8 * c);
    bulk_g2s(sbase + 98304 + c * 4096, src + 98304 + c * 4096, 4096, bar0 + 8 * c);
    bulk_g2s(sbase + 65536 + c * 4096, src + 65536 + c * 4096, 4096, bar0 + 8 * c);
}

__device__ __forceinline__ void at_store(const float* o, __nv_bfloat16* O, int row, int lane) {
    const float l0 = __shfl_sync(0xffffffffu, o[8], lane & ~3);
    const float l1 = __shfl_sync(0xffffffffu, o[10], lane & ~3);
    const float r0 = __fdividef(1.0f, l0), r1 = __fdividef(1.0f, l1);
    const int t = lane & 3;
    uint32_t* op = reinterpret_cast<uint32_t*>(O + (size_t)(row + (lane >> 2)) * 16);
    op[t] = pack_bf16(o[0] * r0, o[1] * r0);
    op[t + 4] = pack_bf16(o[4] * r0, o[5] * r0);
    op[64 + t] = pack_bf16(o[2] * r1, o[3] * r1);
    op[64 + t + 4] = pack_bf16(o[6] * r1, o[7] * r1);
}

__device__ __forceinline__ void mma16816(float* c, const uint32_t* a, uint32_t b0, uint32_t b1) {
    asm volatile("mma.sync.aligned.m16n8k16.row.col.f32.bf16.bf16.f32 {%0,%1,%2,%3}, {%4,%5,%6,%7}, {%8,%9}, {%0,%1,%2,%3};"
                 : "+f"(c[0]), "+f"(c[1]), "+f"(c[2]), "+f"(c[3]) : "r"(a[0]), "r"(a[1]), "r"(a[2]), "r"(a[3]), "r"(b0), "r"(b1));
}
__device__ __forceinline__ void attn_fallback(const __nv_bfloat16* Q, const __nv_bfloat16* KV, __nv_bfloat16* O, uint32_t sbase) {
    const int tid = threadIdx.x;
    const int lane = tid & 31, g = lane >> 2, t = lane & 3;
    const uint32_t* Kg = reinterpret_cast<const uint32_t*>(KV + 65536);
#pragma unroll 1
    for (int mt = 0; mt < 2; mt++) {
        const int row = blockIdx.x * 512 + (tid >> 7) * 128 + mt * 64 + ((tid >> 5) & 3) * 16;
        const uint32_t* qp = reinterpret_cast<const uint32_t*>(Q + (size_t)(row + g) * 16);
        const uint32_t q[4] = {qp[t], qp[64 + t], qp[t + 4], qp[64 + t + 4]};
        float o[12];
#pragma unroll
        for (int i = 0; i < 12; i++) o[i] = 0.f;
        float m0 = -INFINITY, m1 = -INFINITY;
#pragma unroll 1
        for (int kt = 0; kt < S_LEN / 16; kt++) {
            float s[8];
#pragma unroll
            for (int i = 0; i < 8; i++) s[i] = 0.f;
#pragma unroll
            for (int h = 0; h < 2; h++) {
                const uint32_t* kp = Kg + (kt * 2 + h) * 64 + g * 4 + t;
                mma16816(s + 4 * h, q, kp[0], kp[32]);
            }
            float x0 = fmaxf(fmaxf(s[0], s[1]), fmaxf(s[4], s[5])), x1 = fmaxf(fmaxf(s[2], s[3]), fmaxf(s[6], s[7]));
            x0 = fmaxf(x0, __shfl_xor_sync(0xffffffffu, x0, 1)); x0 = fmaxf(x0, __shfl_xor_sync(0xffffffffu, x0, 2));
            x1 = fmaxf(x1, __shfl_xor_sync(0xffffffffu, x1, 1)); x1 = fmaxf(x1, __shfl_xor_sync(0xffffffffu, x1, 2));
            x0 = fmaxf(x0, m0); x1 = fmaxf(x1, m1);
            const float f0 = ex2(m0 - x0), f1 = ex2(m1 - x1);
            m0 = x0; m1 = x1;
#pragma unroll
            for (int j = 0; j < 3; j++) { o[4 * j] *= f0; o[4 * j + 1] *= f0; o[4 * j + 2] *= f1; o[4 * j + 3] *= f1; }
            const uint32_t p[4] = {pack_bf16(ex2(s[0] - m0), ex2(s[1] - m0)), pack_bf16(ex2(s[2] - m1), ex2(s[3] - m1)),
                                   pack_bf16(ex2(s[4] - m0), ex2(s[5] - m0)), pack_bf16(ex2(s[6] - m1), ex2(s[7] - m1))};
#pragma unroll
            for (int j = 0; j < 3; j++) {
                const uint32_t base = sbase + (j == 0 ? kt * 512 : j == 1 ? 65536 + kt * 256 : AT_ONES) + (lane & 15) * 16;
                uint32_t b0, b1;
                asm volatile("ldmatrix.sync.aligned.m8n8.x2.trans.shared.b16 {%0,%1}, [%2];" : "=r"(b0), "=r"(b1) : "r"(base));
                mma16816(o + 4 * j, p, b0, b1);
            }
        }
        at_store(o, O, row, lane);
    }
}

__global__ void __launch_bounds__(640, 1)
k2_attn(const __grid_constant__ CUtensorMap tm_h, const __grid_constant__ CUtensorMap tm_w2,
        const __nv_bfloat16* __restrict__ Q, const __nv_bfloat16* __restrict__ KV, const float* __restrict__ kvmax,
        const __nv_bfloat16* __restrict__ b2, __nv_bfloat16* __restrict__ O, __nv_bfloat16* __restrict__ G,
        uint2* __restrict__ rowstat, uint2* __restrict__ colpart) {
    extern __shared__ __align__(1024) uint8_t smem_raw[];
    const uint32_t sbase = smem_u32(smem_raw);
    const uint32_t bar0 = sbase + AT_BAR, f2_full = bar0 + 64, f2_empty = f2_full + 32, bar_guard = f2_empty + 32, bar_first = bar_guard + 8, sGuard = bar0 + 192;
    const int tid = threadIdx.x;
    const int wg = __shfl_sync(0xffffffffu, tid >> 7, 0);
    const int warp = (tid >> 5) & 3, lane = tid & 31;
    const int g = lane >> 2, t = lane & 3;
    if (tid == 0) DEV_STAMP(1, 0);
    if (tid == 0) {
        for (int i = 0; i < AT_NCHUNK; i++) mbar_init(bar0 + 8 * i, 1);
        for (int i = 0; i < F2_STAGES; i++) { mbar_init(f2_full + 8 * i, 1); mbar_init(f2_empty + 8 * i, 4); }
        mbar_init(bar_guard, 4);
        mbar_init(bar_first, 1);
        mbar_init_fence();
    }
    if (tid < 16) asm volatile("st.shared.v4.b32 [%0], {%1,%2,%2,%2};" ::"r"(sbase + AT_ONES + tid * 16), "r"(0x00003F80u), "r"(0u) : "memory");
    fence_proxy_async();
    __syncthreads();

    if (wg == 4) {
        const int rb = blockIdx.x >> 2, cb = blockIdx.x & 3;
        const uint32_t fb = sbase + F2_BASE;
        const bool leader = tid == 512;
        if (leader) {
#pragma unroll
            for (int s = 0; s < F2_STAGES; s++) {
                mbar_expect_tx(f2_full + 8 * s, F2_STAGE_BYTES);
                tma_load_2d(fb + s * F2_STAGE_BYTES + 8192, &tm_w2, cb * 128, s * 64, f2_full + 8 * s);
                tma_load_2d(fb + s * F2_STAGE_BYTES + 16384, &tm_w2, cb * 128 + 64, s * 64, f2_full + 8 * s);
            }
        }
        pdl_wait();
        mbar_wait(bar0, 0);
        if (leader) {
#pragma unroll
            for (int s = 0; s < F2_STAGES; s++) tma_load_2d(fb + s * F2_STAGE_BYTES, &tm_h, s * 64, rb * 64, f2_full + 8 * s);
        }
        {
            float km = fmaxf(fmaxf(kvmax[lane], kvmax[lane + 32]), fmaxf(kvmax[lane + 64], kvmax[lane + 96]));
            float vm = fmaxf(fmaxf(kvmax[128 + lane], kvmax[160 + lane]), fmaxf(kvmax[192 + lane], kvmax[224 + lane]));
            uint4 qv[4][2];
#pragma unroll
            for (int i = 0; i < 4; i++) {
                const uint4* qr = reinterpret_cast<const uint4*>(Q + (size_t)(blockIdx.x * 512 + warp * 128 + i * 16 + (lane >> 4) * 64 + (lane & 15)) * 16);
                qv[i][0] = qr[0]; qv[i][1] = qr[1];
            }
#pragma unroll
            for (int o = 16; o > 0; o >>= 1) { km = fmaxf(km, __shfl_xor_sync(0xffffffffu, km, o)); vm = fmaxf(vm, __shfl_xor_sync(0xffffffffu, vm, o)); }
#pragma unroll
            for (int i = 0; i < 4; i++) {
                const uint32_t qw[8] = {qv[i][0].x, qv[i][0].y, qv[i][0].z, qv[i][0].w, qv[i][1].x, qv[i][1].y, qv[i][1].z, qv[i][1].w};
                float qn = 0.f;
#pragma unroll
                for (int j = 0; j < 8; j++) qn += bf_lo(qw[j]) * bf_lo(qw[j]) + bf_hi(qw[j]) * bf_hi(qw[j]);
                const bool ok = (qn * km <= 3600.0f) && (vm <= 1.0e12f);
                const uint32_t bad = __any_sync(0xffffffffu, !ok);
                if (lane == 0) asm volatile("st.shared.u32 [%0], %1;" ::"r"(sGuard + (warp * 4 + i) * 4), "r"(bad) : "memory");
            }
            if (lane == 0) mbar_arrive(bar_guard);
        }
        __syncwarp();
        const uint64_t dA0 = make_desc(fb, 16, 1024, 1);
        const uint64_t dB0 = make_desc(fb + 8192, 8192, 1024, 1);
        float acc[64];
#pragma unroll
        for (int i = 0; i < 64; i++) asm volatile("mov.f32 %0, 0f00000000;" : "=f"(acc[i]));
#pragma unroll 1
        for (int ks = 0; ks < F2_NK; ks++) {
            const int s = ks % F2_STAGES;
            mbar_wait(f2_full + 8 * s, (ks / F2_STAGES) & 1);
            wg_fence();
#pragma unroll
            for (int kk = 0; kk < 4; kk++)
                wgmma_ss_n128_tb(acc, dA0 + (uint64_t)((s * F2_STAGE_BYTES + kk * 32) >> 4),
                                 dB0 + (uint64_t)((s * F2_STAGE_BYTES + kk * 2048) >> 4), 1);
            wg_commit();
            wg_wait<1>();
            if (ks > 0 && ks - 1 + F2_STAGES < F2_NK) {
                const int ps = (ks - 1) % F2_STAGES, k0 = (ks - 1 + F2_STAGES) * 64;
                if (lane == 0) mbar_arrive(f2_empty + 8 * ps);
                if (leader) {
                    mbar_wait(f2_empty + 8 * ps, ((ks - 1) / F2_STAGES) & 1);
                    mbar_expect_tx(f2_full + 8 * ps, F2_STAGE_BYTES);
                    tma_load_2d(fb + ps * F2_STAGE_BYTES, &tm_h, k0, rb * 64, f2_full + 8 * ps);
                    tma_load_2d(fb + ps * F2_STAGE_BYTES + 8192, &tm_w2, cb * 128, k0, f2_full + 8 * ps);
                    tma_load_2d(fb + ps * F2_STAGE_BYTES + 16384, &tm_w2, cb * 128 + 64, k0, f2_full + 8 * ps);
                }
                __syncwarp();
            }
        }
        wg_wait<0>();
        fence_regs<64>(acc);
        uint32_t* gp = reinterpret_cast<uint32_t*>(G + (size_t)(rb * 64 + warp * 16 + g) * D_MODEL + cb * 128) + t;
#pragma unroll
        for (int j = 0; j < 16; j++) {
            const uint32_t bb = __ldg(reinterpret_cast<const uint32_t*>(b2 + cb * 128 + j * 8) + t);
            const float b0 = bf_lo(bb), b1v = bf_hi(bb);
            const float z0 = acc[4 * j] + b0, z1 = acc[4 * j + 1] + b1v, z2 = acc[4 * j + 2] + b0, z3 = acc[4 * j + 3] + b1v;
            gp[j * 4] = pack_bf16(__fdividef(z0, 1.0f + __expf(-z0)), __fdividef(z1, 1.0f + __expf(-z1)));
            gp[j * 4 + 8 * (D_MODEL / 2)] = pack_bf16(__fdividef(z2, 1.0f + __expf(-z2)), __fdividef(z3, 1.0f + __expf(-z3)));
        }
        if (leader) DEV_STAMP(1, 5);
        return;
    }

    pdl_wait();
    pdl_launch();
    if (tid == 0) DEV_STAMP(1, 1);
    if (tid == 0) {
        const uint8_t* src = reinterpret_cast<const uint8_t*>(KV);
        mbar_expect_tx(bar_first, 4096);
        bulk_g2s(sbase, src, 4096, bar_first);
        mbar_expect_tx(bar0, 12288);
        bulk_g2s(sbase + 98304, src + 98304, 4096, bar0);
        bulk_g2s(sbase + 65536, src + 65536, 4096, bar0);
        bulk_g2s(sbase + 4096, src + 4096, 4096, bar0);
        at_load_chunk(sbase, KV, bar0, 1); at_load_chunk(sbase, KV, bar0, 2);
    }
    if (tid >= 128 && tid < 288) colpart[blockIdx.x * 160 + tid - 128] = make_uint2(NOT_READY, NOT_READY);
    if (tid >= 288 && tid < 304) rowstat[blockIdx.x * 16 + tid - 288] = make_uint2(NOT_READY, NOT_READY);
    const int rowA = blockIdx.x * 512 + wg * 128 + warp * 16;
    const uint32_t* qp = reinterpret_cast<const uint32_t*>(Q + (size_t)(rowA + g) * 16);
    const uint32_t lo0 = ((sbase & 0x3FFFF) >> 4) | (8u << 16);

#define AT_EXP(P) _Pragma("unroll") for (int i = 0; i < AT_KT / 4; i++) {                       \
                if ((AT_SWMASK >> (i & 15)) & 1) P[i] = exp2_pair_alu(s[2 * i], s[2 * i + 1]);  \
                else P[i] = pack_bf16(ex2(s[2 * i]), ex2(s[2 * i + 1])); }
    uint64_t vstep = 32ull - (16ull << 32);
    asm volatile("" : "+l"(vstep));
#define AT_PV1(P, j) { wgmma_pv(o, P[4 * (j)], P[4 * (j) + 1], P[4 * (j) + 2], P[4 * (j) + 3], dV); dV += vstep; }
#define AT_EXPH(P, h) _Pragma("unroll") for (int i = (h) * 8; i < (h) * 8 + 8; i++) {           \
                if ((AT_SWMASK >> (i & 15)) & 1) P[i] = exp2_pair_alu(s[2 * i], s[2 * i + 1]);  \
                else P[i] = pack_bf16(ex2(s[2 * i]), ex2(s[2 * i + 1])); }
#define AT_STEP(st, DK, INC) {                                                                  \
                wg_wait<0>();                                                                   \
                fence_regs<AT_KT / 2>(s);                                                       \
                AT_EXPH(p0, 0);                                                                 \
                wg_fence();                                                                     \
                AT_PV1(p0, 0); AT_PV1(p0, 1);                                                   \
                wg_commit();                                                                    \
                AT_EXPH(p0, 1);                                                                 \
                if (st == AT_SPC - 1 && mt == 0) mbar_wait(bar0 + 8 * (c + 1), 0);              \
                wg_wait<0>();                                                                   \
                wg_fence();                                                                     \
                wgmma_qk_acc_n64(s, q, DK); DK += INC;                                          \
                AT_PV1(p0, 2); AT_PV1(p0, 3);                                                   \
                wg_commit(); }

#pragma unroll 1
    for (int mt = 0; mt < 2; mt++) {
        uint32_t q[4];
        q[0] = qp[mt * 512 + t]; q[2] = qp[mt * 512 + t + 4]; q[1] = qp[mt * 512 + 64 + t]; q[3] = qp[mt * 512 + 64 + t + 4];
        float o[12];
#pragma unroll
        for (int i = 0; i < 12; i++) asm volatile("mov.f32 %0, 0f00000000;" : "=f"(o[i]));
        float s[AT_KT / 2];
        uint32_t p0[AT_KT / 4];
#pragma unroll
        for (int i = 0; i < AT_KT / 2; i++) {
            if ((AT_SWMASK >> ((i >> 1) & 15)) & 1) asm volatile("mov.f32 %0, %1;" : "=f"(s[i]) : "f"(AT_MAGIC));
            else asm volatile("mov.f32 %0, 0f00000000;" : "=f"(s[i]));
        }
        if (mt == 0) mbar_wait(bar_first, 0);
        if (tid == 0) DEV_STAMP(1, 2 + mt);
        uint64_t dV = desc64(lo0, 4096), dX = desc64(lo0 + 16, 32), dY = desc64(lo0 + (98304 >> 4), 16);
        wg_fence();
        wgmma_qk_acc_n64(s, q, dX); dX += 256;
        wg_commit();
        if (mt == 0) mbar_wait(bar0, 0);
#pragma unroll 1
        for (int c = 0; c < AT_NCHUNK - 1; c++) {
            if (tid == 0 && mt == 0 && c + 3 < AT_NCHUNK) at_load_chunk(sbase, KV, bar0, c + 3);
            AT_STEP(0, dY, 128); AT_STEP(1, dX, 256); AT_STEP(2, dY, 128); AT_STEP(3, dX, 256);
        }
        {
            const int c = 0; (void)c;
            AT_STEP(0, dY, 128); AT_STEP(1, dX, 256); AT_STEP(2, dY, 128);
            wg_wait<0>();
            fence_regs<AT_KT / 2>(s);
            AT_EXP(p0);
            wg_fence();
            AT_PV1(p0, 0); AT_PV1(p0, 1); AT_PV1(p0, 2); AT_PV1(p0, 3);
            wg_commit();
            wg_wait<0>();
            fence_regs<12>(o);
        }
        at_store(o, O, rowA + mt * 64, lane);
    }
    if (tid == 0) DEV_STAMP(1, 4);

    mbar_wait(bar_guard, 0);
    uint32_t bad;
    asm volatile("ld.shared.u32 %0, [%1];" : "=r"(bad) : "r"(sGuard + (tid >> 5) * 4) : "memory");
    if (__any_sync(0xffffffffu, bad != 0) == 0) return;
    attn_fallback(Q, KV, O, sbase);
}

constexpr int K3_STAGE_BYTES = 16384 + 8192;
constexpr int K3_X = 8 * K3_STAGE_BYTES;
constexpr int K3_G = K3_X + 16384;
constexpr int K3_SMEM = K3_G + 16384 + 256;

__global__ void __launch_bounds__(256, 1)
k3_out(const __grid_constant__ CUtensorMap tm_o, const __grid_constant__ CUtensorMap tm_wo,
       const __grid_constant__ CUtensorMap tm_x, const __grid_constant__ CUtensorMap tm_g,
       const __grid_constant__ CUtensorMap tm_out) {
    extern __shared__ __align__(1024) uint8_t smem_raw[];
    const uint32_t sbase = smem_u32(smem_raw);
    const uint32_t sX = sbase + K3_X, sG = sbase + K3_G;
    const uint32_t bar_full = sG + 16384, bar_x = bar_full + 64;
    const int tid = threadIdx.x, warp = __shfl_sync(0xffffffffu, tid >> 5, 0), lane = tid & 31;
    const int rb = blockIdx.x >> 3, cb = blockIdx.x & 7;
    if (tid == 0) {
        DEV_STAMP(2, 0);
        for (int s = 0; s < 8; s++) mbar_init(bar_full + 8 * s, 1);
        mbar_init(bar_x, 1);
        mbar_init_fence();
        for (int s = 0; s < 8; s++) {
            mbar_expect_tx(bar_full + 8 * s, K3_STAGE_BYTES);
            tma_load_2d(sbase + s * K3_STAGE_BYTES + 16384, &tm_wo, cb * 64, s * 64, bar_full + 8 * s);
        }
        mbar_expect_tx(bar_x, 32768);
        tma_load_2d(sX, &tm_x, cb * 64, rb * 128, bar_x);
        pdl_wait();
        DEV_STAMP(2, 1);
        for (int s = 0; s < 8; s++) tma_load_2d(sbase + s * K3_STAGE_BYTES, &tm_o, s * 64, rb * 128, bar_full + 8 * s);
        tma_load_2d(sG, &tm_g, cb * 64, rb * 128, bar_x);
    }
    __syncthreads();
    const int wg = warp >> 2;
    float acc[32];
#pragma unroll
    for (int i = 0; i < 32; i++) asm volatile("mov.f32 %0, 0f00000000;" : "=f"(acc[i]));
    const uint64_t dA0 = make_desc(sbase + wg * 8192, 16, 1024, 1);
    const uint64_t dB0 = make_desc(sbase + 16384, 8192, 1024, 1);
#pragma unroll 1
    for (int ks = 0; ks < 8; ks++) {
        mbar_wait(bar_full + 8 * ks, 0);
        wg_fence();
#pragma unroll
        for (int kk = 0; kk < 4; kk++)
            wgmma_ss_n64_tb(acc, dA0 + (uint64_t)((ks * K3_STAGE_BYTES + kk * 32) >> 4),
                            dB0 + (uint64_t)((ks * K3_STAGE_BYTES + kk * 2048) >> 4), 1);
        wg_commit();
    }
    wg_wait<0>();
    fence_regs<32>(acc);
    if (tid == 0) DEV_STAMP(2, 2);
    mbar_wait(bar_x, 0);
    const int g = lane >> 2, t = lane & 3;
    const int row0 = warp * 16 + g;
#pragma unroll
    for (int j = 0; j < 8; j++) {
#pragma unroll
        for (int h = 0; h < 2; h++) {
            const int row = row0 + h * 8;
            const uint32_t off = row * 128 + ((j ^ (row & 7)) << 4) + t * 4;
            uint32_t xv, gv;
            asm volatile("ld.shared.b32 %0, [%1];" : "=r"(xv) : "r"(sX + off) : "memory");
            asm volatile("ld.shared.b32 %0, [%1];" : "=r"(gv) : "r"(sG + off) : "memory");
            const uint32_t ov = pack_bf16(fmaf(acc[4 * j + 2 * h], bf_lo(gv), bf_lo(xv)), fmaf(acc[4 * j + 2 * h + 1], bf_hi(gv), bf_hi(xv)));
            asm volatile("st.shared.b32 [%0], %1;" ::"r"(sX + off), "r"(ov) : "memory");
        }
    }
    fence_proxy_async();
    __syncwarp();
    if (lane == 0) {
        tma_store_2d(&tm_out, sX + warp * 2048, cb * 64, rb * 128 + warp * 16);
        tma_store_commit();
        if (tid == 0) DEV_STAMP(2, 3);
        tma_store_wait();
        if (tid == 0) DEV_STAMP(2, 4);
    }
}

typedef CUresult (*EncodeFn)(CUtensorMap*, CUtensorMapDataType, cuuint32_t, void*, const cuuint64_t*, const cuuint64_t*,
                             const cuuint32_t*, const cuuint32_t*, CUtensorMapInterleave, CUtensorMapSwizzle,
                             CUtensorMapL2promotion, CUtensorMapFloatOOBfill);

struct HostState {
    bool ready;
    const void* key[11];
    CUtensorMap wq, wk, wv, w1, qo, ho, hi, oi, w2, wo, xi, gi, out;
    void *pQ, *pKV, *pH, *pO, *pMax, *pRow, *pCol, *pFlag, *pG;
};
HostState g_hs;

void make_map(EncodeFn fn, CUtensorMap* m, const void* ptr, uint64_t inner, uint64_t outer, uint32_t box_in, uint32_t box_out) {
    cuuint64_t dims[2] = {inner, outer};
    cuuint64_t strides[1] = {inner * 2};
    cuuint32_t box[2] = {box_in, box_out};
    cuuint32_t es[2] = {1, 1};
    fn(m, CU_TENSOR_MAP_DATA_TYPE_BFLOAT16, 2, const_cast<void*>(ptr), dims, strides, box, es, CU_TENSOR_MAP_INTERLEAVE_NONE,
       CU_TENSOR_MAP_SWIZZLE_128B, CU_TENSOR_MAP_L2_PROMOTION_L2_256B, CU_TENSOR_MAP_FLOAT_OOB_FILL_NONE);
}

template <typename... KArgs, typename... Args>
void launch(void (*kern)(KArgs...), int grid, int block, int smem, bool pdl, Args... args) {
    cudaLaunchConfig_t cfg = {};
    cfg.gridDim = dim3(grid); cfg.blockDim = dim3(block); cfg.dynamicSmemBytes = smem; cfg.stream = cudaStreamPerThread;
    cudaLaunchAttribute at[1];
    at[0].id = cudaLaunchAttributeProgrammaticStreamSerialization;
    at[0].val.programmaticStreamSerializationAllowed = 1;
    cfg.attrs = at; cfg.numAttrs = pdl ? 1 : 0;
    cudaLaunchKernelEx(&cfg, kern, KArgs(args)...);
}

}

extern "C" void kernel_launch(void* const* d_in, const int* in_sizes, int n_in, void* d_out, int out_size) {
    (void)in_sizes; (void)n_in; (void)out_size;
    HostState& hs = g_hs;
    bool same = hs.ready;
    for (int i = 0; i < 10 && same; i++) same = hs.key[i] == d_in[i];
    same = same && hs.key[10] == d_out;
    if (!same) {
        void* fp = nullptr;
        cudaDriverEntryPointQueryResult qr;
        cudaGetDriverEntryPoint("cuTensorMapEncodeTiled", &fp, cudaEnableDefault, &qr);
        EncodeFn fn = (EncodeFn)fp;
        cudaGetSymbolAddress(&hs.pQ, g_Q); cudaGetSymbolAddress(&hs.pKV, g_KV); cudaGetSymbolAddress(&hs.pH, g_H);
        cudaGetSymbolAddress(&hs.pO, g_O); cudaGetSymbolAddress(&hs.pMax, g_kvmax);
        cudaGetSymbolAddress(&hs.pRow, g_rowstat); cudaGetSymbolAddress(&hs.pCol, g_colpart); cudaGetSymbolAddress(&hs.pG, g_G);
        make_map(fn, &hs.wq, d_in[1], 512, 512, 64, 64);
        make_map(fn, &hs.wk, d_in[2], 16, 512, 64, 64);
        make_map(fn, &hs.wv, d_in[3], 16, 512, 64, 64);
        make_map(fn, &hs.w1, d_in[6], F_DIM, 512, 64, 64);
        make_map(fn, &hs.qo, hs.pQ, 512, S_LEN, 64, 16);
        make_map(fn, &hs.ho, hs.pH, F_DIM, S_LEN, 64, 16);
        make_map(fn, &hs.hi, hs.pH, F_DIM, S_LEN, 64, 64);
        make_map(fn, &hs.gi, hs.pG, 512, S_LEN, 64, 128);
        make_map(fn, &hs.oi, hs.pO, 512, S_LEN, 64, 128);
        make_map(fn, &hs.w2, d_in[8], 512, F_DIM, 64, 64);
        make_map(fn, &hs.wo, d_in[4], 512, 512, 64, 64);
        make_map(fn, &hs.xi, d_in[0], 512, S_LEN, 64, 128);
        make_map(fn, &hs.out, d_out, 512, S_LEN, 64, 16);
        cudaFuncSetAttribute(k1_proj, cudaFuncAttributeMaxDynamicSharedMemorySize, K1_SMEM);
        cudaFuncSetAttribute(k2_attn, cudaFuncAttributeMaxDynamicSharedMemorySize, AT_SMEM);
        cudaFuncSetAttribute(k3_out, cudaFuncAttributeMaxDynamicSharedMemorySize, K3_SMEM);
        for (int i = 0; i < 10; i++) hs.key[i] = d_in[i];
        hs.key[10] = d_out;
        hs.ready = true;
    }
    launch(k1_proj, 128, 384, K1_SMEM, false, hs.xi, hs.wq, hs.wk, hs.wv, hs.w1, hs.qo, hs.ho, (const __nv_bfloat16*)d_in[0],
           (const __nv_bfloat16*)d_in[7], (float2*)hs.pRow, (float*)hs.pCol, (__nv_bfloat16*)hs.pKV, (float*)hs.pMax);
    launch(k2_attn, 128, 640, AT_SMEM, true, hs.hi, hs.w2, (const __nv_bfloat16*)hs.pQ, (const __nv_bfloat16*)hs.pKV,
           (const float*)hs.pMax, (const __nv_bfloat16*)d_in[9], (__nv_bfloat16*)hs.pO, (__nv_bfloat16*)hs.pG, (uint2*)hs.pRow, (uint2*)hs.pCol);
    launch(k3_out, 128, 256, K3_SMEM, true, hs.oi, hs.wo, hs.xi, hs.gi, hs.out);
}
```
